```python
import torch

def _softmax(x, axis=-1):
    return torch.softmax(x, dim=axis)
def _gelu(x):
    return torch.nn.functional.gelu(x, approximate="tanh")
def _silu(x):
    return torch.nn.functional.silu(x)
def _sigmoid(x):
    return torch.sigmoid(x)
def _layernorm(x, axis=-1, eps=1e-5):
    m = x.mean(dim=axis, keepdim=True)
    v = x.var(dim=axis, keepdim=True, unbiased=False)
    return (x - m) / torch.sqrt(v + eps)
def _scatter_add(tgt, idx, src, axis=0):
    return tgt.clone().index_add_(axis, idx, src)
def _segment_sum(src, seg, n):
    out = torch.zeros((n,) + src.shape[1:], dtype=src.dtype)
    return out.index_add_(0, seg, src)
def _pad(x, pw):
    flat = tuple(v for pair in reversed(pw) for v in pair)
    return torch.nn.functional.pad(x, flat)

kernel_name = 'standalone__detection_seg_dino__vision'

def setup_inputs():

    _w = (lambda a: (lambda t: t.to(torch.bfloat16) if t.is_floating_point() else t)(torch.as_tensor(a)))
    H = W = (512 // 2) * 2
    C = 192
    Nq = 16
    sc = C ** -0.5
    return {
        "q": _w((lambda *s: torch.randn(*s, dtype=torch.bfloat16) * 0.2)(1, Nq, C)),
        "f0": _w((lambda *s: torch.randn(*s, dtype=torch.bfloat16) * 3.2)(1, H, W, C)),
        "f1": _w((lambda *s: torch.randn(*s, dtype=torch.bfloat16) * 3.2)(1, H // 2, W // 2, C)),
        "wq": _w((lambda *s: torch.randn(*s, dtype=torch.bfloat16) * 1.6)(C, C) * sc),
        "wk": _w((lambda *s: torch.randn(*s, dtype=torch.bfloat16) * 1.6)(C, C) * sc),
        "wv": _w((lambda *s: torch.randn(*s, dtype=torch.bfloat16) * 3.2)(C, C) * sc),
        "wo": _w((lambda *s: torch.randn(*s, dtype=torch.bfloat16) * 3.2)(C, C) * sc),
    }

def reference(q, f0, f1, wq, wk, wv, wo):
    B, H, W, C = f0.shape
    f1u = (lambda x, n, axis: torch.repeat_interleave(x, n, dim=axis))((lambda x, n, axis: torch.repeat_interleave(x, n, dim=axis))(f1, 2, axis=1), 2, axis=2)
    fused = f0 + f1u
    feats = _layernorm(fused.reshape(B, H * W, C), axis=-1)
    qn = _layernorm(q, axis=-1)
    Q = torch.einsum("bnc,cd->bnd", qn, wq)
    K = torch.einsum("bmc,cd->bmd", feats, wk)
    V = torch.einsum("bmc,cd->bmd", feats, wv)
    scale = C ** -0.5
    logits = torch.einsum("bnd,bmd->bnm", Q, K) * scale
    attn = _softmax(logits, axis=-1)
    ctx = torch.einsum("bnm,bmd->bnd", attn, V)
    return q + torch.einsum("bnd,dc->bnc", ctx, wo)
```

```cpp
#include <cuda_runtime.h>
#include <cuda_bf16.h>
#include <cuda.h>
#include <stdint.h>

namespace {

constexpr int C = 192;
constexpr int NQ = 16;
constexpr int W0 = 512;
constexpr int W1 = 256;
constexpr int TP = 8;
constexpr int NT = W1 * W1 / TP;
constexpr int STAGE = TP * 5 * C * 2;
#define NS 12
#define NINIT 5
#define NPRE 3
constexpr int NTHREADS = 256;
constexpr int MAXG = 132;
constexpr int SPIN_LIMIT = 1 << 24;

constexpr int SM_STAGES = 0;
constexpr int SM_X = NS * STAGE;
constexpr int SM_P = SM_X + 12800;
constexpr int SM_MX = SM_P + 2048;
constexpr int SM_RS = SM_MX + 512;
constexpr int SM_BAR = SM_RS + 512;
constexpr int SM_FLAG = SM_BAR + 8 * NS;
constexpr int SM_TOTAL = SM_FLAG + 4 * NS;
constexpr int SMEM_BYTES = SM_TOTAL + 1024;

__device__ float g_part[MAXG * NQ * C];
__device__ float g_ml[MAXG * NQ * 2];
#define NCTR 2
__device__ int g_ctr[8 * 1024];
#define TS(i) do {} while (0)
#define TSD(i, dep) do {} while (0)
#define PH(i, dep) do {} while (0)

__device__ __forceinline__ uint32_t s2u(const void* p) { return (uint32_t)__cvta_generic_to_shared(p); }
__device__ __forceinline__ void mbar_init(uint32_t a, int c) { asm volatile("mbarrier.init.shared::cta.b64 [%0], %1;" ::"r"(a), "r"(c) : "memory"); }
__device__ __forceinline__ void mbar_expect(uint32_t a, uint32_t b) { asm volatile("mbarrier.arrive.expect_tx.shared::cta.b64 _, [%0], %1;" ::"r"(a), "r"(b) : "memory"); }
__device__ __forceinline__ void mbar_arrive(uint32_t a) { asm volatile("mbarrier.arrive.shared::cta.b64 _, [%0];" ::"r"(a) : "memory"); }
__device__ __forceinline__ void mbar_wait(uint32_t a, uint32_t ph) {
    uint32_t ok; int it = 0;
    do {
        asm volatile("{.reg .pred p; mbarrier.try_wait.parity.shared::cta.b64 p, [%1], %2; selp.u32 %0,1,0,p;}" : "=r"(ok) : "r"(a), "r"(ph) : "memory");
        if (++it > SPIN_LIMIT) __trap();
    } while (!ok);
}
__device__ __forceinline__ void bar_sync(int id, int n) { asm volatile("bar.sync %0, %1;" ::"r"(id), "r"(n) : "memory"); }
__device__ __forceinline__ void bar_arrive(int id, int n) { asm volatile("bar.arrive %0, %1;" ::"r"(id), "r"(n) : "memory"); }
__device__ __forceinline__ void ldsm4(uint32_t* r, uint32_t a) {
    asm volatile("ldmatrix.sync.aligned.m8n8.x4.shared.b16 {%0,%1,%2,%3}, [%4];" : "=r"(r[0]), "=r"(r[1]), "=r"(r[2]), "=r"(r[3]) : "r"(a) : "memory");
}
__device__ __forceinline__ void ldsm4t(uint32_t* r, uint32_t a) {
    asm volatile("ldmatrix.sync.aligned.m8n8.x4.trans.shared.b16 {%0,%1,%2,%3}, [%4];" : "=r"(r[0]), "=r"(r[1]), "=r"(r[2]), "=r"(r[3]) : "r"(a) : "memory");
}
__device__ __forceinline__ void ldsm2t(uint32_t* r, uint32_t a) {
    asm volatile("ldmatrix.sync.aligned.m8n8.x2.trans.shared.b16 {%0,%1}, [%2];" : "=r"(r[0]), "=r"(r[1]) : "r"(a) : "memory");
}
__device__ __forceinline__ void mma(float* d, uint32_t a0, uint32_t a1, uint32_t a2, uint32_t a3, uint32_t b0, uint32_t b1) {
    asm("mma.sync.aligned.m16n8k16.row.col.f32.bf16.bf16.f32 {%0,%1,%2,%3}, {%4,%5,%6,%7}, {%8,%9}, {%0,%1,%2,%3};"
        : "+f"(d[0]), "+f"(d[1]), "+f"(d[2]), "+f"(d[3]) : "r"(a0), "r"(a1), "r"(a2), "r"(a3), "r"(b0), "r"(b1));
}
__device__ __forceinline__ uint32_t hadd2(uint32_t a, uint32_t b) {
    uint32_t r; asm("add.rn.bf16x2 %0, %1, %2;" : "=r"(r) : "r"(a), "r"(b)); return r;
}
__device__ __forceinline__ uint32_t pack2(float lo, float hi) {
    uint32_t r; asm("cvt.rn.bf16x2.f32 %0, %1, %2;" : "=r"(r) : "f"(hi), "f"(lo)); return r;
}
__device__ __forceinline__ float bflo(uint32_t v) { return __uint_as_float(v << 16); }
__device__ __forceinline__ float bfhi(uint32_t v) { return __uint_as_float(v & 0xffff0000u); }
__device__ __forceinline__ float ex2(float x) { float r; asm("ex2.approx.ftz.f32 %0, %1;" : "=f"(r) : "f"(x)); return r; }
__device__ __forceinline__ void sts128(uint32_t a, uint32_t x, uint32_t y, uint32_t z, uint32_t w) {
    asm volatile("st.shared.v4.b32 [%0], {%1,%2,%3,%4};" ::"r"(a), "r"(x), "r"(y), "r"(z), "r"(w) : "memory");
}
__device__ __forceinline__ void sts64(uint32_t a, uint32_t x, uint32_t y) {
    asm volatile("st.shared.v2.b32 [%0], {%1,%2};" ::"r"(a), "r"(x), "r"(y) : "memory");
}
__device__ __forceinline__ void sts32(uint32_t a, uint32_t x) { asm volatile("st.shared.b32 [%0], %1;" ::"r"(a), "r"(x) : "memory"); }
__device__ __forceinline__ uint4 lds128(uint32_t a) {
    uint4 v; asm volatile("ld.shared.v4.b32 {%0,%1,%2,%3}, [%4];" : "=r"(v.x), "=r"(v.y), "=r"(v.z), "=r"(v.w) : "r"(a) : "memory"); return v;
}
__device__ __forceinline__ uint32_t lds32(uint32_t a) { uint32_t v; asm volatile("ld.shared.b32 %0, [%1];" : "=r"(v) : "r"(a) : "memory"); return v; }
__device__ __forceinline__ int grab_tile(int* ctr) {
    int v; asm volatile("atom.relaxed.gpu.global.inc.u32 %0, [%1], 0x7fffffff;" : "=r"(v) : "l"(ctr) : "memory"); return v;
}
__device__ __forceinline__ uint32_t opaque(uint32_t v) { uint32_t r; asm volatile("mov.b32 %0, %1;" : "=r"(r) : "r"(v)); return r; }
__device__ __forceinline__ float rsq(float x) { float r; asm("rsqrt.approx.ftz.f32 %0, %1;" : "=f"(r) : "f"(x)); return r; }
__device__ __forceinline__ float f(uint32_t v) { return __uint_as_float(v); }
__device__ __forceinline__ uint32_t u(float v) { return __float_as_uint(v); }

constexpr uint32_t ONES = 0x3F803F80u;
constexpr float QSCALE = 0.07216878364870322f * 1.4426950408889634f;

__device__ __forceinline__ void issue_tile(const CUtensorMap* m0, const CUtensorMap* m1, uint32_t sb, int s, int tl, uint64_t pol) {
    const uint32_t full = sb + SM_BAR + s * 8, dst = sb + SM_STAGES + s * STAGE;
    const int par = tl * TP, y = par >> 8, x = par & 255;
    mbar_expect(full, STAGE);
    asm volatile("cp.async.bulk.tensor.5d.shared::cluster.global.mbarrier::complete_tx::bytes.L2::cache_hint [%0], [%1, {%3,%4,%3,%3,%5}], [%2], %6;"
                 ::"r"(dst), "l"(m0), "r"(full), "r"(0), "r"(x), "r"(2 * y), "l"(pol) : "memory");
    asm volatile("cp.async.bulk.tensor.4d.shared::cluster.global.mbarrier::complete_tx::bytes.L2::cache_hint [%0], [%1, {%3,%4,%3,%5}], [%2], %6;"
                 ::"r"(dst + TP * 4 * C * 2), "l"(m1), "r"(full), "r"(0), "r"(x), "r"(y), "l"(pol) : "memory");
}

__global__ void __launch_bounds__(NTHREADS, 1)
attn_main(const __grid_constant__ CUtensorMap m0, const __grid_constant__ CUtensorMap m1,
          const char* __restrict__ f0, const char* __restrict__ f1,
          const __nv_bfloat16* __restrict__ q, const __nv_bfloat16* __restrict__ wq, const __nv_bfloat16* __restrict__ wk)
{
    extern __shared__ char smem_raw[];
    const uint32_t sb = (s2u(smem_raw) + 1023u) & ~1023u;
    const int warp = threadIdx.x >> 5, lane = threadIdx.x & 31;
    const int G = gridDim.x, b = blockIdx.x;

    uint64_t pol; asm volatile("createpolicy.fractional.L2::evict_first.b64 %0, 1.0;" : "=l"(pol));
    if (warp == 7) {
        if (lane < 3 * NPRE) {
            const int tl = b + (lane / 3) * G, which = lane % 3;
            const int par = tl * TP, y = par >> 8, x = par & 255;
            const char* p = which < 2 ? f0 + ((size_t)(2 * y + which) * W0 + 2 * x) * (C * 2) : f1 + ((size_t)y * W1 + x) * (C * 2);
            asm volatile("cp.async.bulk.prefetch.L2.global [%0], %1;" ::"l"(p), "r"(which < 2 ? TP * 2 * C * 2 : TP * C * 2) : "memory");
        }
    } else if (warp == 6) {
        if (lane == 0) {
            TS(0);
            asm volatile("prefetch.tensormap [%0];" ::"l"(&m0) : "memory");
            asm volatile("prefetch.tensormap [%0];" ::"l"(&m1) : "memory");
        }
        if (lane < NS) { mbar_init(sb + SM_BAR + lane * 8, 1); sts32(sb + SM_FLAG + lane * 4, 0); }
        asm volatile("fence.mbarrier_init.release.cluster;" ::: "memory");
        __syncwarp();
        if (lane == 0) {
            for (int s = 0; s < NINIT; s++) issue_tile(&m0, &m1, sb, s, b + s * G, pol);
        }
        __syncwarp();
    }
    const bool elected = (threadIdx.x & 127) == 96;
    uint32_t smid; asm("mov.u32 %0, %%smid;" : "=r"(smid));
    const int cidx = ((warp >> 2) + 2 * smid) & (NCTR - 1);
    int* const ctr = g_ctr + cidx * 1024;
    int sseq = b + (NS + (warp >> 2)) * G;
    bool more = elected;

    const int g = lane >> 2, t = lane & 3;
    const int grp = warp >> 2, cw = warp & 3;
    uint32_t qa[48];
    float r_lo, r_hi;
    {
        uint4 wkf[3][6];
#pragma unroll
        for (int i = 0; i < 3; i++)
#pragma unroll
            for (int jj = 0; jj < 6; jj++)
                wkf[i][jj] = __ldg(reinterpret_cast<const uint4*>(wk + (24 * warp + 8 * i + g) * C + 32 * jj + 8 * t));
        if (warp < 6) {
            uint4 ql[6], qh[6];
#pragma unroll
            for (int jj = 0; jj < 6; jj++) {
                ql[jj] = __ldg(reinterpret_cast<const uint4*>(q + g * C + 32 * jj + 8 * t));
                qh[jj] = __ldg(reinterpret_cast<const uint4*>(q + (g + 8) * C + 32 * jj + 8 * t));
            }
            float acc[4][4];
#pragma unroll
            for (int v = 0; v < 4; v++) acc[v][0] = acc[v][1] = acc[v][2] = acc[v][3] = 0.f;
            uint2 wv_[2][3][8];
#pragma unroll
            for (int jj = 0; jj < 3; jj++)
#pragma unroll
                for (int i = 0; i < 8; i++)
                    wv_[0][jj][i] = __ldg(reinterpret_cast<const uint2*>(wq + (32 * jj + 8 * t + i) * C + 32 * warp + 4 * g));
            float sl = 0.f, sh = 0.f;
#pragma unroll
            for (int jj = 0; jj < 6; jj++) {
                const uint32_t a[4] = {ql[jj].x, ql[jj].y, ql[jj].z, ql[jj].w}, c[4] = {qh[jj].x, qh[jj].y, qh[jj].z, qh[jj].w};
#pragma unroll
                for (int e = 0; e < 4; e++) { sl += bflo(a[e]) + bfhi(a[e]); sh += bflo(c[e]) + bfhi(c[e]); }
            }
            sl += __shfl_xor_sync(~0u, sl, 1); sh += __shfl_xor_sync(~0u, sh, 1);
            sl += __shfl_xor_sync(~0u, sl, 2); sh += __shfl_xor_sync(~0u, sh, 2);
            if (threadIdx.x == 0) TSD(5, u(sl));
            const float ml = sl * (1.f / C), mh = sh * (1.f / C);
            float vl = 0.f, vh = 0.f;
#pragma unroll
            for (int jj = 0; jj < 6; jj++) {
                const uint32_t a[4] = {ql[jj].x, ql[jj].y, ql[jj].z, ql[jj].w}, c[4] = {qh[jj].x, qh[jj].y, qh[jj].z, qh[jj].w};
#pragma unroll
                for (int e = 0; e < 4; e++) {
                    float d0 = bflo(a[e]) - ml, d1 = bfhi(a[e]) - ml, d2 = bflo(c[e]) - mh, d3 = bfhi(c[e]) - mh;
                    vl += d0 * d0 + d1 * d1; vh += d2 * d2 + d3 * d3;
                }
            }
            vl += __shfl_xor_sync(~0u, vl, 1); vh += __shfl_xor_sync(~0u, vh, 1);
            vl += __shfl_xor_sync(~0u, vl, 2); vh += __shfl_xor_sync(~0u, vh, 2);
            const float rl = rsq(vl * (1.f / C) + 1e-5f), rh = rsq(vh * (1.f / C) + 1e-5f);
            uint32_t nl[6][4], nh[6][4];
#pragma unroll
            for (int jj = 0; jj < 6; jj++) {
                const uint32_t a[4] = {ql[jj].x, ql[jj].y, ql[jj].z, ql[jj].w}, c[4] = {qh[jj].x, qh[jj].y, qh[jj].z, qh[jj].w};
#pragma unroll
                for (int e = 0; e < 4; e++) {
                    nl[jj][e] = pack2((bflo(a[e]) - ml) * rl, (bfhi(a[e]) - ml) * rl);
                    nh[jj][e] = pack2((bflo(c[e]) - mh) * rh, (bfhi(c[e]) - mh) * rh);
                }
            }
#pragma unroll
            for (int jj = 0; jj < 3; jj++)
#pragma unroll
                for (int i = 0; i < 8; i++)
                    wv_[1][jj][i] = __ldg(reinterpret_cast<const uint2*>(wq + (96 + 32 * jj + 8 * t + i) * C + 32 * warp + 4 * g));
#pragma unroll
            for (int hf = 0; hf < 2; hf++)
#pragma unroll
                for (int j3 = 0; j3 < 3; j3++)
#pragma unroll
                    for (int h = 0; h < 2; h++) {
                        const int jj = hf * 3 + j3;
                        const uint2* w = &wv_[hf][j3][4 * h];
#pragma unroll
                        for (int v = 0; v < 4; v++) {
                            const uint32_t sel = (v & 1) ? 0x7632u : 0x5410u;
                            const uint32_t b0 = __byte_perm(v < 2 ? w[0].x : w[0].y, v < 2 ? w[1].x : w[1].y, sel);
                            const uint32_t b1 = __byte_perm(v < 2 ? w[2].x : w[2].y, v < 2 ? w[3].x : w[3].y, sel);
                            mma(acc[v], nl[jj][2 * h], nh[jj][2 * h], nl[jj][2 * h + 1], nh[jj][2 * h + 1], b0, b1);
                        }
                    }
            if (threadIdx.x == 0) TSD(6, u(acc[0][0] + acc[1][0] + acc[2][0] + acc[3][0]));
            sts128(sb + SM_X + (warp * 2 + 0) * 512 + lane * 16, pack2(acc[0][0], acc[1][0]), pack2(acc[2][0], acc[3][0]),
                   pack2(acc[0][1], acc[1][1]), pack2(acc[2][1], acc[3][1]));
            sts128(sb + SM_X + (warp * 2 + 1) * 512 + lane * 16, pack2(acc[0][2], acc[1][2]), pack2(acc[2][2], acc[3][2]),
                   pack2(acc[0][3], acc[1][3]), pack2(acc[2][3], acc[3][3]));
        }
        bar_sync(2, 256);
        if (threadIdx.x == 0) TS(7);
        float kq[3][2][4];
#pragma unroll
        for (int i = 0; i < 3; i++)
#pragma unroll
            for (int e = 0; e < 4; e++) kq[i][0][e] = kq[i][1][e] = 0.f;
#pragma unroll
        for (int jj = 0; jj < 6; jj++) {
            const uint4 lo = lds128(sb + SM_X + (jj * 2 + 0) * 512 + lane * 16);
            const uint4 hi = lds128(sb + SM_X + (jj * 2 + 1) * 512 + lane * 16);
#pragma unroll
            for (int i = 0; i < 3; i++) {
                mma(kq[i][0], lo.x, hi.x, lo.y, hi.y, wkf[i][jj].x, wkf[i][jj].y);
                mma(kq[i][1], lo.z, hi.z, lo.w, hi.w, wkf[i][jj].z, wkf[i][jj].w);
            }
        }
        float sl = 0.f, sh = 0.f;
#pragma unroll
        for (int i = 0; i < 3; i++) {
#pragma unroll
            for (int e = 0; e < 4; e++) kq[i][0][e] += kq[i][1][e];
            sl += kq[i][0][0] + kq[i][0][1]; sh += kq[i][0][2] + kq[i][0][3];
        }
        sl += __shfl_xor_sync(~0u, sl, 1); sh += __shfl_xor_sync(~0u, sh, 1);
        sl += __shfl_xor_sync(~0u, sl, 2); sh += __shfl_xor_sync(~0u, sh, 2);
        if (threadIdx.x == 0) TSD(8, u(sl));
        if (t < 2) sts32(sb + SM_RS + ((g + 8 * t) * 8 + warp) * 4, u(t ? sh : sl));
        bar_sync(2, 256);
        {
            const uint4 a0 = lds128(sb + SM_RS + g * 32), a1 = lds128(sb + SM_RS + g * 32 + 16);
            const uint4 c0 = lds128(sb + SM_RS + (g + 8) * 32), c1 = lds128(sb + SM_RS + (g + 8) * 32 + 16);
            const float ml = (((f(a0.x) + f(a0.y)) + (f(a0.z) + f(a0.w))) + ((f(a1.x) + f(a1.y)) + (f(a1.z) + f(a1.w)))) * (1.f / C);
            const float mh = (((f(c0.x) + f(c0.y)) + (f(c0.z) + f(c0.w))) + ((f(c1.x) + f(c1.y)) + (f(c1.z) + f(c1.w)))) * (1.f / C);
#pragma unroll
            for (int i = 0; i < 3; i++) {
                const int uu = 3 * warp + i;
                sts64(sb + SM_X + 6144 + (uu >> 1) * 512 + lane * 16 + (uu & 1) * 8,
                      pack2((kq[i][0][0] - ml) * QSCALE, (kq[i][0][1] - ml) * QSCALE),
                      pack2((kq[i][0][2] - mh) * QSCALE, (kq[i][0][3] - mh) * QSCALE));
            }
        }
        bar_sync(2, 256);
        float rr[4] = {0.f, 0.f, 0.f, 0.f};
#pragma unroll
        for (int kk = 0; kk < 12; kk++) {
            const uint4 v = lds128(sb + SM_X + 6144 + kk * 512 + lane * 16);
            qa[4 * kk] = v.x; qa[4 * kk + 1] = v.y; qa[4 * kk + 2] = v.z; qa[4 * kk + 3] = v.w;
            mma(rr, v.x, v.y, v.z, v.w, ONES, ONES);
        }
        r_lo = rr[0]; r_hi = rr[2];
    }
    if (threadIdx.x == 0) TS(1);
    if (elected) {
        for (int s = NINIT + ((NINIT ^ grp) & 1); s < NS; s += 2) issue_tile(&m0, &m1, sb, s, b + s * G, pol);
    }
    __syncwarp();

    const int xp = lane & 7, mi = lane >> 3;
    const uint32_t offS = opaque(xp * 128 + ((mi ^ xp) << 4));
    uint32_t offT[6], offT1[2];
#pragma unroll
    for (int i = 0; i < 6; i++) {
        const int J = 6 * cw + i;
        offT[i] = opaque(mi * 3072 + (J >> 3) * 1024 + xp * 128 + (((J & 7) ^ xp) << 4));
    }
    {
        const int J = 6 * cw + mi, J2 = 6 * cw + 4 + (mi & 1);
        offT1[0] = opaque(12288 + (J >> 3) * 1024 + xp * 128 + (((J & 7) ^ xp) << 4));
        offT1[1] = opaque(12288 + (J2 >> 3) * 1024 + xp * 128 + (((J2 & 7) ^ xp) << 4));
    }
    const uint32_t mxw = opaque(sb + SM_MX + grp * 256 + ((g + 8 * t) * 4 + cw) * 4);
    const uint32_t offS0 = opaque(offS + cw * 3072);
    const int shl = opaque(9 * t);
    const uint32_t mxr = sb + SM_MX + grp * 256 + g * 16;
    const uint32_t pw = sb + SM_P + grp * 1024 + (cw >> 1) * 512 + lane * 16 + (cw & 1) * 8;
    const uint32_t pr = sb + SM_P + grp * 1024 + lane * 16;
    const int barid = 3 + grp;

    float acc[6][4];
#pragma unroll
    for (int i = 0; i < 6; i++) acc[i][0] = acc[i][1] = acc[i][2] = acc[i][3] = 0.f;
    float m_lo = -INFINITY, m_hi = -INFINITY, l_lo = 0.f, l_hi = 0.f;
    int s = grp; uint32_t ph = 0;
    while (true) {
        if (lds32(sb + SM_FLAG + s * 4)) break;
        mbar_wait(sb + SM_BAR + s * 8, ph);
        PH(0, 0);
        int nxt = NT;
        if (more) nxt = grab_tile(ctr);
        const uint32_t st = sb + SM_STAGES + s * STAGE;
        float sc[2][4], gr[2][4];
#pragma unroll
        for (int e = 0; e < 4; e++) sc[0][e] = sc[1][e] = gr[0][e] = gr[1][e] = 0.f;
        const uint32_t a0e = st + offS0, a1e = st + 12288 + offS;
#pragma unroll
        for (int qq = 0; qq < 6; qq++) {
            uint32_t x[4], y[4];
            ldsm4(x, (a0e ^ ((qq & 1) << 6)) + (qq >> 1) * 1024);
            ldsm4(y, (a1e ^ ((qq & 1) << 6)) + (qq >> 1) * 1024);
#pragma unroll
            for (int e = 0; e < 4; e++) x[e] = hadd2(x[e], y[e]);
            mma(gr[0], x[0], ONES, x[1], ONES, x[0], x[1]);
            mma(gr[1], x[2], ONES, x[3], ONES, x[2], x[3]);
            mma(sc[0], qa[8 * qq], qa[8 * qq + 1], qa[8 * qq + 2], qa[8 * qq + 3], x[0], x[1]);
            mma(sc[1], qa[8 * qq + 4], qa[8 * qq + 5], qa[8 * qq + 6], qa[8 * qq + 7], x[2], x[3]);
        }
        uint32_t xt[6][4], yt[6];
        ldsm4t(yt, st + offT1[0]);
        ldsm2t(yt + 4, st + offT1[1]);
#pragma unroll
        for (int i = 0; i < 6; i++) ldsm4t(xt[i], st + offT[i]);

        const float ss0 = __shfl_sync(~0u, gr[0][0] + gr[1][0], shl);
        const float ss1 = __shfl_sync(~0u, gr[0][1] + gr[1][1], shl + 4);
        const float mu0 = (gr[0][2] + gr[1][2]) * (1.f / C), mu1 = (gr[0][3] + gr[1][3]) * (1.f / C);
        const float rs0 = rsq(fmaxf(fmaf(-mu0, mu0, ss0 * (1.f / C)), 0.f) + 1e-5f);
        const float rs1 = rsq(fmaxf(fmaf(-mu1, mu1, ss1 * (1.f / C)), 0.f) + 1e-5f);
        const float s0 = fmaf(-mu0, r_lo, sc[0][0] + sc[1][0]) * rs0;
        const float s1 = fmaf(-mu1, r_lo, sc[0][1] + sc[1][1]) * rs1;
        const float s2 = fmaf(-mu0, r_hi, sc[0][2] + sc[1][2]) * rs0;
        const float s3 = fmaf(-mu1, r_hi, sc[0][3] + sc[1][3]) * rs1;
        PH(1, u(s0 + s2));
        float xl = fmaxf(s0, s1), xh = fmaxf(s2, s3);
        xl = fmaxf(xl, __shfl_xor_sync(~0u, xl, 1)); xh = fmaxf(xh, __shfl_xor_sync(~0u, xh, 1));
        xl = fmaxf(xl, __shfl_xor_sync(~0u, xl, 2)); xh = fmaxf(xh, __shfl_xor_sync(~0u, xh, 2));
        if (t < 2) sts32(mxw, u(t ? xh : xl));
#pragma unroll
        for (int i = 0; i < 6; i++)
#pragma unroll
            for (int e = 0; e < 4; e++) xt[i][e] = hadd2(xt[i][e], yt[i]);
        bar_sync(barid, 128);
        PH(2, 0);
        const uint4 ml4 = lds128(mxr), mh4 = lds128(mxr + 128);
        const float nl = fmaxf(fmaxf(fmaxf(f(ml4.x), f(ml4.y)), fmaxf(f(ml4.z), f(ml4.w))), m_lo);
        const float nh = fmaxf(fmaxf(fmaxf(f(mh4.x), f(mh4.y)), fmaxf(f(mh4.z), f(mh4.w))), m_hi);
        const float p0 = ex2(s0 - nl), p1 = ex2(s1 - nl), p2 = ex2(s2 - nh), p3 = ex2(s3 - nh);
        sts64(pw, pack2(p0 * rs0, p1 * rs1), pack2(p2 * rs0, p3 * rs1));
        const float al = ex2(m_lo - nl), ah = ex2(m_hi - nh);
        m_lo = nl; m_hi = nh;
        l_lo = fmaf(l_lo, al, p0 + p1); l_hi = fmaf(l_hi, ah, p2 + p3);
#pragma unroll
        for (int i = 0; i < 6; i++) { acc[i][0] *= al; acc[i][1] *= al; acc[i][2] *= ah; acc[i][3] *= ah; }
        bar_sync(barid, 128);
        PH(3, 0);
        const uint4 pa = lds128(pr), pb = lds128(pr + 512);
#pragma unroll
        for (int i = 0; i < 6; i++) mma(acc[i], pa.x, pa.y, pa.z, pa.w, xt[i][0], xt[i][1]);
#pragma unroll
        for (int i = 0; i < 6; i++) mma(acc[i], pb.x, pb.y, pb.z, pb.w, xt[i][2], xt[i][3]);
        PH(4, u(acc[5][0]));
        PH(5, nxt);
        if (elected) {
            const int tl = nxt * NCTR + cidx + NS * G;
            if (tl < NT) issue_tile(&m0, &m1, sb, s, tl, pol);
            else { more = false; sts32(sb + SM_FLAG + s * 4, 1); }
        }
        __syncwarp();
        PH(6, 0);
        s += 2;
        if (s >= NS) { s -= NS; ph ^= 1; }
    }
    if (threadIdx.x == grp * 128) TS(2 + grp);

    l_lo += __shfl_xor_sync(~0u, l_lo, 1); l_hi += __shfl_xor_sync(~0u, l_hi, 1);
    l_lo += __shfl_xor_sync(~0u, l_lo, 2); l_hi += __shfl_xor_sync(~0u, l_hi, 2);
    if (t < 2) sts32(sb + SM_RS + ((g + 8 * t) * 8 + warp) * 4, u(t ? l_hi : l_lo));
    float own[3][4];
#pragma unroll
    for (int i = 0; i < 3; i++) {
#pragma unroll
        for (int e = 0; e < 4; e++) own[i][e] = grp ? acc[3 + i][e] : acc[i][e];
        sts128(sb + SM_X + (warp * 3 + i) * 512 + lane * 16, u(grp ? acc[i][0] : acc[3 + i][0]), u(grp ? acc[i][1] : acc[3 + i][1]),
               u(grp ? acc[i][2] : acc[3 + i][2]), u(grp ? acc[i][3] : acc[3 + i][3]));
    }
    if (cw == 0 && t < 2) sts32(sb + SM_X + 12288 + (grp * 16 + g + 8 * t) * 4, u(t ? m_hi : m_lo));
    bar_sync(2, 256);
    {
        const float ol = f(lds32(sb + SM_X + 12288 + ((grp ^ 1) * 16 + g) * 4)), oh = f(lds32(sb + SM_X + 12288 + ((grp ^ 1) * 16 + g + 8) * 4));
        const float nl = fmaxf(ol, m_lo), nh = fmaxf(oh, m_hi);
        const float al = ex2(m_lo - nl), ah = ex2(m_hi - nh), bl = ex2(ol - nl), bh = ex2(oh - nh);
        float* dst = g_part + (size_t)b * NQ * C + 48 * cw + 24 * grp + 2 * t;
#pragma unroll
        for (int i = 0; i < 3; i++) {
            const uint4 o = lds128(sb + SM_X + ((warp ^ 4) * 3 + i) * 512 + lane * 16);
            *reinterpret_cast<float2*>(dst + g * C + 8 * i) = make_float2(own[i][0] * al + f(o.x) * bl, own[i][1] * al + f(o.y) * bl);
            *reinterpret_cast<float2*>(dst + (g + 8) * C + 8 * i) = make_float2(own[i][2] * ah + f(o.z) * bh, own[i][3] * ah + f(o.w) * bh);
        }
        if (warp == 0 && t < 2) {
            const int row = g + 8 * t;
            const uint4 o = lds128(sb + SM_RS + row * 32), w = lds128(sb + SM_RS + row * 32 + 16);
            const float L = ((f(o.x) + f(o.y)) + (f(o.z) + f(o.w))) * (t ? ah : al) + ((f(w.x) + f(w.y)) + (f(w.z) + f(w.w))) * (t ? bh : bl);
            *reinterpret_cast<float2*>(g_ml + (b * NQ + row) * 2) = make_float2(t ? nh : nl, L);
        }
    }
    if (threadIdx.x == 0) TS(4);
}

__global__ void __launch_bounds__(C)
attn_final(const __nv_bfloat16* __restrict__ q, const __nv_bfloat16* __restrict__ wv, const __nv_bfloat16* __restrict__ wo,
           __nv_bfloat16* __restrict__ out, int G)
{
    __shared__ float wgt[MAXG], v0[C], v1[C], red[8];
    const int n = blockIdx.x, c = threadIdx.x;
    if (n == 0 && c < NCTR) g_ctr[c * 1024] = 0;
    float M = -INFINITY;
    for (int s = 0; s < G; s++) M = fmaxf(M, g_ml[(s * NQ + n) * 2]);
    if (c < G) wgt[c] = exp2f(g_ml[(c * NQ + n) * 2] - M);
    __syncthreads();
    float L = 0.f, a = 0.f;
    for (int s = 0; s < G; s++) { L += wgt[s] * g_ml[(s * NQ + n) * 2 + 1]; a += wgt[s] * g_part[(s * NQ + n) * C + c]; }
    a /= L;
    float sum = a;
    for (int o = 16; o; o >>= 1) sum += __shfl_xor_sync(~0u, sum, o);
    if ((c & 31) == 0) red[c >> 5] = sum;
    __syncthreads();
    const float mean = (red[0] + red[1] + red[2] + red[3] + red[4] + red[5]) * (1.f / C);
    v0[c] = a - mean;
    __syncthreads();
    float x = 0.f;
    for (int k = 0; k < C; k++) x += v0[k] * __bfloat162float(wv[k * C + c]);
    v1[c] = x;
    __syncthreads();
    float y = 0.f;
    for (int k = 0; k < C; k++) y += v1[k] * __bfloat162float(wo[k * C + c]);
    out[n * C + c] = __float2bfloat16(__bfloat162float(q[n * C + c]) + y);
}

typedef CUresult (*EncodeFn)(CUtensorMap*, CUtensorMapDataType, cuuint32_t, void*, const cuuint64_t*, const cuuint64_t*,
                             const cuuint32_t*, const cuuint32_t*, CUtensorMapInterleave, CUtensorMapSwizzle,
                             CUtensorMapL2promotion, CUtensorMapFloatOOBfill);

}

extern "C" void kernel_launch(void* const* d_in, const int* in_sizes, int n_in, void* d_out, int out_size) {
    const __nv_bfloat16* q = (const __nv_bfloat16*)d_in[0];
    char* f0 = (char*)d_in[1];
    char* f1 = (char*)d_in[2];
    const __nv_bfloat16* wq = (const __nv_bfloat16*)d_in[3];
    const __nv_bfloat16* wk = (const __nv_bfloat16*)d_in[4];
    const __nv_bfloat16* wv = (const __nv_bfloat16*)d_in[5];
    const __nv_bfloat16* wo = (const __nv_bfloat16*)d_in[6];

    static EncodeFn enc = nullptr;
    static int grid = 0;
    if (!enc) {
        void* fn = nullptr; cudaDriverEntryPointQueryResult qr;
        cudaGetDriverEntryPoint("cuTensorMapEncodeTiled", &fn, cudaEnableDefault, &qr);
        enc = (EncodeFn)fn;
        int dev = 0, sms = 0;
        cudaGetDevice(&dev);
        cudaDeviceGetAttribute(&sms, cudaDevAttrMultiProcessorCount, dev);
        grid = sms < MAXG ? sms : MAXG;
        cudaFuncSetAttribute(attn_main, cudaFuncAttributeMaxDynamicSharedMemorySize, SMEM_BYTES);
    }
    CUtensorMap m0, m1;
    {
        cuuint64_t dims[5] = {64, W1, 3, 2, W0};
        cuuint64_t str[4] = {2 * C * 2, 128, C * 2, (cuuint64_t)W0 * C * 2};
        cuuint32_t box[5] = {64, TP, 3, 2, 2}, es[5] = {1, 1, 1, 1, 1};
        enc(&m0, CU_TENSOR_MAP_DATA_TYPE_BFLOAT16, 5, f0, dims, str, box, es, CU_TENSOR_MAP_INTERLEAVE_NONE,
            CU_TENSOR_MAP_SWIZZLE_128B, CU_TENSOR_MAP_L2_PROMOTION_NONE, CU_TENSOR_MAP_FLOAT_OOB_FILL_NONE);
    }
    {
        cuuint64_t dims[4] = {64, W1, 3, W1};
        cuuint64_t str[3] = {C * 2, 128, (cuuint64_t)W1 * C * 2};
        cuuint32_t box[4] = {64, TP, 3, 1}, es[4] = {1, 1, 1, 1};
        enc(&m1, CU_TENSOR_MAP_DATA_TYPE_BFLOAT16, 4, f1, dims, str, box, es, CU_TENSOR_MAP_INTERLEAVE_NONE,
            CU_TENSOR_MAP_SWIZZLE_128B, CU_TENSOR_MAP_L2_PROMOTION_NONE, CU_TENSOR_MAP_FLOAT_OOB_FILL_NONE);
    }
    attn_main<<<grid, NTHREADS, SMEM_BYTES, cudaStreamPerThread>>>(m0, m1, f0, f1, q, wq, wk);
    attn_final<<<NQ, C, 0, cudaStreamPerThread>>>(q, wv, wo, (__nv_bfloat16*)d_out, grid);
}
```

```cpp
#include <cuda_runtime.h>
#include <cuda_bf16.h>
#include <cuda.h>
#include <stdint.h>

namespace {

constexpr int C = 192;
constexpr int NQ = 16;
constexpr int W0 = 512;
constexpr int W1 = 256;
constexpr int TP = 8;
constexpr int NT = W1 * W1 / TP;
constexpr int STAGE = TP * 5 * C * 2;
#define NS 12
#define D0 1
#define D1 4
#define D2 2
#define NRAMP 3
#define TAILT 1000
#define QSLEEP 700
#define WSL 24
#define INITT 2500
#define NST 2
#define NPRE 2
constexpr int NTHREADS = 384;
constexpr int MAXG = 132;
constexpr int NRD = 128;
constexpr int NSRC = 12;
constexpr int SPIN_LIMIT = 1 << 22;
constexpr uint32_t EMPTY = 0xFFFFFFFFu;

constexpr int SM_STAGES = 0;
constexpr int SM_X = NS * STAGE;
constexpr int SM_QK = SM_X + 12800;
constexpr int SM_W = SM_QK + 6144;
constexpr int WP = 196;
constexpr int SM_P = SM_W + 24 * WP * 4;
constexpr int SM_MX = SM_P + 2048;
constexpr int SM_RS = SM_MX + 512;
constexpr int SM_RED = SM_RS + 512;
constexpr int SM_CS = SM_RED + 1024;
constexpr int SM_BAR = SM_CS + 256;
constexpr int SM_WBAR = SM_BAR + 16 * NS;
constexpr int SM_LATE = SM_WBAR + 64;
constexpr int SM_FLAG = SM_LATE + 16;
constexpr int SM_TOTAL = SM_FLAG + 4 * NS;
constexpr int SMEM_BYTES = SM_TOTAL + 1024;
static_assert(SMEM_BYTES <= 232448, "smem");

struct Scratch {
    uint4 x1[NRD * MAXG * 8];
    uint4 x2[NQ * C / 4];
    uint4 qk[NSRC * 32];
    unsigned ctr[64];
};
__device__ __align__(128) Scratch g_scratch;
#define g_x1 (scr->x1)
#define g_x2 (scr->x2)
#define g_qk (scr->qk)
#define g_ctr (scr->ctr)
#define g_ts (scr->ts)
#define g_tr (scr->tr)
#define TR(k, i) do {} while (0)
#define TS(i) do {} while (0)
#define TSD(i, dep) do {} while (0)
#define TSX(i, dep) do {} while (0)
#define TSP(i, dep) do {} while (0)
#define TSE(i) TS(i)
#define CK_(i, dep) do {} while (0)
#define PH(i, dep) do {} while (0)

__device__ __forceinline__ uint32_t s2u(const void* p) { return (uint32_t)__cvta_generic_to_shared(p); }
__device__ __forceinline__ void mbar_init(uint32_t a, int c) { asm volatile("mbarrier.init.shared::cta.b64 [%0], %1;" ::"r"(a), "r"(c) : "memory"); }
__device__ __forceinline__ void mbar_expect(uint32_t a, uint32_t b) { asm volatile("mbarrier.arrive.expect_tx.shared::cta.b64 _, [%0], %1;" ::"r"(a), "r"(b) : "memory"); }
__device__ __forceinline__ void mbar_arrive(uint32_t a) { asm volatile("mbarrier.arrive.shared::cta.b64 _, [%0];" ::"r"(a) : "memory"); }
__device__ __forceinline__ void mbar_wait(uint32_t a, uint32_t ph) {
    uint32_t ok; int it = 0;
    do {
        asm volatile("{.reg .pred p; mbarrier.try_wait.parity.shared::cta.b64 p, [%1], %2; selp.u32 %0,1,0,p;}" : "=r"(ok) : "r"(a), "r"(ph) : "memory");
        if (++it > SPIN_LIMIT) __trap();
    } while (!ok);
}
__device__ __forceinline__ void bar_sync(int id, int n) { asm volatile("bar.sync %0, %1;" ::"r"(id), "r"(n) : "memory"); }
__device__ __forceinline__ void bar_arrive(int id, int n) { asm volatile("bar.arrive %0, %1;" ::"r"(id), "r"(n) : "memory"); }
__device__ __forceinline__ void ldsm4(uint32_t* r, uint32_t a) {
    asm volatile("ldmatrix.sync.aligned.m8n8.x4.shared.b16 {%0,%1,%2,%3}, [%4];" : "=r"(r[0]), "=r"(r[1]), "=r"(r[2]), "=r"(r[3]) : "r"(a) : "memory");
}
__device__ __forceinline__ void ldsm4t(uint32_t* r, uint32_t a) {
    asm volatile("ldmatrix.sync.aligned.m8n8.x4.trans.shared.b16 {%0,%1,%2,%3}, [%4];" : "=r"(r[0]), "=r"(r[1]), "=r"(r[2]), "=r"(r[3]) : "r"(a) : "memory");
}
__device__ __forceinline__ void ldsm2t(uint32_t* r, uint32_t a) {
    asm volatile("ldmatrix.sync.aligned.m8n8.x2.trans.shared.b16 {%0,%1}, [%2];" : "=r"(r[0]), "=r"(r[1]) : "r"(a) : "memory");
}
__device__ __forceinline__ void mma(float* d, uint32_t a0, uint32_t a1, uint32_t a2, uint32_t a3, uint32_t b0, uint32_t b1) {
    asm("mma.sync.aligned.m16n8k16.row.col.f32.bf16.bf16.f32 {%0,%1,%2,%3}, {%4,%5,%6,%7}, {%8,%9}, {%0,%1,%2,%3};"
        : "+f"(d[0]), "+f"(d[1]), "+f"(d[2]), "+f"(d[3]) : "r"(a0), "r"(a1), "r"(a2), "r"(a3), "r"(b0), "r"(b1));
}
__device__ __forceinline__ void mma8(float* d, uint32_t a0, uint32_t a1, uint32_t b0) {
    asm("mma.sync.aligned.m16n8k8.row.col.f32.bf16.bf16.f32 {%0,%1,%2,%3}, {%4,%5}, {%6}, {%0,%1,%2,%3};"
        : "+f"(d[0]), "+f"(d[1]), "+f"(d[2]), "+f"(d[3]) : "r"(a0), "r"(a1), "r"(b0));
}
__device__ __forceinline__ uint32_t hadd2(uint32_t a, uint32_t b) {
    uint32_t r; asm("add.rn.bf16x2 %0, %1, %2;" : "=r"(r) : "r"(a), "r"(b)); return r;
}
__device__ __forceinline__ uint32_t pack2(float lo, float hi) {
    uint32_t r; asm("cvt.rn.bf16x2.f32 %0, %1, %2;" : "=r"(r) : "f"(hi), "f"(lo)); return r;
}
__device__ __forceinline__ float bflo(uint32_t v) { return __uint_as_float(v << 16); }
__device__ __forceinline__ float bfhi(uint32_t v) { return __uint_as_float(v & 0xffff0000u); }
__device__ __forceinline__ float ex2(float x) { float r; asm("ex2.approx.ftz.f32 %0, %1;" : "=f"(r) : "f"(x)); return r; }
__device__ __forceinline__ void sts128(uint32_t a, uint32_t x, uint32_t y, uint32_t z, uint32_t w) {
    asm volatile("st.shared.v4.b32 [%0], {%1,%2,%3,%4};" ::"r"(a), "r"(x), "r"(y), "r"(z), "r"(w) : "memory");
}
__device__ __forceinline__ void sts64(uint32_t a, uint32_t x, uint32_t y) {
    asm volatile("st.shared.v2.b32 [%0], {%1,%2};" ::"r"(a), "r"(x), "r"(y) : "memory");
}
__device__ __forceinline__ void sts32(uint32_t a, uint32_t x) { asm volatile("st.shared.b32 [%0], %1;" ::"r"(a), "r"(x) : "memory"); }
__device__ __forceinline__ uint4 lds128(uint32_t a) {
    uint4 v; asm volatile("ld.shared.v4.b32 {%0,%1,%2,%3}, [%4];" : "=r"(v.x), "=r"(v.y), "=r"(v.z), "=r"(v.w) : "r"(a) : "memory"); return v;
}
__device__ __forceinline__ uint32_t lds32(uint32_t a) { uint32_t v; asm volatile("ld.shared.b32 %0, [%1];" : "=r"(v) : "r"(a) : "memory"); return v; }
__device__ __forceinline__ int grab_tile(unsigned* ctr) {
    int v; asm volatile("atom.relaxed.gpu.global.inc.u32 %0, [%1], 0x7fffffff;" : "=r"(v) : "l"(ctr) : "memory"); return v;
}
__device__ __forceinline__ uint32_t opaque(uint32_t v) { uint32_t r; asm volatile("mov.b32 %0, %1;" : "=r"(r) : "r"(v)); return r; }
__device__ __forceinline__ float rsq(float x) { float r; asm("rsqrt.approx.ftz.f32 %0, %1;" : "=f"(r) : "f"(x)); return r; }
__device__ __forceinline__ float f(uint32_t v) { return __uint_as_float(v); }
__device__ __forceinline__ uint32_t u(float v) { return __float_as_uint(v); }

constexpr uint32_t ONES = 0x3F803F80u;
constexpr float QSCALE = 0.07216878364870322f * 1.4426950408889634f;

__device__ __forceinline__ void issue_tile(const CUtensorMap* m0, const CUtensorMap* m1, uint32_t sb, int s, int tl, uint64_t pol) {
    const uint32_t full = sb + SM_BAR + s * 8, dst = sb + SM_STAGES + s * STAGE;
    const int par = tl * TP, y = par >> 8, x = par & 255;
    mbar_expect(full, STAGE);
    asm volatile("cp.async.bulk.tensor.5d.shared::cluster.global.mbarrier::complete_tx::bytes.L2::cache_hint [%0], [%1, {%3,%4,%3,%3,%5}], [%2], %6;"
                 ::"r"(dst), "l"(m0), "r"(full), "r"(0), "r"(x), "r"(2 * y), "l"(pol) : "memory");
    asm volatile("cp.async.bulk.tensor.4d.shared::cluster.global.mbarrier::complete_tx::bytes.L2::cache_hint [%0], [%1, {%3,%4,%3,%5}], [%2], %6;"
                 ::"r"(dst + TP * 4 * C * 2), "l"(m1), "r"(full), "r"(0), "r"(x), "r"(y), "l"(pol) : "memory");
}

__device__ __forceinline__ uint4 ldg_relaxed(const uint4* p) {
    uint4 v; asm volatile("ld.relaxed.gpu.global.v4.u32 {%0,%1,%2,%3}, [%4];" : "=r"(v.x), "=r"(v.y), "=r"(v.z), "=r"(v.w) : "l"(p) : "memory"); return v;
}
__device__ __forceinline__ uint32_t ldg_relaxed32(const void* p) {
    uint32_t v; asm volatile("ld.relaxed.gpu.global.u32 %0, [%1];" : "=r"(v) : "l"(p) : "memory"); return v;
}
__device__ __forceinline__ void stg_relaxed(uint4* p, uint32_t x, uint32_t y, uint32_t z, uint32_t w) {
    asm volatile("st.relaxed.gpu.global.v4.u32 [%0], {%1,%2,%3,%4};" ::"l"(p), "r"(x), "r"(y), "r"(z), "r"(w) : "memory");
}
__device__ __forceinline__ void stg_relaxed32(void* p, uint32_t x) { asm volatile("st.relaxed.gpu.global.u32 [%0], %1;" ::"l"(p), "r"(x) : "memory"); }
__device__ __forceinline__ bool has(const uint4& v, uint32_t m) { return v.x == m || v.y == m || v.z == m || v.w == m; }
__device__ __forceinline__ uint32_t hadd2v(uint32_t a, uint32_t b) {
    uint32_t r; asm volatile("add.rn.bf16x2 %0, %1, %2;" : "=r"(r) : "r"(a), "r"(b)); return r;
}

enum { B_QK = 1, B_QN = 2, B_GRP = 3  , B_Q = 5, B_MERGE = 6, B_HELP = 7, B_WO = 8, B_RED = 9 };

__global__ void __launch_bounds__(NTHREADS, 1)
attn_main(const char* __restrict__ f0, const char* __restrict__ f1,
          const __nv_bfloat16* __restrict__ q, const __nv_bfloat16* __restrict__ wq, const __nv_bfloat16* __restrict__ wk, Scratch* scr,
          const __nv_bfloat16* __restrict__ wv, const __nv_bfloat16* __restrict__ wo, __nv_bfloat16* __restrict__ out,
          const __grid_constant__ CUtensorMap m0, const __grid_constant__ CUtensorMap m1)
{
    CK_(0, 0);
    extern __shared__ char smem_raw[];
    const uint32_t sb = (s2u(smem_raw) + 1023u) & ~1023u;
    const int warp = threadIdx.x >> 5, lane = threadIdx.x & 31;
    const int G = gridDim.x, b = blockIdx.x;
    const int g = lane >> 2, t = lane & 3;
    const bool src = b < NSRC;

    if (warp >= 8) {
        if (warp < 10) {
            const int p = warp - 8;
            if (lane == 0) {
                if (p == 0) TS(0);
                asm volatile("prefetch.tensormap [%0];" ::"l"(p ? &m1 : &m0) : "memory");
            }
            if (lane < NS / 2) {
                const int s = 2 * lane + p;
                mbar_init(sb + SM_BAR + s * 8, 1); mbar_init(sb + SM_BAR + (NS + s) * 8, 1); sts32(sb + SM_FLAG + s * 4, 0);
            }
            if (p == 0 && lane == 31) mbar_init(sb + SM_LATE, 1);
            asm volatile("fence.mbarrier_init.release.cluster;" ::: "memory");
            __syncwarp();
            bar_arrive(B_QK, 384);
            if (src) bar_sync(B_Q, 320);
            int s = p; uint32_t ph = 1;
            if (lane == 0) {
                uint64_t pol; asm volatile("createpolicy.fractional.L2::evict_first.b64 %0, 1.0;" : "=l"(pol));
                int sa = p, na = 0; uint32_t pa = 0;
                int tl = b + p * G;
                bool late = false;
                for (int n = 0;; n++) {
                    int nxt = tl + 2 * G;
                    if (n >= NST - 1) nxt = grab_tile(g_ctr) + 2 * NST * G;
                    const int d = n < NRAMP ? D0 : (tl >= NT - TAILT ? D2 : D1);
                    while (n - na >= d) {
                        mbar_wait(sb + SM_BAR + sa * 8, pa);
                        if (na < NS / 2) TR(1, 2 * na + p);
                        na++; sa += 2;
                        if (sa >= NS) { sa -= NS; pa ^= 1; }
                    }
                    if (n >= NS / 2) mbar_wait(sb + SM_BAR + (NS + s) * 8, ph);
                    issue_tile(&m0, &m1, sb, s, tl, pol);
                    TR(0, 2 * n + p);
                    s += 2;
                    if (s >= NS) { s -= NS; ph ^= 1; }
                    if (p == 0 && !late && nxt >= NT - INITT) { late = true; mbar_arrive(sb + SM_LATE); }
                    tl = nxt;
                    if (tl >= NT) break;
                }
                if (p == 0 && !late) mbar_arrive(sb + SM_LATE);
                if (p) TSE(5);
            }
            __syncwarp();
            bar_sync(B_HELP, 128);
            if (lane == 0) {
                mbar_wait(sb + SM_BAR + (NS + s) * 8, ph);
                sts32(sb + SM_FLAG + s * 4, 1);
                mbar_arrive(sb + SM_BAR + s * 8);
            }
            __syncwarp();
            if (p == 0) return;
        } else {
            const int hw = warp - 10, h = threadIdx.x - 320;
            uint4 v[6];
            for (int it = 0;; it++) {
                bool miss = false;
#pragma unroll
                for (int k = 0; k < 6; k++) v[k] = ldg_relaxed(g_qk + k * 64 + h);
#pragma unroll
                for (int k = 0; k < 6; k++) miss |= has(v[k], 0);
                if (!miss) break;
                if (it > SPIN_LIMIT) __trap();
                if (it == 0) __nanosleep(QSLEEP);
            }
#pragma unroll
            for (int k = 0; k < 6; k++) sts128(sb + SM_QK + (k * 64 + h) * 16, ~v[k].x, ~v[k].y, ~v[k].z, ~v[k].w);
            __syncwarp();
            bar_sync(B_QK, 384);
            if (b < NRD) {
                const int js = b & 7;
                uint4 wt[9];
#pragma unroll
                for (int k = 0; k < 9; k++) {
                    const int idx = k * 64 + h, d = idx / 3, i = idx - 3 * d;
                    wt[k] = __ldg(reinterpret_cast<const uint4*>(wo + d * C + 24 * js + 8 * i));
                }
#pragma unroll
                for (int k = 0; k < 9; k++) {
                    const int idx = k * 64 + h, d = idx / 3, i = idx - 3 * d;
                    sts128(sb + SM_X + ((i * 6 + (d >> 5)) * 4 + ((d >> 1) & 3)) * 128 + (((d >> 3) & 3) * 2 + (d & 1)) * 16, wt[k].x, wt[k].y, wt[k].z, wt[k].w);
                }
                bar_sync(B_WO, 64);
                float cs[3][2] = {{0.f, 0.f}, {0.f, 0.f}, {0.f, 0.f}};
#pragma unroll 1
                for (int m = 0; m < 6; m++) {
                    const int mt = 2 * ((m + (b >> 3)) % 6) + hw;
                    uint4 lo[6], hi[6];
#pragma unroll
                    for (int jj = 0; jj < 6; jj++) {
                        lo[jj] = __ldg(reinterpret_cast<const uint4*>(wv + (16 * mt + g) * C + 32 * jj + 8 * t));
                        hi[jj] = __ldg(reinterpret_cast<const uint4*>(wv + (16 * mt + g + 8) * C + 32 * jj + 8 * t));
                    }
                    float a[3][4];
#pragma unroll
                    for (int i = 0; i < 3; i++) a[i][0] = a[i][1] = a[i][2] = a[i][3] = 0.f;
#pragma unroll
                    for (int jj = 0; jj < 6; jj++)
#pragma unroll
                        for (int i = 0; i < 3; i++) {
                            uint32_t bb[4];
                            ldsm4t(bb, sb + SM_X + (i * 6 + jj) * 512 + lane * 16);
                            mma(a[i], lo[jj].x, hi[jj].x, lo[jj].y, hi[jj].y, bb[0], bb[1]);
                            mma(a[i], lo[jj].z, hi[jj].z, lo[jj].w, hi[jj].w, bb[2], bb[3]);
                        }
#pragma unroll
                    for (int i = 0; i < 3; i++)
#pragma unroll
                        for (int e = 0; e < 2; e++) {
                            const uint32_t ad = sb + SM_W + ((8 * i + 2 * t + e) * WP + 16 * mt + g) * 4;
                            sts32(ad, u(a[i][e])); sts32(ad + 32, u(a[i][2 + e]));
                            cs[i][e] += a[i][e] + a[i][2 + e];
                        }
                }
#pragma unroll
                for (int i = 0; i < 3; i++)
#pragma unroll
                    for (int e = 0; e < 2; e++) {
                        float c = cs[i][e];
                        c += __shfl_xor_sync(~0u, c, 4); c += __shfl_xor_sync(~0u, c, 8); c += __shfl_xor_sync(~0u, c, 16);
                        if (g == 0) sts32(sb + SM_CS + (hw * 24 + 8 * i + 2 * t + e) * 4, u(c));
                    }
                if (h == 0) TSE(6);
            }
            bar_arrive(B_HELP, 128);
            mbar_wait(sb + SM_LATE, 0);
            if (b < NRD) {
#pragma unroll 1
                for (int i = h; i < G * 8; i += 64) stg_relaxed(g_x1 + b * (MAXG * 8) + i, EMPTY, EMPTY, EMPTY, EMPTY);
                if (h < 6) stg_relaxed(g_x2 + b * 6 + h, EMPTY, EMPTY, EMPTY, EMPTY);
                __threadfence();
                bar_sync(B_WO, 64);
                if (h == 0) asm volatile("red.release.gpu.global.add.u32 [%0], 1;" ::"l"(g_ctr + 32) : "memory");
            }
            if (h == 0) {
                for (int it = 0;; it++) {
                    uint32_t v; asm volatile("ld.acquire.gpu.global.u32 %0, [%1];" : "=r"(v) : "l"(g_ctr + 32) : "memory");
                    if (v >= NRD) break;
                    if (it > SPIN_LIMIT) __trap();
                    __nanosleep(200);
                }
                TSE(7);
            }
            __syncwarp();
            bar_arrive(B_MERGE, 320);
        }
        const int ft = threadIdx.x - 288;
        if (b >= NRD) return;
        const int n = b >> 3, js = b & 7, jp = ft >> 3, ks = ft & 7;
        float w0[24], w1[24];
        {
            const float c0 = (f(lds32(sb + SM_CS + 8 * jp)) + f(lds32(sb + SM_CS + 96 + 8 * jp))) * (1.f / C);
            const float c1 = (f(lds32(sb + SM_CS + 8 * jp + 4)) + f(lds32(sb + SM_CS + 96 + 8 * jp + 4))) * (1.f / C);
#pragma unroll
            for (int k = 0; k < 6; k++) {
                const uint4 a = lds128(sb + SM_W + (2 * jp * WP + 24 * ks + 4 * k) * 4), c = lds128(sb + SM_W + ((2 * jp + 1) * WP + 24 * ks + 4 * k) * 4);
                w0[4 * k] = f(a.x) - c0; w0[4 * k + 1] = f(a.y) - c0; w0[4 * k + 2] = f(a.z) - c0; w0[4 * k + 3] = f(a.w) - c0;
                w1[4 * k] = f(c.x) - c1; w1[4 * k + 1] = f(c.y) - c1; w1[4 * k + 2] = f(c.z) - c1; w1[4 * k + 3] = f(c.w) - c1;
            }
        }
        const uint32_t qv = __ldg(reinterpret_cast<const uint32_t*>(q + n * C + 24 * js + 2 * jp));
        float o0 = ks ? 0.f : bflo(qv), o1 = ks ? 0.f : bfhi(qv), o2 = 0.f, o3 = 0.f;
        bar_sync(B_RED, 352);
        if (ft < 48) {
            uint4 x;
            for (int it = 0;; it++) {
                x = ldg_relaxed(g_x2 + n * 48 + ft);
                if (!has(x, EMPTY)) break;
                if (it > SPIN_LIMIT) __trap();
            }
            sts128(sb + SM_QK + ft * 16, x.x, x.y, x.z, x.w);
        }
        __syncwarp();
        bar_sync(B_WO, 96);
        uint4 v[6];
#pragma unroll
        for (int k = 0; k < 6; k++) v[k] = lds128(sb + SM_QK + (ks * 6 + k) * 16);
        if (ft == 0) TSX(9, v[0].x);
#pragma unroll
        for (int k = 0; k < 6; k++) {
            o0 = fmaf(f(v[k].x), w0[4 * k], o0); o1 = fmaf(f(v[k].x), w1[4 * k], o1);
            o2 = fmaf(f(v[k].y), w0[4 * k + 1], o2); o3 = fmaf(f(v[k].y), w1[4 * k + 1], o3);
            o0 = fmaf(f(v[k].z), w0[4 * k + 2], o0); o1 = fmaf(f(v[k].z), w1[4 * k + 2], o1);
            o2 = fmaf(f(v[k].w), w0[4 * k + 3], o2); o3 = fmaf(f(v[k].w), w1[4 * k + 3], o3);
        }
        o0 += o2; o1 += o3;
        __syncwarp();
#pragma unroll
        for (int o = 1; o < 8; o <<= 1) { o0 += __shfl_xor_sync(~0u, o0, o); o1 += __shfl_xor_sync(~0u, o1, o); }
        if (ks == 0) *reinterpret_cast<uint32_t*>(out + n * C + 24 * js + 2 * jp) = pack2(o0, o1);
        if (ft == 0) TSD(11, u(o0));
        return;
    }

    const int grp = warp >> 2, cw = warp & 3;
    if (!src && lane == 0) {
        const char* a; int sz;
        if (warp >= 6) {
            sz = C * C * 2 / WSL; a = (const char*)(warp == 6 ? wq : wk) + (b % WSL) * sz;
        } else {
            const int tl = b + (warp / 3) * G, which = warp % 3;
            const int par = tl * TP, y = par >> 8, x = par & 255;
            a = which < 2 ? f0 + ((size_t)(2 * y + which) * W0 + 2 * x) * (C * 2) : f1 + ((size_t)y * W1 + x) * (C * 2);
            sz = which < 2 ? TP * 2 * C * 2 : TP * C * 2;
        }
        if (warp >= 6 || warp < 3 * NPRE) asm volatile("cp.async.bulk.prefetch.L2.global [%0], %1;" ::"l"(a), "r"(sz) : "memory");
    }
    if (src) {
        const uint32_t wqs = sb + SM_STAGES + (NS - 5) * STAGE, wbar = sb + SM_WBAR;
        const int hr = lane >> 4, qt = (lane >> 2) & 3, sub = lane & 3;
        const uint32_t* qp = reinterpret_cast<const uint32_t*>(q + (warp + 8 * hr) * C + 48 * qt + 6 * sub);
        uint32_t qw[6];
        CK_(1, (uint32_t)(size_t)qp);
#pragma unroll
        for (int j = 0; j < 3; j++) { qw[j] = __ldg(qp + j); qw[3 + j] = __ldg(qp + 12 + j); }
        CK_(2, 0);
        if (lane == 0) { mbar_init(wbar + warp * 8, 1); asm volatile("fence.mbarrier_init.release.cluster;" ::: "memory"); mbar_expect(wbar + warp * 8, 9216);
            asm volatile("cp.async.bulk.shared::cluster.global.mbarrier::complete_tx::bytes [%0], [%1], 9216, [%2];"
                         ::"r"(wqs + warp * 9232), "l"(wq + 24 * warp * C), "r"(wbar + warp * 8) : "memory");
        }
        __syncwarp();
        CK_(3, 0);
        CK_(4, qw[0]);
        CK_(5, qw[5]);
        if (threadIdx.x == 0) TSP(2, 0);
        float e[12];
#pragma unroll
        for (int j = 0; j < 6; j++) { e[2 * j] = bflo(qw[j]); e[2 * j + 1] = bfhi(qw[j]); }
        float sm = ((e[0] + e[1]) + (e[2] + e[3])) + ((e[4] + e[5]) + (e[6] + e[7])) + ((e[8] + e[9]) + (e[10] + e[11]));
#pragma unroll
        for (int o = 1; o < 16; o <<= 1) sm += __shfl_xor_sync(~0u, sm, o);
        if (threadIdx.x == 0) TSP(5, u(sm));
        float v0 = 0.f, v1 = 0.f;
#pragma unroll
        for (int j = 0; j < 12; j++) e[j] -= sm * (1.f / C);
#pragma unroll
        for (int j = 0; j < 6; j++) { v0 = fmaf(e[j], e[j], v0); v1 = fmaf(e[6 + j], e[6 + j], v1); }
        v0 += v1;
#pragma unroll
        for (int o = 1; o < 16; o <<= 1) v0 += __shfl_xor_sync(~0u, v0, o);
        const float rq = rsq(v0 * (1.f / C) + 1e-5f);
#pragma unroll
        for (int j = 0; j < 6; j++)
            sts32(sb + SM_X + (3 * sub + (j >> 1)) * 512 + (4 * warp + qt) * 16 + (2 * (j & 1) + hr) * 4, pack2(e[j] * rq, e[6 + j] * rq));
        if (threadIdx.x == 0) TSP(8, 0);
        uint32_t wkf[2][3];
#pragma unroll
        for (int i = 0; i < 2; i++)
#pragma unroll
            for (int j = 0; j < 3; j++) wkf[i][j] = __ldg(reinterpret_cast<const uint32_t*>(wk + (16 * b + 8 * i + g) * C + 24 * warp + 8 * j + 2 * t));
        bar_sync(B_QN, 256);
        float acc[2][3][4];
#pragma unroll
        for (int i = 0; i < 3; i++)
#pragma unroll
            for (int e = 0; e < 4; e++) acc[0][i][e] = acc[1][i][e] = 0.f;
        const uint32_t ba = wqs + (lane & 7) * 9232 + (lane >> 3) * 384 + 48 * warp;
        uint4 a[12];
#pragma unroll
        for (int kk = 0; kk < 12; kk++) a[kk] = lds128(sb + SM_X + kk * 512 + lane * 16);
        mbar_wait(wbar + (lane & 7) * 8, 0);
        __syncwarp();
        if (threadIdx.x == 0) TSP(4, 0);
#pragma unroll
        for (int kp = 0; kp < 6; kp++)
#pragma unroll
            for (int i = 0; i < 3; i++) {
                uint32_t bb[4];
                ldsm4t(bb, ba + kp * 1536 + i * 16);
                mma(acc[0][i], a[2 * kp].x, a[2 * kp].y, a[2 * kp].z, a[2 * kp].w, bb[0], bb[1]);
                mma(acc[1][i], a[2 * kp + 1].x, a[2 * kp + 1].y, a[2 * kp + 1].z, a[2 * kp + 1].w, bb[2], bb[3]);
            }
        if (threadIdx.x == 0) TSP(7, u(acc[1][2][3]));
        float kq[2][4] = {{0.f, 0.f, 0.f, 0.f}, {0.f, 0.f, 0.f, 0.f}};
#pragma unroll
        for (int j = 0; j < 3; j++) {
            const uint32_t a0 = pack2(acc[0][j][0] + acc[1][j][0], acc[0][j][1] + acc[1][j][1]), a1 = pack2(acc[0][j][2] + acc[1][j][2], acc[0][j][3] + acc[1][j][3]);
            mma8(kq[0], a0, a1, wkf[0][j]);
            mma8(kq[1], a0, a1, wkf[1][j]);
        }
        if (warp < 7) {
            sts128(sb + SM_W + warp * 1024 + lane * 16, u(kq[0][0]), u(kq[0][1]), u(kq[0][2]), u(kq[0][3]));
            sts128(sb + SM_W + warp * 1024 + 512 + lane * 16, u(kq[1][0]), u(kq[1][1]), u(kq[1][2]), u(kq[1][3]));
            bar_arrive(B_Q, 320);
        } else {
            bar_sync(B_Q, 320);
#pragma unroll
            for (int w = 0; w < 7; w++)
#pragma unroll
                for (int i = 0; i < 2; i++) {
                    const uint4 o = lds128(sb + SM_W + w * 1024 + i * 512 + lane * 16);
                    kq[i][0] += f(o.x); kq[i][1] += f(o.y); kq[i][2] += f(o.z); kq[i][3] += f(o.w);
                }
            stg_relaxed(g_qk + b * 32 + lane, ~pack2(kq[0][0] * QSCALE, kq[0][1] * QSCALE), ~pack2(kq[0][2] * QSCALE, kq[0][3] * QSCALE),
                        ~pack2(kq[1][0] * QSCALE, kq[1][1] * QSCALE), ~pack2(kq[1][2] * QSCALE, kq[1][3] * QSCALE));
            if (lane == 0) TS(10);
        }
    }

    const int xp = lane & 7, mi = lane >> 3;
    const uint32_t offS = opaque(xp * 128 + ((mi ^ xp) << 4));
    uint32_t offT[6], offT1[2];
#pragma unroll
    for (int i = 0; i < 6; i++) {
        const int J = 6 * cw + i;
        offT[i] = opaque(mi * 3072 + (J >> 3) * 1024 + xp * 128 + (((J & 7) ^ xp) << 4));
    }
    {
        const int J = 6 * cw + mi, J2 = 6 * cw + 4 + (mi & 1);
        offT1[0] = opaque(12288 + (J >> 3) * 1024 + xp * 128 + (((J & 7) ^ xp) << 4));
        offT1[1] = opaque(12288 + (J2 >> 3) * 1024 + xp * 128 + (((J2 & 7) ^ xp) << 4));
    }
    const uint32_t mxw = opaque(sb + SM_MX + grp * 256 + ((g + 8 * t) * 4 + cw) * 4);
    const uint32_t offS0 = opaque(offS + cw * 3072);
    const int shl = opaque(9 * t);
    const uint32_t mxr = sb + SM_MX + grp * 256 + g * 16;
    const uint32_t pw = sb + SM_P + grp * 1024 + (cw >> 1) * 512 + lane * 16 + (cw & 1) * 8;
    const uint32_t pr = sb + SM_P + grp * 1024 + lane * 16;
    const int barid = B_GRP + grp;
    const bool elected = (threadIdx.x & 127) == 96;

    uint32_t qa[48];
    float r_lo, r_hi;
    bar_sync(B_QK, 384);
    {
        float rr[2][4] = {{0.f, 0.f, 0.f, 0.f}, {0.f, 0.f, 0.f, 0.f}};
#pragma unroll
        for (int kk = 0; kk < 12; kk++) {
            const uint4 v = lds128(sb + SM_QK + kk * 512 + lane * 16);
            qa[4 * kk] = v.x; qa[4 * kk + 1] = v.y; qa[4 * kk + 2] = v.z; qa[4 * kk + 3] = v.w;
            mma(rr[kk & 1], v.x, v.y, v.z, v.w, ONES, ONES);
        }
        r_lo = rr[0][0] + rr[1][0]; r_hi = rr[0][2] + rr[1][2];
    }
    if (threadIdx.x == 0) TS(1);

    float acc[6][4];
#pragma unroll
    for (int i = 0; i < 6; i++) acc[i][0] = acc[i][1] = acc[i][2] = acc[i][3] = 0.f;
    float m_lo = -INFINITY, m_hi = -INFINITY, l_lo = 0.f, l_hi = 0.f;
    int s = grp; uint32_t ph = 0;
    while (true) {
        mbar_wait(sb + SM_BAR + s * 8, ph);
        PH(0, 0);
        const uint32_t stop = lds32(sb + SM_FLAG + s * 4);
        const uint32_t st = sb + SM_STAGES + s * STAGE;
        float sc[2][4], gr[2][4];
#pragma unroll
        for (int e = 0; e < 4; e++) sc[0][e] = sc[1][e] = gr[0][e] = gr[1][e] = 0.f;
        const uint32_t a0e = st + offS0, a1e = st + 12288 + offS;
        uint32_t x0[4], y0[4];
        ldsm4(x0, a0e);
        ldsm4(y0, a1e);
        if (stop) break;
#pragma unroll
        for (int qq = 0; qq < 6; qq++) {
            uint32_t x[4], y[4];
            if (qq == 0) {
#pragma unroll
                for (int e = 0; e < 4; e++) { x[e] = x0[e]; y[e] = y0[e]; }
            } else {
                ldsm4(x, (a0e ^ ((qq & 1) << 6)) + (qq >> 1) * 1024);
                ldsm4(y, (a1e ^ ((qq & 1) << 6)) + (qq >> 1) * 1024);
            }
#pragma unroll
            for (int e = 0; e < 4; e++) x[e] = hadd2(x[e], y[e]);
            mma(gr[0], x[0], ONES, x[1], ONES, x[0], x[1]);
            mma(gr[1], x[2], ONES, x[3], ONES, x[2], x[3]);
            mma(sc[0], qa[8 * qq], qa[8 * qq + 1], qa[8 * qq + 2], qa[8 * qq + 3], x[0], x[1]);
            mma(sc[1], qa[8 * qq + 4], qa[8 * qq + 5], qa[8 * qq + 6], qa[8 * qq + 7], x[2], x[3]);
        }
        uint32_t xt[6][4], yt[6];
        ldsm4t(yt, st + offT1[0]);
        ldsm2t(yt + 4, st + offT1[1]);
#pragma unroll
        for (int i = 0; i < 6; i++) ldsm4t(xt[i], st + offT[i]);

        const float ss0 = __shfl_sync(~0u, gr[0][0] + gr[1][0], shl);
        const float ss1 = __shfl_sync(~0u, gr[0][1] + gr[1][1], shl + 4);
        const float mu0 = (gr[0][2] + gr[1][2]) * (1.f / C), mu1 = (gr[0][3] + gr[1][3]) * (1.f / C);
        const float rs0 = rsq(fmaxf(fmaf(-mu0, mu0, ss0 * (1.f / C)), 0.f) + 1e-5f);
        const float rs1 = rsq(fmaxf(fmaf(-mu1, mu1, ss1 * (1.f / C)), 0.f) + 1e-5f);
        const float s0 = fmaf(-mu0, r_lo, sc[0][0] + sc[1][0]) * rs0;
        const float s1 = fmaf(-mu1, r_lo, sc[0][1] + sc[1][1]) * rs1;
        const float s2 = fmaf(-mu0, r_hi, sc[0][2] + sc[1][2]) * rs0;
        const float s3 = fmaf(-mu1, r_hi, sc[0][3] + sc[1][3]) * rs1;
        PH(1, u(s0 + s2));
        float xl = fmaxf(s0, s1), xh = fmaxf(s2, s3);
        xl = fmaxf(xl, __shfl_xor_sync(~0u, xl, 1)); xh = fmaxf(xh, __shfl_xor_sync(~0u, xh, 1));
        xl = fmaxf(xl, __shfl_xor_sync(~0u, xl, 2)); xh = fmaxf(xh, __shfl_xor_sync(~0u, xh, 2));
        if (t < 2) sts32(mxw, u(t ? xh : xl));
#pragma unroll
        for (int i = 0; i < 6; i++)
#pragma unroll
            for (int e = 0; e < 4; e++) xt[i][e] = hadd2v(xt[i][e], yt[i]);
        bar_sync(barid, 128);
        PH(2, 0);
        const uint4 ml4 = lds128(mxr), mh4 = lds128(mxr + 128);
        if (elected) mbar_arrive(sb + SM_BAR + (NS + s) * 8);
        const float nl = fmaxf(fmaxf(fmaxf(f(ml4.x), f(ml4.y)), fmaxf(f(ml4.z), f(ml4.w))), m_lo);
        const float nh = fmaxf(fmaxf(fmaxf(f(mh4.x), f(mh4.y)), fmaxf(f(mh4.z), f(mh4.w))), m_hi);
        const float p0 = ex2(s0 - nl), p1 = ex2(s1 - nl), p2 = ex2(s2 - nh), p3 = ex2(s3 - nh);
        sts64(pw, pack2(p0 * rs0, p1 * rs1), pack2(p2 * rs0, p3 * rs1));
        const float al = ex2(m_lo - nl), ah = ex2(m_hi - nh);
        m_lo = nl; m_hi = nh;
        l_lo = fmaf(l_lo, al, p0 + p1); l_hi = fmaf(l_hi, ah, p2 + p3);
#pragma unroll
        for (int i = 0; i < 6; i++) { acc[i][0] *= al; acc[i][1] *= al; acc[i][2] *= ah; acc[i][3] *= ah; }
        bar_sync(barid, 128);
        PH(3, 0);
        const uint4 pa = lds128(pr), pb = lds128(pr + 512);
#pragma unroll
        for (int i = 0; i < 6; i++) mma(acc[i], pa.x, pa.y, pa.z, pa.w, xt[i][0], xt[i][1]);
#pragma unroll
        for (int i = 0; i < 6; i++) mma(acc[i], pb.x, pb.y, pb.z, pb.w, xt[i][2], xt[i][3]);
        PH(4, u(acc[5][0]));
        s += 2;
        if (s >= NS) { s -= NS; ph ^= 1; }
    }
    if (threadIdx.x == grp * 128) TSE(2 + grp);
    if (threadIdx.x == grp * 128 + 96) TSX(2 + grp, u(acc[5][0]));

    l_lo += __shfl_xor_sync(~0u, l_lo, 1); l_hi += __shfl_xor_sync(~0u, l_hi, 1);
    l_lo += __shfl_xor_sync(~0u, l_lo, 2); l_hi += __shfl_xor_sync(~0u, l_hi, 2);
    if (t < 2) sts32(sb + SM_RS + ((g + 8 * t) * 8 + warp) * 4, u(t ? l_hi : l_lo));
    float own[3][4];
#pragma unroll
    for (int i = 0; i < 3; i++) {
#pragma unroll
        for (int e = 0; e < 4; e++) own[i][e] = grp ? acc[3 + i][e] : acc[i][e];
        sts128(sb + SM_X + (warp * 3 + i) * 512 + lane * 16, u(grp ? acc[i][0] : acc[3 + i][0]), u(grp ? acc[i][1] : acc[3 + i][1]),
               u(grp ? acc[i][2] : acc[3 + i][2]), u(grp ? acc[i][3] : acc[3 + i][3]));
    }
    if (cw == 0 && t < 2) sts32(sb + SM_X + 12288 + (grp * 16 + g + 8 * t) * 4, u(t ? m_hi : m_lo));
    bar_sync(B_MERGE, 320);
    if (threadIdx.x == 224) TSX(4, 0);
    {
        const float ol = f(lds32(sb + SM_X + 12288 + ((grp ^ 1) * 16 + g) * 4)), oh = f(lds32(sb + SM_X + 12288 + ((grp ^ 1) * 16 + g + 8) * 4));
        const uint4 la = lds128(sb + SM_RS + g * 32 + grp * 16), lb = lds128(sb + SM_RS + g * 32 + (grp ^ 1) * 16);
        const uint4 ha = lds128(sb + SM_RS + (g + 8) * 32 + grp * 16), hb = lds128(sb + SM_RS + (g + 8) * 32 + (grp ^ 1) * 16);
        uint4 o[3];
#pragma unroll
        for (int i = 0; i < 3; i++) o[i] = lds128(sb + SM_X + ((warp ^ 4) * 3 + i) * 512 + lane * 16);
        const float nl = fmaxf(ol, m_lo), nh = fmaxf(oh, m_hi);
        const float al = ex2(m_lo - nl), ah = ex2(m_hi - nh), bl = ex2(ol - nl), bh = ex2(oh - nh);
        const float Ll = ((f(la.x) + f(la.y)) + (f(la.z) + f(la.w))) * al + ((f(lb.x) + f(lb.y)) + (f(lb.z) + f(lb.w))) * bl;
        const float Lh = ((f(ha.x) + f(ha.y)) + (f(ha.z) + f(ha.w))) * ah + ((f(hb.x) + f(hb.y)) + (f(hb.z) + f(hb.w))) * bh;
        uint4* dl = g_x1 + ((g * 8 + 2 * cw + grp) * MAXG + b) * 8 + t;
        uint4* dh = dl + 64 * MAXG * 8;
        stg_relaxed(dl, u(own[0][0] * al + f(o[0].x) * bl), u(own[0][1] * al + f(o[0].y) * bl), u(own[1][0] * al + f(o[1].x) * bl), u(own[1][1] * al + f(o[1].y) * bl));
        stg_relaxed(dh, u(own[0][2] * ah + f(o[0].z) * bh), u(own[0][3] * ah + f(o[0].w) * bh), u(own[1][2] * ah + f(o[1].z) * bh), u(own[1][3] * ah + f(o[1].w) * bh));
        stg_relaxed(dl + 4, u(own[2][0] * al + f(o[2].x) * bl), u(own[2][1] * al + f(o[2].y) * bl), u(nl), u(Ll));
        stg_relaxed(dh + 4, u(own[2][2] * ah + f(o[2].z) * bh), u(own[2][3] * ah + f(o[2].w) * bh), u(nh), u(Lh));
    }
    if (threadIdx.x == 0) TSE(4);
    if (threadIdx.x == 224) TSX(5, 0);
    if (b >= NRD) return;

    {
        const uint4* mb = g_x1 + (b * MAXG + (threadIdx.x >> 2)) * 8 + t;
        uint4 a[3], c[3];
        bool miss[3] = {true, true, (threadIdx.x >> 2) + 128 < G};
        a[2] = make_uint4(0, 0, 0, 0); c[2] = make_uint4(0, 0, u(-INFINITY), 0);
        for (int it = 0;; it++) {
#pragma unroll
            for (int k = 0; k < 3; k++)
                if (miss[k]) { a[k] = ldg_relaxed(mb + k * 512); c[k] = ldg_relaxed(mb + k * 512 + 4); }
#pragma unroll
            for (int k = 0; k < 3; k++) miss[k] = has(a[k], EMPTY) || has(c[k], EMPTY);
            if (!(miss[0] || miss[1] || miss[2])) break;
            if (it > SPIN_LIMIT) __trap();
        }
        __syncwarp();
        if (threadIdx.x == 224) TSX(6, 0);
        float M = fmaxf(fmaxf(f(c[0].z), f(c[1].z)), f(c[2].z));
        M = fmaxf(M, __shfl_xor_sync(~0u, M, 4)); M = fmaxf(M, __shfl_xor_sync(~0u, M, 8)); M = fmaxf(M, __shfl_xor_sync(~0u, M, 16));
        const float e0 = ex2(f(c[0].z) - M), e1 = ex2(f(c[1].z) - M), e2 = ex2(f(c[2].z) - M);
        float v[7];
        v[0] = f(a[0].x) * e0 + f(a[1].x) * e1 + f(a[2].x) * e2; v[1] = f(a[0].y) * e0 + f(a[1].y) * e1 + f(a[2].y) * e2;
        v[2] = f(a[0].z) * e0 + f(a[1].z) * e1 + f(a[2].z) * e2; v[3] = f(a[0].w) * e0 + f(a[1].w) * e1 + f(a[2].w) * e2;
        v[4] = f(c[0].x) * e0 + f(c[1].x) * e1 + f(c[2].x) * e2; v[5] = f(c[0].y) * e0 + f(c[1].y) * e1 + f(c[2].y) * e2;
        v[6] = f(c[0].w) * e0 + f(c[1].w) * e1 + f(c[2].w) * e2;
#pragma unroll
        for (int o = 4; o < 32; o <<= 1)
#pragma unroll
            for (int e = 0; e < 7; e++) v[e] += __shfl_xor_sync(~0u, v[e], o);
        if (lane < 4) {
            sts128(sb + SM_RED + warp * 128 + t * 32, u(v[0]), u(v[1]), u(v[2]), u(v[3]));
            sts128(sb + SM_RED + warp * 128 + t * 32 + 16, u(v[4]), u(v[5]), u(v[6]), u(M));
        }
        if (warp < 7) { bar_arrive(B_RED, 352); return; }
        bar_sync(B_RED, 352);
        if (lane == 0) TSX(7, 0);
        const int j = lane < 24 ? lane : 0;
        float x[8], l[8], mw[8];
#pragma unroll
        for (int w = 0; w < 8; w++) {
            x[w] = f(lds32(sb + SM_RED + w * 128 + ((j >> 1) & 3) * 32 + (2 * (j >> 3) + (j & 1)) * 4));
            l[w] = f(lds32(sb + SM_RED + w * 128 + 24)); mw[w] = f(lds32(sb + SM_RED + w * 128 + 28));
        }
        M = fmaxf(fmaxf(fmaxf(mw[0], mw[1]), fmaxf(mw[2], mw[3])), fmaxf(fmaxf(mw[4], mw[5]), fmaxf(mw[6], mw[7])));
        float X0 = 0.f, X1 = 0.f, L0 = 0.f, L1 = 0.f;
#pragma unroll
        for (int w = 0; w < 8; w += 2) {
            const float ea = ex2(mw[w] - M), eb = ex2(mw[w + 1] - M);
            X0 = fmaf(x[w], ea, X0); L0 = fmaf(l[w], ea, L0); X1 = fmaf(x[w + 1], eb, X1); L1 = fmaf(l[w + 1], eb, L1);
        }
        if (lane < 24) stg_relaxed32(reinterpret_cast<float*>(g_x2) + b * 24 + lane, u(__fdividef(X0 + X1, L0 + L1)));
        if (lane == 0) TSX(8, 0);
        if (b < NSRC) g_qk[b * 32 + lane] = make_uint4(0, 0, 0, 0);
        if (b == NSRC && lane < 2) g_ctr[32 * lane] = 0;
    }
}

typedef CUresult (*EncodeFn)(CUtensorMap*, CUtensorMapDataType, cuuint32_t, void*, const cuuint64_t*, const cuuint64_t*,
                             const cuuint32_t*, const cuuint32_t*, CUtensorMapInterleave, CUtensorMapSwizzle,
                             CUtensorMapL2promotion, CUtensorMapFloatOOBfill);

}

extern "C" void kernel_launch(void* const* d_in, const int* in_sizes, int n_in, void* d_out, int out_size) {
    const __nv_bfloat16* q = (const __nv_bfloat16*)d_in[0];
    char* f0 = (char*)d_in[1];
    char* f1 = (char*)d_in[2];
    const __nv_bfloat16* wq = (const __nv_bfloat16*)d_in[3];
    const __nv_bfloat16* wk = (const __nv_bfloat16*)d_in[4];
    const __nv_bfloat16* wv = (const __nv_bfloat16*)d_in[5];
    const __nv_bfloat16* wo = (const __nv_bfloat16*)d_in[6];

    static EncodeFn enc = nullptr;
    static int grid = 0;
    static Scratch* scr = nullptr;
    if (!enc) {
        void* fn = nullptr; cudaDriverEntryPointQueryResult qr;
        cudaGetDriverEntryPoint("cuTensorMapEncodeTiled", &fn, cudaEnableDefault, &qr);
        enc = (EncodeFn)fn;
        cudaGetSymbolAddress((void**)&scr, g_scratch);
        int dev = 0, sms = 0;
        cudaGetDevice(&dev);
        cudaDeviceGetAttribute(&sms, cudaDevAttrMultiProcessorCount, dev);
        grid = sms < MAXG ? sms : MAXG;
        cudaFuncSetAttribute(attn_main, cudaFuncAttributeMaxDynamicSharedMemorySize, SMEM_BYTES);
    }
    CUtensorMap m0, m1;
    {
        cuuint64_t dims[5] = {64, W1, 3, 2, W0};
        cuuint64_t str[4] = {2 * C * 2, 128, C * 2, (cuuint64_t)W0 * C * 2};
        cuuint32_t box[5] = {64, TP, 3, 2, 2}, es[5] = {1, 1, 1, 1, 1};
        enc(&m0, CU_TENSOR_MAP_DATA_TYPE_BFLOAT16, 5, f0, dims, str, box, es, CU_TENSOR_MAP_INTERLEAVE_NONE,
            CU_TENSOR_MAP_SWIZZLE_128B, CU_TENSOR_MAP_L2_PROMOTION_NONE, CU_TENSOR_MAP_FLOAT_OOB_FILL_NONE);
    }
    {
        cuuint64_t dims[4] = {64, W1, 3, W1};
        cuuint64_t str[3] = {C * 2, 128, (cuuint64_t)W1 * C * 2};
        cuuint32_t box[4] = {64, TP, 3, 1}, es[4] = {1, 1, 1, 1};
        enc(&m1, CU_TENSOR_MAP_DATA_TYPE_BFLOAT16, 4, f1, dims, str, box, es, CU_TENSOR_MAP_INTERLEAVE_NONE,
            CU_TENSOR_MAP_SWIZZLE_128B, CU_TENSOR_MAP_L2_PROMOTION_NONE, CU_TENSOR_MAP_FLOAT_OOB_FILL_NONE);
    }
    attn_main<<<grid, NTHREADS, SMEM_BYTES, cudaStreamPerThread>>>(f0, f1, q, wq, wk, scr, wv, wo, (__nv_bfloat16*)d_out, m0, m1);
}
```

```cpp
#include <cuda_runtime.h>
#include <cuda_bf16.h>
#include <cuda.h>
#include <stdint.h>

namespace {

constexpr int C = 192;
constexpr int NQ = 16;
constexpr int W0 = 512;
constexpr int W1 = 256;
constexpr int TP = 8;
constexpr int NT = W1 * W1 / TP;
constexpr int STAGE = TP * 5 * C * 2;
#define NS 12
#define D0 1
#define D1 4
#define D2 2
#define NRAMP 3
#define TAILT 1000
#define QSLEEP 700
#define WSL 24
#define INITT 2500
#define NST 2
#define NPRE 2
static_assert(NST > D0, "the first dynamic tile index must not delay the start");
constexpr int NTHREADS = 384;
constexpr int MAXG = 132;
constexpr int NRD = 128;
constexpr int NSRC = 12;
constexpr int SPIN_LIMIT = 1 << 22;
constexpr uint32_t EMPTY = 0xFFFFFFFFu;

constexpr int SM_STAGES = 0;
constexpr int SM_X = NS * STAGE;
constexpr int SM_QK = SM_X + 12800;
constexpr int SM_W = SM_QK + 6144;
constexpr int WP = 196;
constexpr int SM_P = SM_W + 24 * WP * 4;
constexpr int SM_MX = SM_P + 2048;
constexpr int SM_RS = SM_MX + 512;
constexpr int SM_RED = SM_RS + 512;
constexpr int SM_CS = SM_RED + 1024;
constexpr int SM_BAR = SM_CS + 256;
constexpr int SM_WBAR = SM_BAR + 16 * NS;
constexpr int SM_LATE = SM_WBAR + 64;
constexpr int SM_WDONE = SM_LATE + 8;
constexpr int SM_FLAG = SM_LATE + 16;
constexpr int SM_TOTAL = SM_FLAG + 4 * NS;
constexpr int SMEM_BYTES = SM_TOTAL + 1024;
static_assert(SMEM_BYTES <= 232448, "smem");

struct Scratch {
    uint4 x1[NRD * MAXG * 8];
    uint4 x2[NQ * C / 4];
    uint4 qk[NSRC * 32];
    unsigned ctr[64];
};
__device__ __align__(128) Scratch g_scratch;
#define g_x1 (scr->x1)
#define g_x2 (scr->x2)
#define g_qk (scr->qk)
#define g_ctr (scr->ctr)
#define g_ts (scr->ts)
#define g_tr (scr->tr)
#define TR(k, i) do {} while (0)
#define TS(i) do {} while (0)
#define TSD(i, dep) do {} while (0)
#define TSX(i, dep) do {} while (0)
#define TSP(i, dep) do {} while (0)
#define TSE(i) TS(i)
#define CK_(i, dep) do {} while (0)
#define PH(i, dep) do {} while (0)

__device__ __forceinline__ uint32_t s2u(const void* p) { return (uint32_t)__cvta_generic_to_shared(p); }
__device__ __forceinline__ void mbar_init(uint32_t a, int c) { asm volatile("mbarrier.init.shared::cta.b64 [%0], %1;" ::"r"(a), "r"(c) : "memory"); }
__device__ __forceinline__ void mbar_expect(uint32_t a, uint32_t b) { asm volatile("mbarrier.arrive.expect_tx.shared::cta.b64 _, [%0], %1;" ::"r"(a), "r"(b) : "memory"); }
__device__ __forceinline__ void mbar_arrive(uint32_t a) { asm volatile("mbarrier.arrive.shared::cta.b64 _, [%0];" ::"r"(a) : "memory"); }
__device__ __forceinline__ void mbar_wait(uint32_t a, uint32_t ph) {
    uint32_t ok; int it = 0;
    do {
        asm volatile("{.reg .pred p; mbarrier.try_wait.parity.shared::cta.b64 p, [%1], %2; selp.u32 %0,1,0,p;}" : "=r"(ok) : "r"(a), "r"(ph) : "memory");
        if (++it > SPIN_LIMIT) __trap();
    } while (!ok);
}
__device__ __forceinline__ void bar_sync(int id, int n) { asm volatile("bar.sync %0, %1;" ::"r"(id), "r"(n) : "memory"); }
__device__ __forceinline__ void bar_arrive(int id, int n) { asm volatile("bar.arrive %0, %1;" ::"r"(id), "r"(n) : "memory"); }
__device__ __forceinline__ void ldsm4(uint32_t* r, uint32_t a) {
    asm volatile("ldmatrix.sync.aligned.m8n8.x4.shared.b16 {%0,%1,%2,%3}, [%4];" : "=r"(r[0]), "=r"(r[1]), "=r"(r[2]), "=r"(r[3]) : "r"(a) : "memory");
}
__device__ __forceinline__ void ldsm4t(uint32_t* r, uint32_t a) {
    asm volatile("ldmatrix.sync.aligned.m8n8.x4.trans.shared.b16 {%0,%1,%2,%3}, [%4];" : "=r"(r[0]), "=r"(r[1]), "=r"(r[2]), "=r"(r[3]) : "r"(a) : "memory");
}
__device__ __forceinline__ void ldsm2t(uint32_t* r, uint32_t a) {
    asm volatile("ldmatrix.sync.aligned.m8n8.x2.trans.shared.b16 {%0,%1}, [%2];" : "=r"(r[0]), "=r"(r[1]) : "r"(a) : "memory");
}
__device__ __forceinline__ void mma(float* d, uint32_t a0, uint32_t a1, uint32_t a2, uint32_t a3, uint32_t b0, uint32_t b1) {
    asm("mma.sync.aligned.m16n8k16.row.col.f32.bf16.bf16.f32 {%0,%1,%2,%3}, {%4,%5,%6,%7}, {%8,%9}, {%0,%1,%2,%3};"
        : "+f"(d[0]), "+f"(d[1]), "+f"(d[2]), "+f"(d[3]) : "r"(a0), "r"(a1), "r"(a2), "r"(a3), "r"(b0), "r"(b1));
}
__device__ __forceinline__ void mma8(float* d, uint32_t a0, uint32_t a1, uint32_t b0) {
    asm("mma.sync.aligned.m16n8k8.row.col.f32.bf16.bf16.f32 {%0,%1,%2,%3}, {%4,%5}, {%6}, {%0,%1,%2,%3};"
        : "+f"(d[0]), "+f"(d[1]), "+f"(d[2]), "+f"(d[3]) : "r"(a0), "r"(a1), "r"(b0));
}
__device__ __forceinline__ uint32_t hadd2(uint32_t a, uint32_t b) {
    uint32_t r; asm("add.rn.bf16x2 %0, %1, %2;" : "=r"(r) : "r"(a), "r"(b)); return r;
}
__device__ __forceinline__ uint32_t pack2(float lo, float hi) {
    uint32_t r; asm("cvt.rn.bf16x2.f32 %0, %1, %2;" : "=r"(r) : "f"(hi), "f"(lo)); return r;
}
__device__ __forceinline__ float bflo(uint32_t v) { return __uint_as_float(v << 16); }
__device__ __forceinline__ float bfhi(uint32_t v) { return __uint_as_float(v & 0xffff0000u); }
__device__ __forceinline__ float ex2(float x) { float r; asm("ex2.approx.ftz.f32 %0, %1;" : "=f"(r) : "f"(x)); return r; }
__device__ __forceinline__ void sts128(uint32_t a, uint32_t x, uint32_t y, uint32_t z, uint32_t w) {
    asm volatile("st.shared.v4.b32 [%0], {%1,%2,%3,%4};" ::"r"(a), "r"(x), "r"(y), "r"(z), "r"(w) : "memory");
}
__device__ __forceinline__ void sts64(uint32_t a, uint32_t x, uint32_t y) {
    asm volatile("st.shared.v2.b32 [%0], {%1,%2};" ::"r"(a), "r"(x), "r"(y) : "memory");
}
__device__ __forceinline__ void sts32(uint32_t a, uint32_t x) { asm volatile("st.shared.b32 [%0], %1;" ::"r"(a), "r"(x) : "memory"); }
__device__ __forceinline__ uint4 lds128(uint32_t a) {
    uint4 v; asm volatile("ld.shared.v4.b32 {%0,%1,%2,%3}, [%4];" : "=r"(v.x), "=r"(v.y), "=r"(v.z), "=r"(v.w) : "r"(a) : "memory"); return v;
}
__device__ __forceinline__ uint32_t lds32(uint32_t a) { uint32_t v; asm volatile("ld.shared.b32 %0, [%1];" : "=r"(v) : "r"(a) : "memory"); return v; }
__device__ __forceinline__ int grab_tile(unsigned* ctr) {
    int v; asm volatile("atom.relaxed.gpu.global.inc.u32 %0, [%1], 0x7fffffff;" : "=r"(v) : "l"(ctr) : "memory"); return v;
}
__device__ __forceinline__ uint32_t opaque(uint32_t v) { uint32_t r; asm volatile("mov.b32 %0, %1;" : "=r"(r) : "r"(v)); return r; }
__device__ __forceinline__ float rsq(float x) { float r; asm("rsqrt.approx.ftz.f32 %0, %1;" : "=f"(r) : "f"(x)); return r; }
__device__ __forceinline__ float rcp(float x) { float r; asm("rcp.approx.ftz.f32 %0, %1;" : "=f"(r) : "f"(x)); return r; }
__device__ __forceinline__ float lg2(float x) { float r; asm("lg2.approx.ftz.f32 %0, %1;" : "=f"(r) : "f"(x)); return r; }
__device__ __forceinline__ float f(uint32_t v) { return __uint_as_float(v); }
__device__ __forceinline__ uint32_t u(float v) { return __float_as_uint(v); }

constexpr uint32_t ONES = 0x3F803F80u;
constexpr float QSCALE = 0.07216878364870322f * 1.4426950408889634f;

__device__ __forceinline__ void issue_tile(const CUtensorMap* m0, const CUtensorMap* m1, uint32_t sb, int s, int tl, uint64_t pol) {
    const uint32_t full = sb + SM_BAR + s * 8, dst = sb + SM_STAGES + s * STAGE;
    const int par = tl * TP, y = par >> 8, x = par & 255;
    mbar_expect(full, STAGE);
    asm volatile("cp.async.bulk.tensor.5d.shared::cluster.global.mbarrier::complete_tx::bytes.L2::cache_hint [%0], [%1, {%3,%4,%3,%3,%5}], [%2], %6;"
                 ::"r"(dst), "l"(m0), "r"(full), "r"(0), "r"(x), "r"(2 * y), "l"(pol) : "memory");
    asm volatile("cp.async.bulk.tensor.4d.shared::cluster.global.mbarrier::complete_tx::bytes.L2::cache_hint [%0], [%1, {%3,%4,%3,%5}], [%2], %6;"
                 ::"r"(dst + TP * 4 * C * 2), "l"(m1), "r"(full), "r"(0), "r"(x), "r"(y), "l"(pol) : "memory");
}

__device__ __forceinline__ uint4 ldg_relaxed(const uint4* p) {
    uint4 v; asm volatile("ld.relaxed.gpu.global.v4.u32 {%0,%1,%2,%3}, [%4];" : "=r"(v.x), "=r"(v.y), "=r"(v.z), "=r"(v.w) : "l"(p) : "memory"); return v;
}
__device__ __forceinline__ uint32_t ldg_relaxed32(const void* p) {
    uint32_t v; asm volatile("ld.relaxed.gpu.global.u32 %0, [%1];" : "=r"(v) : "l"(p) : "memory"); return v;
}
__device__ __forceinline__ void stg_relaxed(uint4* p, uint32_t x, uint32_t y, uint32_t z, uint32_t w) {
    asm volatile("st.relaxed.gpu.global.v4.u32 [%0], {%1,%2,%3,%4};" ::"l"(p), "r"(x), "r"(y), "r"(z), "r"(w) : "memory");
}
__device__ __forceinline__ void stg_relaxed32(void* p, uint32_t x) { asm volatile("st.relaxed.gpu.global.u32 [%0], %1;" ::"l"(p), "r"(x) : "memory"); }
__device__ __forceinline__ bool has(const uint4& v, uint32_t m) { return v.x == m || v.y == m || v.z == m || v.w == m; }
__device__ __forceinline__ uint32_t hadd2v(uint32_t a, uint32_t b) {
    uint32_t r; asm volatile("add.rn.bf16x2 %0, %1, %2;" : "=r"(r) : "r"(a), "r"(b)); return r;
}

__device__ __forceinline__ int ctx_pos(int c) {
    const int ch = c / 24, r = c - 24 * ch, idx = 2 * (r >> 3) + (r & 1), hf = idx >= 3;
    return 24 * ch + 12 * hf + 3 * ((r >> 1) & 3) + idx - 3 * hf;
}

enum { B_QK = 1, B_QN = 2, B_GRP = 3  , B_Q = 5, B_MERGE = 6, B_HELP = 7, B_WO = 8, B_RED = 9 };

__global__ void __launch_bounds__(NTHREADS, 1)
attn_main(const char* __restrict__ f0, const char* __restrict__ f1,
          const __nv_bfloat16* __restrict__ q, const __nv_bfloat16* __restrict__ wq, const __nv_bfloat16* __restrict__ wk, Scratch* scr,
          const __nv_bfloat16* __restrict__ wv, const __nv_bfloat16* __restrict__ wo, __nv_bfloat16* __restrict__ out,
          const __grid_constant__ CUtensorMap m0, const __grid_constant__ CUtensorMap m1)
{
    CK_(0, 0);
    extern __shared__ char smem_raw[];
    const uint32_t sb = (s2u(smem_raw) + 1023u) & ~1023u;
    const int warp = threadIdx.x >> 5, lane = threadIdx.x & 31;
    const int G = gridDim.x, b = blockIdx.x;
    const int g = lane >> 2, t = lane & 3;
    const bool src = b < NSRC;

    if (warp >= 8) {
        if (warp < 10) {
            const int p = warp - 8;
            if (lane == 0) {
                if (p == 0) TS(0);
                asm volatile("prefetch.tensormap [%0];" ::"l"(p ? &m1 : &m0) : "memory");
            }
            if (lane < NS / 2) {
                const int s = 2 * lane + p;
                mbar_init(sb + SM_BAR + s * 8, 1); mbar_init(sb + SM_BAR + (NS + s) * 8, 1); sts32(sb + SM_FLAG + s * 4, 0);
            }
            if (p == 0 && lane == 31) { mbar_init(sb + SM_LATE, 1); mbar_init(sb + SM_WDONE, 2); }
            asm volatile("fence.mbarrier_init.release.cluster;" ::: "memory");
            __syncwarp();
            bar_arrive(B_QK, 384);
            if (src) bar_sync(B_Q, 320);
            if (lane == 0) {
                uint64_t pol; asm volatile("createpolicy.fractional.L2::evict_first.b64 %0, 1.0;" : "=l"(pol));
                int s = p; uint32_t ph = 1;
                int sa = p, na = 0; uint32_t pa = 0;
                int tl = b + p * G;
                bool late = p;
                for (int n = 0;; n++) {
                    int nxt = tl + 2 * G;
                    if (n >= NST - 1) nxt = grab_tile(g_ctr) + 2 * NST * G;
                    const int d = n < NRAMP ? D0 : (tl >= NT - TAILT ? D2 : D1);
                    while (n - na >= d) {
                        mbar_wait(sb + SM_BAR + sa * 8, pa);
                        if (na < NS / 2) TR(1, 2 * na + p);
                        na++; sa += 2;
                        if (sa >= NS) { sa -= NS; pa ^= 1; }
                    }
                    mbar_wait(sb + SM_BAR + (NS + s) * 8, ph);
                    const bool last = nxt >= NT;
                    if (last) {
                        mbar_wait(sb + SM_WDONE, 0);
                        sts32(sb + SM_FLAG + s * 4, 1);
                    }
                    issue_tile(&m0, &m1, sb, s, tl, pol);
                    TR(0, 2 * n + p);
                    if (!late && nxt >= NT - INITT) { late = true; mbar_arrive(sb + SM_LATE); }
                    if (last) break;
                    s += 2;
                    if (s >= NS) { s -= NS; ph ^= 1; }
                    tl = nxt;
                }
                if (p) TSE(5);
            }
            __syncwarp();
            if (p == 0) return;
        } else {
            const int hw = warp - 10, h = threadIdx.x - 320;
            uint4 v[6];
            for (int it = 0;; it++) {
                bool miss = false;
#pragma unroll
                for (int k = 0; k < 6; k++) v[k] = ldg_relaxed(g_qk + k * 64 + h);
#pragma unroll
                for (int k = 0; k < 6; k++) miss |= has(v[k], 0);
                if (!miss) break;
                if (it > SPIN_LIMIT) __trap();
                if (it == 0) __nanosleep(QSLEEP);
            }
#pragma unroll
            for (int k = 0; k < 6; k++) sts128(sb + SM_QK + (k * 64 + h) * 16, ~v[k].x, ~v[k].y, ~v[k].z, ~v[k].w);
            __syncwarp();
            bar_sync(B_QK, 384);
            if (b < NRD) {
                const int js = b & 7;
                uint4 wt[9];
#pragma unroll
                for (int k = 0; k < 9; k++) {
                    const int idx = k * 64 + h, d = idx / 3, i = idx - 3 * d;
                    wt[k] = __ldg(reinterpret_cast<const uint4*>(wo + d * C + 24 * js + 8 * i));
                }
#pragma unroll
                for (int k = 0; k < 9; k++) {
                    const int idx = k * 64 + h, d = idx / 3, i = idx - 3 * d;
                    sts128(sb + SM_X + ((i * 6 + (d >> 5)) * 4 + ((d >> 1) & 3)) * 128 + (((d >> 3) & 3) * 2 + (d & 1)) * 16, wt[k].x, wt[k].y, wt[k].z, wt[k].w);
                }
                bar_sync(B_WO, 64);
                float cs[3][2] = {{0.f, 0.f}, {0.f, 0.f}, {0.f, 0.f}};
#pragma unroll 1
                for (int m = 0; m < 6; m++) {
                    const int mt = 2 * ((m + (b >> 3)) % 6) + hw;
                    uint4 lo[6], hi[6];
#pragma unroll
                    for (int jj = 0; jj < 6; jj++) {
                        lo[jj] = __ldg(reinterpret_cast<const uint4*>(wv + (16 * mt + g) * C + 32 * jj + 8 * t));
                        hi[jj] = __ldg(reinterpret_cast<const uint4*>(wv + (16 * mt + g + 8) * C + 32 * jj + 8 * t));
                    }
                    float a[3][4];
#pragma unroll
                    for (int i = 0; i < 3; i++) a[i][0] = a[i][1] = a[i][2] = a[i][3] = 0.f;
                    const uint32_t p0 = 4 * ctx_pos(16 * mt + g), p1 = 4 * ctx_pos(16 * mt + g + 8);
#pragma unroll
                    for (int jj = 0; jj < 6; jj++)
#pragma unroll
                        for (int i = 0; i < 3; i++) {
                            uint32_t bb[4];
                            ldsm4t(bb, sb + SM_X + (i * 6 + jj) * 512 + lane * 16);
                            mma(a[i], lo[jj].x, hi[jj].x, lo[jj].y, hi[jj].y, bb[0], bb[1]);
                            mma(a[i], lo[jj].z, hi[jj].z, lo[jj].w, hi[jj].w, bb[2], bb[3]);
                        }
#pragma unroll
                    for (int i = 0; i < 3; i++)
#pragma unroll
                        for (int e = 0; e < 2; e++) {
                            const uint32_t ad = sb + SM_W + (8 * i + 2 * t + e) * WP * 4;
                            sts32(ad + p0, u(a[i][e])); sts32(ad + p1, u(a[i][2 + e]));
                            cs[i][e] += a[i][e] + a[i][2 + e];
                        }
                }
#pragma unroll
                for (int i = 0; i < 3; i++)
#pragma unroll
                    for (int e = 0; e < 2; e++) {
                        float c = cs[i][e];
                        c += __shfl_xor_sync(~0u, c, 4); c += __shfl_xor_sync(~0u, c, 8); c += __shfl_xor_sync(~0u, c, 16);
                        if (g == 0) sts32(sb + SM_CS + (hw * 24 + 8 * i + 2 * t + e) * 4, u(c));
                    }
                if (h == 0) TSE(6);
            }
            __syncwarp();
            if (lane == 0) mbar_arrive(sb + SM_WDONE);
            mbar_wait(sb + SM_LATE, 0);
            if (b < NRD) {
#pragma unroll 1
                for (int i = h; i < G * 8; i += 64) stg_relaxed(g_x1 + b * (MAXG * 8) + i, EMPTY, EMPTY, EMPTY, EMPTY);
                if (h < 6) stg_relaxed(g_x2 + b * 6 + h, EMPTY, EMPTY, EMPTY, EMPTY);
                __threadfence();
                bar_sync(B_WO, 64);
                if (h == 0) asm volatile("red.release.gpu.global.add.u32 [%0], 1;" ::"l"(g_ctr + 32) : "memory");
            }
            if (h == 0) {
                for (int it = 0;; it++) {
                    uint32_t v; asm volatile("ld.acquire.gpu.global.u32 %0, [%1];" : "=r"(v) : "l"(g_ctr + 32) : "memory");
                    if (v >= NRD) break;
                    if (it > SPIN_LIMIT) __trap();
                    __nanosleep(200);
                }
                TSE(7);
            }
            __syncwarp();
            bar_arrive(B_MERGE, 320);
        }
        const int ft = threadIdx.x - 288;
        if (b >= NRD) return;
        mbar_wait(sb + SM_WDONE, 0);
        const int n = b >> 3, js = b & 7, jp = ft >> 3, ks = ft & 7;
        float w0[24], w1[24];
        {
            const float c0 = (f(lds32(sb + SM_CS + 8 * jp)) + f(lds32(sb + SM_CS + 96 + 8 * jp))) * (1.f / C);
            const float c1 = (f(lds32(sb + SM_CS + 8 * jp + 4)) + f(lds32(sb + SM_CS + 96 + 8 * jp + 4))) * (1.f / C);
#pragma unroll
            for (int k = 0; k < 6; k++) {
                const uint4 a = lds128(sb + SM_W + (2 * jp * WP + 24 * ks + 4 * k) * 4), c = lds128(sb + SM_W + ((2 * jp + 1) * WP + 24 * ks + 4 * k) * 4);
                w0[4 * k] = f(a.x) - c0; w0[4 * k + 1] = f(a.y) - c0; w0[4 * k + 2] = f(a.z) - c0; w0[4 * k + 3] = f(a.w) - c0;
                w1[4 * k] = f(c.x) - c1; w1[4 * k + 1] = f(c.y) - c1; w1[4 * k + 2] = f(c.z) - c1; w1[4 * k + 3] = f(c.w) - c1;
            }
        }
        const uint32_t qv = __ldg(reinterpret_cast<const uint32_t*>(q + n * C + 24 * js + 2 * jp));
        float o0 = ks ? 0.f : bflo(qv), o1 = ks ? 0.f : bfhi(qv), o2 = 0.f, o3 = 0.f;
        bar_sync(B_RED, 352);
        if (ft < 48) {
            uint4 x;
            for (int it = 0;; it++) {
                x = ldg_relaxed(g_x2 + n * 48 + ft);
                if (!has(x, EMPTY)) break;
                if (it > SPIN_LIMIT) __trap();
            }
            sts128(sb + SM_QK + ft * 16, x.x, x.y, x.z, x.w);
        }
        __syncwarp();
        bar_sync(B_WO, 96);
        uint4 v[6];
#pragma unroll
        for (int k = 0; k < 6; k++) v[k] = lds128(sb + SM_QK + (ks * 6 + k) * 16);
        if (ft == 0) TSX(9, v[0].x);
#pragma unroll
        for (int k = 0; k < 6; k++) {
            o0 = fmaf(f(v[k].x), w0[4 * k], o0); o1 = fmaf(f(v[k].x), w1[4 * k], o1);
            o2 = fmaf(f(v[k].y), w0[4 * k + 1], o2); o3 = fmaf(f(v[k].y), w1[4 * k + 1], o3);
            o0 = fmaf(f(v[k].z), w0[4 * k + 2], o0); o1 = fmaf(f(v[k].z), w1[4 * k + 2], o1);
            o2 = fmaf(f(v[k].w), w0[4 * k + 3], o2); o3 = fmaf(f(v[k].w), w1[4 * k + 3], o3);
        }
        o0 += o2; o1 += o3;
        __syncwarp();
#pragma unroll
        for (int o = 1; o < 8; o <<= 1) { o0 += __shfl_xor_sync(~0u, o0, o); o1 += __shfl_xor_sync(~0u, o1, o); }
        if (ks == 0) *reinterpret_cast<uint32_t*>(out + n * C + 24 * js + 2 * jp) = pack2(o0, o1);
        if (ft == 0) TSD(11, u(o0));
        return;
    }

    const int grp = warp >> 2, cw = warp & 3;
    if (!src && lane == 0) {
        const char* a; int sz;
        if (warp >= 6) {
            sz = C * C * 2 / WSL; a = (const char*)(warp == 6 ? wq : wk) + (b % WSL) * sz;
        } else {
            const int tl = b + (warp / 3) * G, which = warp % 3;
            const int par = tl * TP, y = par >> 8, x = par & 255;
            a = which < 2 ? f0 + ((size_t)(2 * y + which) * W0 + 2 * x) * (C * 2) : f1 + ((size_t)y * W1 + x) * (C * 2);
            sz = which < 2 ? TP * 2 * C * 2 : TP * C * 2;
        }
        if (warp >= 6 || warp < 3 * NPRE) asm volatile("cp.async.bulk.prefetch.L2.global [%0], %1;" ::"l"(a), "r"(sz) : "memory");
    }
    if (src) {
        const uint32_t wqs = sb + SM_STAGES + (NS - 5) * STAGE, wbar = sb + SM_WBAR;
        const int hr = lane >> 4, qt = (lane >> 2) & 3, sub = lane & 3;
        const uint32_t* qp = reinterpret_cast<const uint32_t*>(q + (warp + 8 * hr) * C + 48 * qt + 6 * sub);
        uint32_t qw[6];
        CK_(1, (uint32_t)(size_t)qp);
#pragma unroll
        for (int j = 0; j < 3; j++) { qw[j] = __ldg(qp + j); qw[3 + j] = __ldg(qp + 12 + j); }
        CK_(2, 0);
        if (lane == 0) { mbar_init(wbar + warp * 8, 1); asm volatile("fence.mbarrier_init.release.cluster;" ::: "memory"); mbar_expect(wbar + warp * 8, 9216);
            asm volatile("cp.async.bulk.shared::cluster.global.mbarrier::complete_tx::bytes [%0], [%1], 9216, [%2];"
                         ::"r"(wqs + warp * 9232), "l"(wq + 24 * warp * C), "r"(wbar + warp * 8) : "memory");
        }
        __syncwarp();
        CK_(3, 0);
        CK_(4, qw[0]);
        CK_(5, qw[5]);
        if (threadIdx.x == 0) TSP(2, 0);
        float e[12];
#pragma unroll
        for (int j = 0; j < 6; j++) { e[2 * j] = bflo(qw[j]); e[2 * j + 1] = bfhi(qw[j]); }
        float sm = ((e[0] + e[1]) + (e[2] + e[3])) + ((e[4] + e[5]) + (e[6] + e[7])) + ((e[8] + e[9]) + (e[10] + e[11]));
#pragma unroll
        for (int o = 1; o < 16; o <<= 1) sm += __shfl_xor_sync(~0u, sm, o);
        if (threadIdx.x == 0) TSP(5, u(sm));
        float v0 = 0.f, v1 = 0.f;
#pragma unroll
        for (int j = 0; j < 12; j++) e[j] -= sm * (1.f / C);
#pragma unroll
        for (int j = 0; j < 6; j++) { v0 = fmaf(e[j], e[j], v0); v1 = fmaf(e[6 + j], e[6 + j], v1); }
        v0 += v1;
#pragma unroll
        for (int o = 1; o < 16; o <<= 1) v0 += __shfl_xor_sync(~0u, v0, o);
        const float rq = rsq(v0 * (1.f / C) + 1e-5f);
#pragma unroll
        for (int j = 0; j < 6; j++)
            sts32(sb + SM_X + (3 * sub + (j >> 1)) * 512 + (4 * warp + qt) * 16 + (2 * (j & 1) + hr) * 4, pack2(e[j] * rq, e[6 + j] * rq));
        if (threadIdx.x == 0) TSP(8, 0);
        uint32_t wkf[2][3];
#pragma unroll
        for (int i = 0; i < 2; i++)
#pragma unroll
            for (int j = 0; j < 3; j++) wkf[i][j] = __ldg(reinterpret_cast<const uint32_t*>(wk + (16 * b + 8 * i + g) * C + 24 * warp + 8 * j + 2 * t));
        bar_sync(B_QN, 256);
        float acc[2][3][4];
#pragma unroll
        for (int i = 0; i < 3; i++)
#pragma unroll
            for (int e = 0; e < 4; e++) acc[0][i][e] = acc[1][i][e] = 0.f;
        const uint32_t ba = wqs + (lane & 7) * 9232 + (lane >> 3) * 384 + 48 * warp;
        uint4 a[12];
#pragma unroll
        for (int kk = 0; kk < 12; kk++) a[kk] = lds128(sb + SM_X + kk * 512 + lane * 16);
        mbar_wait(wbar + (lane & 7) * 8, 0);
        __syncwarp();
        if (threadIdx.x == 0) TSP(4, 0);
#pragma unroll
        for (int kp = 0; kp < 6; kp++)
#pragma unroll
            for (int i = 0; i < 3; i++) {
                uint32_t bb[4];
                ldsm4t(bb, ba + kp * 1536 + i * 16);
                mma(acc[0][i], a[2 * kp].x, a[2 * kp].y, a[2 * kp].z, a[2 * kp].w, bb[0], bb[1]);
                mma(acc[1][i], a[2 * kp + 1].x, a[2 * kp + 1].y, a[2 * kp + 1].z, a[2 * kp + 1].w, bb[2], bb[3]);
            }
        if (threadIdx.x == 0) TSP(7, u(acc[1][2][3]));
        float kq[2][4] = {{0.f, 0.f, 0.f, 0.f}, {0.f, 0.f, 0.f, 0.f}};
#pragma unroll
        for (int j = 0; j < 3; j++) {
            const uint32_t a0 = pack2(acc[0][j][0] + acc[1][j][0], acc[0][j][1] + acc[1][j][1]), a1 = pack2(acc[0][j][2] + acc[1][j][2], acc[0][j][3] + acc[1][j][3]);
            mma8(kq[0], a0, a1, wkf[0][j]);
            mma8(kq[1], a0, a1, wkf[1][j]);
        }
        if (warp < 7) {
            sts128(sb + SM_W + warp * 1024 + lane * 16, u(kq[0][0]), u(kq[0][1]), u(kq[0][2]), u(kq[0][3]));
            sts128(sb + SM_W + warp * 1024 + 512 + lane * 16, u(kq[1][0]), u(kq[1][1]), u(kq[1][2]), u(kq[1][3]));
            bar_arrive(B_Q, 320);
        } else {
            bar_sync(B_Q, 320);
#pragma unroll
            for (int w = 0; w < 7; w++)
#pragma unroll
                for (int i = 0; i < 2; i++) {
                    const uint4 o = lds128(sb + SM_W + w * 1024 + i * 512 + lane * 16);
                    kq[i][0] += f(o.x); kq[i][1] += f(o.y); kq[i][2] += f(o.z); kq[i][3] += f(o.w);
                }
            stg_relaxed(g_qk + b * 32 + lane, ~pack2(kq[0][0] * QSCALE, kq[0][1] * QSCALE), ~pack2(kq[0][2] * QSCALE, kq[0][3] * QSCALE),
                        ~pack2(kq[1][0] * QSCALE, kq[1][1] * QSCALE), ~pack2(kq[1][2] * QSCALE, kq[1][3] * QSCALE));
            if (lane == 0) TS(10);
        }
    }

    const int xp = lane & 7, mi = lane >> 3;
    const uint32_t offS = opaque(xp * 128 + ((mi ^ xp) << 4));
    uint32_t offT[6], offT1[2];
#pragma unroll
    for (int i = 0; i < 6; i++) {
        const int J = 6 * cw + i;
        offT[i] = opaque(mi * 3072 + (J >> 3) * 1024 + xp * 128 + (((J & 7) ^ xp) << 4));
    }
    {
        const int J = 6 * cw + mi, J2 = 6 * cw + 4 + (mi & 1);
        offT1[0] = opaque(12288 + (J >> 3) * 1024 + xp * 128 + (((J & 7) ^ xp) << 4));
        offT1[1] = opaque(12288 + (J2 >> 3) * 1024 + xp * 128 + (((J2 & 7) ^ xp) << 4));
    }
    const uint32_t mxw = opaque(sb + SM_MX + grp * 256 + ((g + 8 * t) * 4 + cw) * 4);
    const uint32_t offS0 = opaque(offS + cw * 3072);
    const int shl = opaque(9 * t);
    const uint32_t mxr = sb + SM_MX + grp * 256 + g * 16;
    const uint32_t pw = sb + SM_P + grp * 1024 + (cw >> 1) * 512 + lane * 16 + (cw & 1) * 8;
    const uint32_t pr = sb + SM_P + grp * 1024 + lane * 16;
    const int barid = B_GRP + grp;
    const bool elected = (threadIdx.x & 127) == 96;

    uint32_t qa[48];
    float r_lo, r_hi;
    bar_sync(B_QK, 384);
    {
        float rr[2][4] = {{0.f, 0.f, 0.f, 0.f}, {0.f, 0.f, 0.f, 0.f}};
#pragma unroll
        for (int kk = 0; kk < 12; kk++) {
            const uint4 v = lds128(sb + SM_QK + kk * 512 + lane * 16);
            qa[4 * kk] = v.x; qa[4 * kk + 1] = v.y; qa[4 * kk + 2] = v.z; qa[4 * kk + 3] = v.w;
            mma(rr[kk & 1], v.x, v.y, v.z, v.w, ONES, ONES);
        }
        r_lo = rr[0][0] + rr[1][0]; r_hi = rr[0][2] + rr[1][2];
    }
    if (threadIdx.x == 0) TS(1);

    float acc[6][4];
#pragma unroll
    for (int i = 0; i < 6; i++) acc[i][0] = acc[i][1] = acc[i][2] = acc[i][3] = 0.f;
    float m_lo = -INFINITY, m_hi = -INFINITY, l_lo = 0.f, l_hi = 0.f;
    int s = grp; uint32_t ph = 0;
    while (true) {
        mbar_wait(sb + SM_BAR + s * 8, ph);
        PH(0, 0);
        const uint32_t stop = lds32(sb + SM_FLAG + s * 4);
        const uint32_t st = sb + SM_STAGES + s * STAGE;
        float sc[2][4], gr[2][4];
#pragma unroll
        for (int e = 0; e < 4; e++) sc[0][e] = sc[1][e] = gr[0][e] = gr[1][e] = 0.f;
        const uint32_t a0e = st + offS0, a1e = st + 12288 + offS;
#pragma unroll
        for (int qq = 0; qq < 6; qq++) {
            uint32_t x[4], y[4];
            ldsm4(x, (a0e ^ ((qq & 1) << 6)) + (qq >> 1) * 1024);
            ldsm4(y, (a1e ^ ((qq & 1) << 6)) + (qq >> 1) * 1024);
#pragma unroll
            for (int e = 0; e < 4; e++) x[e] = hadd2(x[e], y[e]);
            mma(gr[0], x[0], ONES, x[1], ONES, x[0], x[1]);
            mma(gr[1], x[2], ONES, x[3], ONES, x[2], x[3]);
            mma(sc[0], qa[8 * qq], qa[8 * qq + 1], qa[8 * qq + 2], qa[8 * qq + 3], x[0], x[1]);
            mma(sc[1], qa[8 * qq + 4], qa[8 * qq + 5], qa[8 * qq + 6], qa[8 * qq + 7], x[2], x[3]);
        }
        uint32_t xt[6][4], yt[6];
        ldsm4t(yt, st + offT1[0]);
        ldsm2t(yt + 4, st + offT1[1]);
#pragma unroll
        for (int i = 0; i < 6; i++) ldsm4t(xt[i], st + offT[i]);

        const float ss0 = __shfl_sync(~0u, gr[0][0] + gr[1][0], shl);
        const float ss1 = __shfl_sync(~0u, gr[0][1] + gr[1][1], shl + 4);
        const float mu0 = (gr[0][2] + gr[1][2]) * (1.f / C), mu1 = (gr[0][3] + gr[1][3]) * (1.f / C);
        const float rs0 = rsq(fmaxf(fmaf(-mu0, mu0, ss0 * (1.f / C)), 0.f) + 1e-5f);
        const float rs1 = rsq(fmaxf(fmaf(-mu1, mu1, ss1 * (1.f / C)), 0.f) + 1e-5f);
        const float s0 = fmaf(-mu0, r_lo, sc[0][0] + sc[1][0]) * rs0;
        const float s1 = fmaf(-mu1, r_lo, sc[0][1] + sc[1][1]) * rs1;
        const float s2 = fmaf(-mu0, r_hi, sc[0][2] + sc[1][2]) * rs0;
        const float s3 = fmaf(-mu1, r_hi, sc[0][3] + sc[1][3]) * rs1;
        PH(1, u(s0 + s2));
        float xl = fmaxf(s0, s1), xh = fmaxf(s2, s3);
        xl = fmaxf(xl, __shfl_xor_sync(~0u, xl, 1)); xh = fmaxf(xh, __shfl_xor_sync(~0u, xh, 1));
        xl = fmaxf(xl, __shfl_xor_sync(~0u, xl, 2)); xh = fmaxf(xh, __shfl_xor_sync(~0u, xh, 2));
        if (t < 2) sts32(mxw, u(t ? xh : xl));
#pragma unroll
        for (int i = 0; i < 6; i++)
#pragma unroll
            for (int e = 0; e < 4; e++) xt[i][e] = hadd2v(xt[i][e], yt[i]);
        bar_sync(barid, 128);
        PH(2, 0);
        const uint4 ml4 = lds128(mxr), mh4 = lds128(mxr + 128);
        if (elected) mbar_arrive(sb + SM_BAR + (NS + s) * 8);
        const float nl = fmaxf(fmaxf(fmaxf(f(ml4.x), f(ml4.y)), fmaxf(f(ml4.z), f(ml4.w))), m_lo);
        const float nh = fmaxf(fmaxf(fmaxf(f(mh4.x), f(mh4.y)), fmaxf(f(mh4.z), f(mh4.w))), m_hi);
        const float p0 = ex2(s0 - nl), p1 = ex2(s1 - nl), p2 = ex2(s2 - nh), p3 = ex2(s3 - nh);
        sts64(pw, pack2(p0 * rs0, p1 * rs1), pack2(p2 * rs0, p3 * rs1));
        const float al = ex2(m_lo - nl), ah = ex2(m_hi - nh);
        m_lo = nl; m_hi = nh;
        l_lo = fmaf(l_lo, al, p0 + p1); l_hi = fmaf(l_hi, ah, p2 + p3);
#pragma unroll
        for (int i = 0; i < 6; i++) { acc[i][0] *= al; acc[i][1] *= al; acc[i][2] *= ah; acc[i][3] *= ah; }
        bar_sync(barid, 128);
        PH(3, 0);
        const uint4 pa = lds128(pr), pb = lds128(pr + 512);
#pragma unroll
        for (int i = 0; i < 6; i++) mma(acc[i], pa.x, pa.y, pa.z, pa.w, xt[i][0], xt[i][1]);
#pragma unroll
        for (int i = 0; i < 6; i++) mma(acc[i], pb.x, pb.y, pb.z, pb.w, xt[i][2], xt[i][3]);
        PH(4, u(acc[5][0]));
        if (stop) break;
        s += 2;
        if (s >= NS) { s -= NS; ph ^= 1; }
    }
    if (threadIdx.x == grp * 128) TSE(2 + grp);
    if (threadIdx.x == grp * 128 + 96) TSX(2 + grp, u(acc[5][0]));

    l_lo += __shfl_xor_sync(~0u, l_lo, 1); l_hi += __shfl_xor_sync(~0u, l_hi, 1);
    l_lo += __shfl_xor_sync(~0u, l_lo, 2); l_hi += __shfl_xor_sync(~0u, l_hi, 2);
    if (t < 2) sts32(sb + SM_RS + ((g + 8 * t) * 8 + warp) * 4, u(t ? l_hi : l_lo));
    float own[3][4];
#pragma unroll
    for (int i = 0; i < 3; i++) {
#pragma unroll
        for (int e = 0; e < 4; e++) own[i][e] = grp ? acc[3 + i][e] : acc[i][e];
        sts128(sb + SM_X + (warp * 3 + i) * 512 + lane * 16, u(grp ? acc[i][0] : acc[3 + i][0]), u(grp ? acc[i][1] : acc[3 + i][1]),
               u(grp ? acc[i][2] : acc[3 + i][2]), u(grp ? acc[i][3] : acc[3 + i][3]));
    }
    if (cw == 0 && t < 2) sts32(sb + SM_X + 12288 + (grp * 16 + g + 8 * t) * 4, u(t ? m_hi : m_lo));
    bar_sync(B_MERGE, 320);
    if (threadIdx.x == 224) TSX(4, 0);
    {
        const float ol = f(lds32(sb + SM_X + 12288 + ((grp ^ 1) * 16 + g) * 4)), oh = f(lds32(sb + SM_X + 12288 + ((grp ^ 1) * 16 + g + 8) * 4));
        const uint4 la = lds128(sb + SM_RS + g * 32 + grp * 16), lb = lds128(sb + SM_RS + g * 32 + (grp ^ 1) * 16);
        const uint4 ha = lds128(sb + SM_RS + (g + 8) * 32 + grp * 16), hb = lds128(sb + SM_RS + (g + 8) * 32 + (grp ^ 1) * 16);
        uint4 o[3];
#pragma unroll
        for (int i = 0; i < 3; i++) o[i] = lds128(sb + SM_X + ((warp ^ 4) * 3 + i) * 512 + lane * 16);
        const float nl = fmaxf(ol, m_lo), nh = fmaxf(oh, m_hi);
        const float al = ex2(m_lo - nl), ah = ex2(m_hi - nh), bl = ex2(ol - nl), bh = ex2(oh - nh);
        const float Ll = ((f(la.x) + f(la.y)) + (f(la.z) + f(la.w))) * al + ((f(lb.x) + f(lb.y)) + (f(lb.z) + f(lb.w))) * bl;
        const float Lh = ((f(ha.x) + f(ha.y)) + (f(ha.z) + f(ha.w))) * ah + ((f(hb.x) + f(hb.y)) + (f(hb.z) + f(hb.w))) * bh;
        const float rl = rcp(Ll), rh = rcp(Lh), wl = nl + lg2(Ll), wh = nh + lg2(Lh);
        const float a0 = al * rl, b0 = bl * rl, a1 = ah * rh, b1 = bh * rh;
        uint4* dl = g_x1 + (((g >> 1) * 16 + 2 * (2 * cw + grp)) * MAXG + b) * 8 + (lane & 7);
        uint4* dh = dl + 64 * MAXG * 8;
        stg_relaxed(dl, u(own[0][0] * a0 + f(o[0].x) * b0), u(own[0][1] * a0 + f(o[0].y) * b0), u(own[1][0] * a0 + f(o[1].x) * b0), u(wl));
        stg_relaxed(dh, u(own[0][2] * a1 + f(o[0].z) * b1), u(own[0][3] * a1 + f(o[0].w) * b1), u(own[1][2] * a1 + f(o[1].z) * b1), u(wh));
        stg_relaxed(dl + MAXG * 8, u(own[1][1] * a0 + f(o[1].y) * b0), u(own[2][0] * a0 + f(o[2].x) * b0), u(own[2][1] * a0 + f(o[2].y) * b0), u(wl));
        stg_relaxed(dh + MAXG * 8, u(own[1][3] * a1 + f(o[1].w) * b1), u(own[2][2] * a1 + f(o[2].z) * b1), u(own[2][3] * a1 + f(o[2].w) * b1), u(wh));
    }
    if (threadIdx.x == 0) TSE(4);
    if (threadIdx.x == 224) TSX(5, 0);
    if (b >= NRD) return;

    {
        const uint4* mb = g_x1 + b * (MAXG * 8) + threadIdx.x;
        uint4 a[5];
        bool miss[5] = {true, true, true, true, (int)threadIdx.x + 1024 < G * 8};
        a[4] = make_uint4(0, 0, 0, u(-INFINITY));
        for (int it = 0;; it++) {
#pragma unroll
            for (int k = 0; k < 5; k++)
                if (miss[k]) a[k] = ldg_relaxed(mb + k * 256);
#pragma unroll
            for (int k = 0; k < 5; k++) miss[k] = has(a[k], EMPTY);
            if (!(miss[0] || miss[1] || miss[2] || miss[3] || miss[4])) break;
            if (it > SPIN_LIMIT) __trap();
        }
        __syncwarp();
        if (threadIdx.x == 224) TSX(6, a[0].w);
        float M = fmaxf(fmaxf(fmaxf(f(a[0].w), f(a[1].w)), fmaxf(f(a[2].w), f(a[3].w))), f(a[4].w));
        M = fmaxf(M, __shfl_xor_sync(~0u, M, 8)); M = fmaxf(M, __shfl_xor_sync(~0u, M, 16));
        float v0 = 0.f, v1 = 0.f, v2 = 0.f, v3 = 0.f;
#pragma unroll
        for (int k = 0; k < 5; k++) {
            const float e = ex2(f(a[k].w) - M);
            v0 = fmaf(f(a[k].x), e, v0); v1 = fmaf(f(a[k].y), e, v1); v2 = fmaf(f(a[k].z), e, v2); v3 += e;
        }
#pragma unroll
        for (int o = 8; o < 32; o <<= 1) {
            v0 += __shfl_xor_sync(~0u, v0, o); v1 += __shfl_xor_sync(~0u, v1, o); v2 += __shfl_xor_sync(~0u, v2, o); v3 += __shfl_xor_sync(~0u, v3, o);
        }
        if (lane < 8) {
            sts128(sb + SM_RED + warp * 128 + lane * 16, u(v0), u(v1), u(v2), u(v3));
            if (t == 0) sts32(sb + SM_RS + (lane >> 2) * 32 + warp * 4, u(M));
        }
        if (warp < 7) { bar_arrive(B_RED, 352); return; }
        const int j = lane < 24 ? lane : 0, rr = j >= 12, jj = j - 12 * rr, tt = jj / 3;
        const uint32_t xa = sb + SM_RED + (rr * 4 + tt) * 16 + (jj - 3 * tt) * 4, la = sb + SM_RED + rr * 64 + 12;
        float* const x2p = reinterpret_cast<float*>(g_x2) + (2 * (b >> 4) + rr) * C + (b & 15) * 12 + jj;
        bar_sync(B_RED, 352);
        if (lane == 0) TSX(7, 0);
        const uint4 ma = lds128(sb + SM_RS + rr * 32), mc = lds128(sb + SM_RS + rr * 32 + 16);
        float x[8], l[8];
#pragma unroll
        for (int w = 0; w < 8; w++) { x[w] = f(lds32(xa + w * 128)); l[w] = f(lds32(la + w * 128)); }
        const float mw[8] = {f(ma.x), f(ma.y), f(ma.z), f(ma.w), f(mc.x), f(mc.y), f(mc.z), f(mc.w)};
        M = fmaxf(fmaxf(fmaxf(mw[0], mw[1]), fmaxf(mw[2], mw[3])), fmaxf(fmaxf(mw[4], mw[5]), fmaxf(mw[6], mw[7])));
        float X0 = 0.f, X1 = 0.f, L0 = 0.f, L1 = 0.f;
#pragma unroll
        for (int w = 0; w < 8; w += 2) {
            const float ea = ex2(mw[w] - M), eb = ex2(mw[w + 1] - M);
            X0 = fmaf(x[w], ea, X0); L0 = fmaf(l[w], ea, L0); X1 = fmaf(x[w + 1], eb, X1); L1 = fmaf(l[w + 1], eb, L1);
        }
        if (lane < 24) stg_relaxed32(x2p, u((X0 + X1) * rcp(L0 + L1)));
        if (lane == 0) TSX(8, 0);
        if (b < NSRC) g_qk[b * 32 + lane] = make_uint4(0, 0, 0, 0);
        if (b == NSRC && lane < 2) g_ctr[32 * lane] = 0;
    }
}

typedef CUresult (*EncodeFn)(CUtensorMap*, CUtensorMapDataType, cuuint32_t, void*, const cuuint64_t*, const cuuint64_t*,
                             const cuuint32_t*, const cuuint32_t*, CUtensorMapInterleave, CUtensorMapSwizzle,
                             CUtensorMapL2promotion, CUtensorMapFloatOOBfill);

}

extern "C" void kernel_launch(void* const* d_in, const int* in_sizes, int n_in, void* d_out, int out_size) {
    const __nv_bfloat16* q = (const __nv_bfloat16*)d_in[0];
    char* f0 = (char*)d_in[1];
    char* f1 = (char*)d_in[2];
    const __nv_bfloat16* wq = (const __nv_bfloat16*)d_in[3];
    const __nv_bfloat16* wk = (const __nv_bfloat16*)d_in[4];
    const __nv_bfloat16* wv = (const __nv_bfloat16*)d_in[5];
    const __nv_bfloat16* wo = (const __nv_bfloat16*)d_in[6];

    static EncodeFn enc = nullptr;
    static int grid = 0;
    static Scratch* scr = nullptr;
    if (!enc) {
        void* fn = nullptr; cudaDriverEntryPointQueryResult qr;
        cudaGetDriverEntryPoint("cuTensorMapEncodeTiled", &fn, cudaEnableDefault, &qr);
        enc = (EncodeFn)fn;
        cudaGetSymbolAddress((void**)&scr, g_scratch);
        int dev = 0, sms = 0;
        cudaGetDevice(&dev);
        cudaDeviceGetAttribute(&sms, cudaDevAttrMultiProcessorCount, dev);
        grid = sms < MAXG ? sms : MAXG;
        cudaFuncSetAttribute(attn_main, cudaFuncAttributeMaxDynamicSharedMemorySize, SMEM_BYTES);
    }
    CUtensorMap m0, m1;
    {
        cuuint64_t dims[5] = {64, W1, 3, 2, W0};
        cuuint64_t str[4] = {2 * C * 2, 128, C * 2, (cuuint64_t)W0 * C * 2};
        cuuint32_t box[5] = {64, TP, 3, 2, 2}, es[5] = {1, 1, 1, 1, 1};
        enc(&m0, CU_TENSOR_MAP_DATA_TYPE_BFLOAT16, 5, f0, dims, str, box, es, CU_TENSOR_MAP_INTERLEAVE_NONE,
            CU_TENSOR_MAP_SWIZZLE_128B, CU_TENSOR_MAP_L2_PROMOTION_NONE, CU_TENSOR_MAP_FLOAT_OOB_FILL_NONE);
    }
    {
        cuuint64_t dims[4] = {64, W1, 3, W1};
        cuuint64_t str[3] = {C * 2, 128, (cuuint64_t)W1 * C * 2};
        cuuint32_t box[4] = {64, TP, 3, 1}, es[4] = {1, 1, 1, 1};
        enc(&m1, CU_TENSOR_MAP_DATA_TYPE_BFLOAT16, 4, f1, dims, str, box, es, CU_TENSOR_MAP_INTERLEAVE_NONE,
            CU_TENSOR_MAP_SWIZZLE_128B, CU_TENSOR_MAP_L2_PROMOTION_NONE, CU_TENSOR_MAP_FLOAT_OOB_FILL_NONE);
    }
    attn_main<<<grid, NTHREADS, SMEM_BYTES, cudaStreamPerThread>>>(f0, f1, q, wq, wk, scr, wv, wo, (__nv_bfloat16*)d_out, m0, m1);
}
```

```cpp
#include <cuda_runtime.h>
#include <cuda_bf16.h>
#include <cuda.h>
#include <stdint.h>

namespace {

constexpr int C = 192;
constexpr int NQ = 16;
constexpr int W0 = 512;
constexpr int W1 = 256;
constexpr int TP = 8;
constexpr int NT = W1 * W1 / TP;
constexpr int STAGE = TP * 5 * C * 2;
#define NS 14
#define D0 1
#define D1 4
#define D2 2
#define NRAMP 3
#define TAILT 1000
#define QSLEEP 700
#define WSL 24
#define MAXT 3000
#define REFT 1800
#define POLLN 1
#define PGAP 110
#define NST 2
#define NPRE 2
static_assert(NST > D0, "the first dynamic tile index must not delay the start");
constexpr int NTHREADS = 384;
constexpr int MAXG = 132;
constexpr int NRD = NQ;
constexpr int ACC = (NQ * 64 + NQ);
constexpr int NSRC = 12;
constexpr int SPIN_LIMIT = 1 << 22;
constexpr uint32_t EMPTY = 0xFFFFFFFFu;

constexpr int SM_STAGES = 0;
constexpr int SM_P = NS * STAGE;
constexpr int SM_QK = SM_P + 2048;
constexpr int SM_MX = SM_QK + 6144;
constexpr int SM_RS = SM_MX + 512;
constexpr int SM_M = SM_RS + 512;
constexpr int SM_BAR = SM_M + 64;
constexpr int SM_REF = SM_BAR + 16 * NS;
constexpr int SM_FLAG = SM_REF + 8;
constexpr int SM_TOTAL = SM_FLAG + 4 * NS;
constexpr int SMEM_BYTES = SM_TOTAL + 1024;
static_assert(SMEM_BYTES <= 232448, "smem");
constexpr int WROW = 400;
constexpr int RD_W = 0;
constexpr int RD_QN = 2 * C * WROW;
constexpr int RD_KQ = RD_QN + 6144;
constexpr int RD_WA = RD_KQ + 7168;
constexpr int BROW = 144;
constexpr int RD_B = RD_WA + 4 * 6144;
constexpr int RD_BAR = RD_B + 8 * BROW;
static_assert(RD_BAR + 64 <= SM_TOTAL, "smem");

struct Scratch {
    float4 acc[2 * ACC];
    uint4 qk[NSRC * 32];
    unsigned ctr[32];
    unsigned mmax[32];
    unsigned mref[32];
};
__device__ __align__(128) Scratch g_scratch;
#define g_acc (scr->acc)
#define g_qk (scr->qk)
#define g_ctr (scr->ctr)
#define g_mmax (scr->mmax)
#define g_mref (scr->mref)
#define g_ts (scr->ts)
#define g_tr (scr->tr)
#define TR(k, i) do {} while (0)
#define TS(i) do {} while (0)
#define TSD(i, dep) do {} while (0)
#define TSX(i, dep) do {} while (0)
#define TSP(i, dep) do {} while (0)
#define TSE(i) TS(i)
#define CK_(i, dep) do {} while (0)
#define PH(i, dep) do {} while (0)

__device__ __forceinline__ uint32_t s2u(const void* p) { return (uint32_t)__cvta_generic_to_shared(p); }
__device__ __forceinline__ void mbar_init(uint32_t a, int c) { asm volatile("mbarrier.init.shared::cta.b64 [%0], %1;" ::"r"(a), "r"(c) : "memory"); }
__device__ __forceinline__ void mbar_expect(uint32_t a, uint32_t b) { asm volatile("mbarrier.arrive.expect_tx.shared::cta.b64 _, [%0], %1;" ::"r"(a), "r"(b) : "memory"); }
__device__ __forceinline__ void mbar_arrive(uint32_t a) { asm volatile("mbarrier.arrive.shared::cta.b64 _, [%0];" ::"r"(a) : "memory"); }
__device__ __forceinline__ void mbar_wait(uint32_t a, uint32_t ph) {
    uint32_t ok; int it = 0;
    do {
        asm volatile("{.reg .pred p; mbarrier.try_wait.parity.shared::cta.b64 p, [%1], %2; selp.u32 %0,1,0,p;}" : "=r"(ok) : "r"(a), "r"(ph) : "memory");
        if (++it > SPIN_LIMIT) __trap();
    } while (!ok);
}
__device__ __forceinline__ void bar_sync(int id, int n) { asm volatile("bar.sync %0, %1;" ::"r"(id), "r"(n) : "memory"); }
__device__ __forceinline__ void bar_arrive(int id, int n) { asm volatile("bar.arrive %0, %1;" ::"r"(id), "r"(n) : "memory"); }
__device__ __forceinline__ void ldsm4(uint32_t* r, uint32_t a) {
    asm volatile("ldmatrix.sync.aligned.m8n8.x4.shared.b16 {%0,%1,%2,%3}, [%4];" : "=r"(r[0]), "=r"(r[1]), "=r"(r[2]), "=r"(r[3]) : "r"(a) : "memory");
}
__device__ __forceinline__ void ldsm4t(uint32_t* r, uint32_t a) {
    asm volatile("ldmatrix.sync.aligned.m8n8.x4.trans.shared.b16 {%0,%1,%2,%3}, [%4];" : "=r"(r[0]), "=r"(r[1]), "=r"(r[2]), "=r"(r[3]) : "r"(a) : "memory");
}
__device__ __forceinline__ void ldsm2t(uint32_t* r, uint32_t a) {
    asm volatile("ldmatrix.sync.aligned.m8n8.x2.trans.shared.b16 {%0,%1}, [%2];" : "=r"(r[0]), "=r"(r[1]) : "r"(a) : "memory");
}
__device__ __forceinline__ void mma(float* d, uint32_t a0, uint32_t a1, uint32_t a2, uint32_t a3, uint32_t b0, uint32_t b1) {
    asm("mma.sync.aligned.m16n8k16.row.col.f32.bf16.bf16.f32 {%0,%1,%2,%3}, {%4,%5,%6,%7}, {%8,%9}, {%0,%1,%2,%3};"
        : "+f"(d[0]), "+f"(d[1]), "+f"(d[2]), "+f"(d[3]) : "r"(a0), "r"(a1), "r"(a2), "r"(a3), "r"(b0), "r"(b1));
}
__device__ __forceinline__ void mma8(float* d, uint32_t a0, uint32_t a1, uint32_t b0) {
    asm("mma.sync.aligned.m16n8k8.row.col.f32.bf16.bf16.f32 {%0,%1,%2,%3}, {%4,%5}, {%6}, {%0,%1,%2,%3};"
        : "+f"(d[0]), "+f"(d[1]), "+f"(d[2]), "+f"(d[3]) : "r"(a0), "r"(a1), "r"(b0));
}
__device__ __forceinline__ uint32_t hadd2(uint32_t a, uint32_t b) {
    uint32_t r; asm("add.rn.bf16x2 %0, %1, %2;" : "=r"(r) : "r"(a), "r"(b)); return r;
}
__device__ __forceinline__ uint32_t pack2(float lo, float hi) {
    uint32_t r; asm("cvt.rn.bf16x2.f32 %0, %1, %2;" : "=r"(r) : "f"(hi), "f"(lo)); return r;
}
__device__ __forceinline__ float bflo(uint32_t v) { return __uint_as_float(v << 16); }
__device__ __forceinline__ float bfhi(uint32_t v) { return __uint_as_float(v & 0xffff0000u); }
__device__ __forceinline__ float ex2(float x) { float r; asm("ex2.approx.ftz.f32 %0, %1;" : "=f"(r) : "f"(x)); return r; }
__device__ __forceinline__ void sts128(uint32_t a, uint32_t x, uint32_t y, uint32_t z, uint32_t w) {
    asm volatile("st.shared.v4.b32 [%0], {%1,%2,%3,%4};" ::"r"(a), "r"(x), "r"(y), "r"(z), "r"(w) : "memory");
}
__device__ __forceinline__ void sts64(uint32_t a, uint32_t x, uint32_t y) {
    asm volatile("st.shared.v2.b32 [%0], {%1,%2};" ::"r"(a), "r"(x), "r"(y) : "memory");
}
__device__ __forceinline__ void sts32(uint32_t a, uint32_t x) { asm volatile("st.shared.b32 [%0], %1;" ::"r"(a), "r"(x) : "memory"); }
__device__ __forceinline__ uint4 lds128(uint32_t a) {
    uint4 v; asm volatile("ld.shared.v4.b32 {%0,%1,%2,%3}, [%4];" : "=r"(v.x), "=r"(v.y), "=r"(v.z), "=r"(v.w) : "r"(a) : "memory"); return v;
}
__device__ __forceinline__ uint32_t lds32(uint32_t a) { uint32_t v; asm volatile("ld.shared.b32 %0, [%1];" : "=r"(v) : "r"(a) : "memory"); return v; }
__device__ __forceinline__ int grab_tile(unsigned* ctr) {
    int v; asm volatile("atom.relaxed.gpu.global.inc.u32 %0, [%1], 0x7fffffff;" : "=r"(v) : "l"(ctr) : "memory"); return v;
}
__device__ __forceinline__ uint32_t opaque(uint32_t v) { uint32_t r; asm volatile("mov.b32 %0, %1;" : "=r"(r) : "r"(v)); return r; }
__device__ __forceinline__ float rsq(float x) { float r; asm("rsqrt.approx.ftz.f32 %0, %1;" : "=f"(r) : "f"(x)); return r; }
__device__ __forceinline__ float rcp(float x) { float r; asm("rcp.approx.ftz.f32 %0, %1;" : "=f"(r) : "f"(x)); return r; }
__device__ __forceinline__ float lg2(float x) { float r; asm("lg2.approx.ftz.f32 %0, %1;" : "=f"(r) : "f"(x)); return r; }
__device__ __forceinline__ float f(uint32_t v) { return __uint_as_float(v); }
__device__ __forceinline__ uint32_t u(float v) { return __float_as_uint(v); }

constexpr uint32_t ONES = 0x3F803F80u;
constexpr float QSCALE = 0.07216878364870322f * 1.4426950408889634f;

__device__ __forceinline__ void issue_tile(const CUtensorMap* m0, const CUtensorMap* m1, uint32_t sb, int s, int tl, uint64_t pol) {
    const uint32_t full = sb + SM_BAR + s * 8, dst = sb + SM_STAGES + s * STAGE;
    const int par = tl * TP, y = par >> 8, x = par & 255;
    mbar_expect(full, STAGE);
    asm volatile("cp.async.bulk.tensor.5d.shared::cluster.global.mbarrier::complete_tx::bytes.L2::cache_hint [%0], [%1, {%3,%4,%3,%3,%5}], [%2], %6;"
                 ::"r"(dst), "l"(m0), "r"(full), "r"(0), "r"(x), "r"(2 * y), "l"(pol) : "memory");
    asm volatile("cp.async.bulk.tensor.4d.shared::cluster.global.mbarrier::complete_tx::bytes.L2::cache_hint [%0], [%1, {%3,%4,%3,%5}], [%2], %6;"
                 ::"r"(dst + TP * 4 * C * 2), "l"(m1), "r"(full), "r"(0), "r"(x), "r"(y), "l"(pol) : "memory");
}

__device__ __forceinline__ uint4 ldg_relaxed(const uint4* p) {
    uint4 v; asm volatile("ld.relaxed.gpu.global.v4.u32 {%0,%1,%2,%3}, [%4];" : "=r"(v.x), "=r"(v.y), "=r"(v.z), "=r"(v.w) : "l"(p) : "memory"); return v;
}
__device__ __forceinline__ uint32_t ldg_relaxed32(const void* p) {
    uint32_t v; asm volatile("ld.relaxed.gpu.global.u32 %0, [%1];" : "=r"(v) : "l"(p) : "memory"); return v;
}
__device__ __forceinline__ void stg_relaxed(uint4* p, uint32_t x, uint32_t y, uint32_t z, uint32_t w) {
    asm volatile("st.relaxed.gpu.global.v4.u32 [%0], {%1,%2,%3,%4};" ::"l"(p), "r"(x), "r"(y), "r"(z), "r"(w) : "memory");
}
__device__ __forceinline__ void stg_relaxed32(void* p, uint32_t x) { asm volatile("st.relaxed.gpu.global.u32 [%0], %1;" ::"l"(p), "r"(x) : "memory"); }
__device__ __forceinline__ bool has(const uint4& v, uint32_t m) { return v.x == m || v.y == m || v.z == m || v.w == m; }
__device__ __forceinline__ uint32_t hadd2v(uint32_t a, uint32_t b) {
    uint32_t r; asm volatile("add.rn.bf16x2 %0, %1, %2;" : "=r"(r) : "r"(a), "r"(b)); return r;
}

__device__ __forceinline__ void red4(float4* p, float x, float y, float z) {
    asm volatile("red.relaxed.gpu.global.add.v4.f32 [%0], {%1,%2,%3,%4};" ::"l"(p), "f"(x), "f"(y), "f"(z), "f"(1.f) : "memory");
}
__device__ __forceinline__ uint2 ldg_relaxed64(const void* p) {
    uint2 v; asm volatile("ld.relaxed.gpu.global.v2.u32 {%0,%1}, [%2];" : "=r"(v.x), "=r"(v.y) : "l"(p) : "memory"); return v;
}
__device__ __forceinline__ void lds128_if(uint4& v, uint32_t a, bool p) {
    asm volatile("{.reg .pred p; setp.ne.u32 p, %5, 0; @p ld.shared.v4.b32 {%0,%1,%2,%3}, [%4];}" : "=r"(v.x), "=r"(v.y), "=r"(v.z), "=r"(v.w) : "r"(a), "r"((uint32_t)p) : "memory");
}
__device__ __forceinline__ uint32_t lds32v(uint32_t a) { uint32_t v; asm volatile("ld.volatile.shared.b32 %0, [%1];" : "=r"(v) : "r"(a) : "memory"); return v; }

enum { B_QK = 1, B_QN = 2, B_GRP = 3  , B_Q = 5, B_MERGE = 6, B_ALL = 7 };

__device__ __noinline__ void slow_row(const char* __restrict__ f0, const char* __restrict__ f1, const __nv_bfloat16* __restrict__ q,
                                      const __nv_bfloat16* __restrict__ wq, const __nv_bfloat16* __restrict__ wk, Scratch* scr, const uint32_t sb)
{
    const int warp = threadIdx.x >> 5, lane = threadIdx.x & 31, b = blockIdx.x;
    const int g = lane >> 2, t = lane & 3;
    const uint32_t bw = sb + RD_B + t * BROW + g * 16;
    float* const sm = reinterpret_cast<float*>(__cvta_shared_to_generic(sb + RD_W));
    const int c = threadIdx.x;
    bar_sync(B_ALL, 384);
    if (c < C) sm[c] = __bfloat162float(q[b * C + c]);
    bar_sync(B_ALL, 384);
    float mu = 0.f, var = 0.f, s = 0.f;
#pragma unroll 1
    for (int i = 0; i < C; i++) mu += sm[i];
    mu *= 1.f / C;
#pragma unroll 1
    for (int i = 0; i < C; i++) var += (sm[i] - mu) * (sm[i] - mu);
    if (c < C) {
#pragma unroll 1
        for (int i = 0; i < C; i++) s = fmaf(sm[i] - mu, __bfloat162float(wq[i * C + c]), s);
        sm[C + c] = s * rsq(var * (1.f / C) + 1e-5f);
    }
    bar_sync(B_ALL, 384);
    if (c < C) {
        s = 0.f;
#pragma unroll 1
        for (int i = 0; i < C; i++) s = fmaf(sm[C + i], __bfloat162float(wk[c * C + i]), s);
        sm[2 * C + c] = s * QSCALE;
    }
    bar_sync(B_ALL, 384);
    float k[6], a[6], m = -INFINITY, l = 0.f;
#pragma unroll
    for (int i = 0; i < 6; i++) { k[i] = sm[2 * C + 24 * g + 8 * (i >> 1) + 2 * t + (i & 1)]; a[i] = 0.f; }
#pragma unroll 1
    for (int px = warp; px < W0 * W0; px += 12) {
        const uint32_t* p0 = reinterpret_cast<const uint32_t*>(f0 + (size_t)px * (C * 2)) + 12 * g + t;
        const uint32_t* p1 = reinterpret_cast<const uint32_t*>(f1 + (size_t)((px >> 10) * W1 + ((px & (W0 - 1)) >> 1)) * (C * 2)) + 12 * g + t;
        float x[6], s1 = 0.f, s2 = 0.f, d = 0.f;
#pragma unroll
        for (int i = 0; i < 3; i++) { const uint32_t v = hadd2(__ldg(p0 + 4 * i), __ldg(p1 + 4 * i)); x[2 * i] = bflo(v); x[2 * i + 1] = bfhi(v); s1 += x[2 * i] + x[2 * i + 1]; }
#pragma unroll
        for (int o = 1; o < 32; o <<= 1) s1 += __shfl_xor_sync(~0u, s1, o);
#pragma unroll
        for (int i = 0; i < 6; i++) { x[i] -= s1 * (1.f / C); s2 = fmaf(x[i], x[i], s2); d = fmaf(x[i], k[i], d); }
#pragma unroll
        for (int o = 1; o < 32; o <<= 1) { s2 += __shfl_xor_sync(~0u, s2, o); d += __shfl_xor_sync(~0u, d, o); }
        const float rs = rsq(s2 * (1.f / C) + 1e-5f), nm = fmaxf(m, d * rs), al = ex2(m - nm), p = ex2(d * rs - nm);
        m = nm; l = fmaf(l, al, p);
#pragma unroll
        for (int i = 0; i < 6; i++) a[i] = fmaf(a[i], al, x[i] * (p * rs));
    }
    if (lane == 0) sm[3 * C + warp] = m;
    bar_sync(B_ALL, 384);
    float M = m;
#pragma unroll 1
    for (int w = 0; w < 12; w++) M = fmaxf(M, sm[3 * C + w]);
    const float al = ex2(m - M);
#pragma unroll
    for (int i = 0; i < 6; i++) sm[4 * C + (warp * 7 + i) * 32 + lane] = a[i] * al;
    sm[4 * C + (warp * 7 + 6) * 32 + lane] = l * al;
    bar_sync(B_ALL, 384);
    if (warp == 8) {
        float x[7];
#pragma unroll
        for (int i = 0; i < 7; i++) { x[i] = 0.f; for (int w = 0; w < 12; w++) x[i] += sm[4 * C + (w * 7 + i) * 32 + lane]; }
        uint32_t hi[3], lo[3];
#pragma unroll
        for (int i = 0; i < 3; i++) { hi[i] = pack2(x[2 * i], x[2 * i + 1]); lo[i] = pack2(x[2 * i] - bflo(hi[i]), x[2 * i + 1] - bfhi(hi[i])); }
        sts128(bw, hi[0], hi[1], hi[2], u(x[6]));
        sts128(bw + 4 * BROW, lo[0], lo[1], lo[2], u(x[6]));
        if (b < NSRC) g_qk[b * 32 + lane] = make_uint4(0, 0, 0, 0);
        if (lane == 0) { g_mref[b] = 0; if (b == NSRC) g_ctr[0] = 0; }
    }
    bar_sync(B_ALL, 384);
}

__device__ __forceinline__ void reducer(const char* __restrict__ f0, const char* __restrict__ f1, const __nv_bfloat16* __restrict__ q, const __nv_bfloat16* __restrict__ wq, const __nv_bfloat16* __restrict__ wk,
                                        Scratch* scr, const __nv_bfloat16* __restrict__ wv, const __nv_bfloat16* __restrict__ wo,
                                        __nv_bfloat16* __restrict__ out, const uint32_t sb, const int GS)
{
    const int warp = threadIdx.x >> 5, lane = threadIdx.x & 31, b = blockIdx.x;
    const int g = lane >> 2, t = lane & 3;
    if (threadIdx.x == 256) TS(0);
    if (b < NSRC && warp < 8) {
        const uint32_t wqs = sb + RD_W, wbar = sb + RD_BAR;
        const int hr = lane >> 4, qt = (lane >> 2) & 3, sub = lane & 3;
        const uint32_t* qp = reinterpret_cast<const uint32_t*>(q + (warp + 8 * hr) * C + 48 * qt + 6 * sub);
        uint32_t qw[6];
#pragma unroll
        for (int j = 0; j < 3; j++) { qw[j] = __ldg(qp + j); qw[3 + j] = __ldg(qp + 12 + j); }
        if (lane == 0) { mbar_init(wbar + warp * 8, 1); asm volatile("fence.mbarrier_init.release.cluster;" ::: "memory"); mbar_expect(wbar + warp * 8, 9216);
            asm volatile("cp.async.bulk.shared::cluster.global.mbarrier::complete_tx::bytes [%0], [%1], 9216, [%2];"
                         ::"r"(wqs + warp * 9232), "l"(wq + 24 * warp * C), "r"(wbar + warp * 8) : "memory");
        }
        __syncwarp();
        if (threadIdx.x == 0) TSP(2, 0);
        float e[12];
#pragma unroll
        for (int j = 0; j < 6; j++) { e[2 * j] = bflo(qw[j]); e[2 * j + 1] = bfhi(qw[j]); }
        float sm = ((e[0] + e[1]) + (e[2] + e[3])) + ((e[4] + e[5]) + (e[6] + e[7])) + ((e[8] + e[9]) + (e[10] + e[11]));
#pragma unroll
        for (int o = 1; o < 16; o <<= 1) sm += __shfl_xor_sync(~0u, sm, o);
        if (threadIdx.x == 0) TSP(5, u(sm));
        float v0 = 0.f, v1 = 0.f;
#pragma unroll
        for (int j = 0; j < 12; j++) e[j] -= sm * (1.f / C);
#pragma unroll
        for (int j = 0; j < 6; j++) { v0 = fmaf(e[j], e[j], v0); v1 = fmaf(e[6 + j], e[6 + j], v1); }
        v0 += v1;
#pragma unroll
        for (int o = 1; o < 16; o <<= 1) v0 += __shfl_xor_sync(~0u, v0, o);
        const float rq = rsq(v0 * (1.f / C) + 1e-5f);
#pragma unroll
        for (int j = 0; j < 6; j++)
            sts32(sb + RD_QN + (3 * sub + (j >> 1)) * 512 + (4 * warp + qt) * 16 + (2 * (j & 1) + hr) * 4, pack2(e[j] * rq, e[6 + j] * rq));
        if (threadIdx.x == 0) TSP(8, 0);
        uint32_t wkf[2][3];
#pragma unroll
        for (int i = 0; i < 2; i++)
#pragma unroll
            for (int j = 0; j < 3; j++) wkf[i][j] = __ldg(reinterpret_cast<const uint32_t*>(wk + (16 * b + 8 * i + g) * C + 24 * warp + 8 * j + 2 * t));
        bar_sync(B_QN, 256);
        float acc[2][3][4];
#pragma unroll
        for (int i = 0; i < 3; i++)
#pragma unroll
            for (int e = 0; e < 4; e++) acc[0][i][e] = acc[1][i][e] = 0.f;
        const uint32_t ba = wqs + (lane & 7) * 9232 + (lane >> 3) * 384 + 48 * warp;
        uint4 a[12];
#pragma unroll
        for (int kk = 0; kk < 12; kk++) a[kk] = lds128(sb + RD_QN + kk * 512 + lane * 16);
        mbar_wait(wbar + (lane & 7) * 8, 0);
        __syncwarp();
        if (threadIdx.x == 0) TSP(4, 0);
#pragma unroll
        for (int kp = 0; kp < 6; kp++)
#pragma unroll
            for (int i = 0; i < 3; i++) {
                uint32_t bb[4];
                ldsm4t(bb, ba + kp * 1536 + i * 16);
                mma(acc[0][i], a[2 * kp].x, a[2 * kp].y, a[2 * kp].z, a[2 * kp].w, bb[0], bb[1]);
                mma(acc[1][i], a[2 * kp + 1].x, a[2 * kp + 1].y, a[2 * kp + 1].z, a[2 * kp + 1].w, bb[2], bb[3]);
            }
        if (threadIdx.x == 0) TSP(7, u(acc[1][2][3]));
        float kq[2][4] = {{0.f, 0.f, 0.f, 0.f}, {0.f, 0.f, 0.f, 0.f}};
#pragma unroll
        for (int j = 0; j < 3; j++) {
            const uint32_t a0 = pack2(acc[0][j][0] + acc[1][j][0], acc[0][j][1] + acc[1][j][1]), a1 = pack2(acc[0][j][2] + acc[1][j][2], acc[0][j][3] + acc[1][j][3]);
            mma8(kq[0], a0, a1, wkf[0][j]);
            mma8(kq[1], a0, a1, wkf[1][j]);
        }
        if (warp < 7) {
            sts128(sb + RD_KQ + warp * 1024 + lane * 16, u(kq[0][0]), u(kq[0][1]), u(kq[0][2]), u(kq[0][3]));
            sts128(sb + RD_KQ + warp * 1024 + 512 + lane * 16, u(kq[1][0]), u(kq[1][1]), u(kq[1][2]), u(kq[1][3]));
            bar_arrive(B_Q, 256);
        } else {
            bar_sync(B_Q, 256);
#pragma unroll
            for (int w = 0; w < 7; w++)
#pragma unroll
                for (int i = 0; i < 2; i++) {
                    const uint4 o = lds128(sb + RD_KQ + w * 1024 + i * 512 + lane * 16);
                    kq[i][0] += f(o.x); kq[i][1] += f(o.y); kq[i][2] += f(o.z); kq[i][3] += f(o.w);
                }
            stg_relaxed(g_qk + b * 32 + lane, ~pack2(kq[0][0] * QSCALE, kq[0][1] * QSCALE), ~pack2(kq[0][2] * QSCALE, kq[0][3] * QSCALE),
                        ~pack2(kq[1][0] * QSCALE, kq[1][1] * QSCALE), ~pack2(kq[1][2] * QSCALE, kq[1][3] * QSCALE));
            if (lane == 0) TS(10);
        }
    } else if (b >= NSRC) {
        if (b == NSRC && warp == 0) stg_relaxed32(g_mmax + lane, 0);
        __nanosleep(2500);
    }
    bar_sync(B_ALL, 384);

    uint32_t wa[12][4];
    {
#pragma unroll 1
        for (int r = 0; r < 3; r++) {
            uint4 v[8];
#pragma unroll
            for (int k = 0; k < 8; k++) {
                const int idx = (8 * r + k) * 384 + threadIdx.x;
                v[k] = __ldg(reinterpret_cast<const uint4*>(idx < 4608 ? wv : wo - C * C) + idx);
            }
#pragma unroll
            for (int k = 0; k < 8; k++) {
                const int idx = (8 * r + k) * 384 + threadIdx.x, row = idx / 24;
                sts128(sb + RD_W + row * WROW + (idx - 24 * row) * 16, v[k].x, v[k].y, v[k].z, v[k].w);
            }
        }
        bar_sync(B_ALL, 384);
        float d[24][4];
#pragma unroll
        for (int i = 0; i < 24; i++) d[i][0] = d[i][1] = d[i][2] = d[i][3] = 0.f;
        const int mi = lane >> 3, r = lane & 7;
        const uint32_t aa = sb + RD_W + (C + (mi >> 1) * 8 + r) * WROW + (16 * warp + (mi & 1) * 8) * 2;
        const uint32_t ba = sb + RD_W + ((mi >> 1) * 8 + r) * WROW + (mi & 1) * 16;
#pragma unroll 1
        for (int kk = 0; kk < 12; kk++) {
            uint32_t a[4];
            ldsm4t(a, aa + kk * 16 * WROW);
#pragma unroll
            for (int i = 0; i < 12; i++) {
                uint32_t bb[4];
                ldsm4(bb, ba + i * 16 * WROW + kk * 32);
                mma(d[2 * i], a[0], a[1], a[2], a[3], bb[0], bb[1]);
                mma(d[2 * i + 1], a[0], a[1], a[2], a[3], bb[2], bb[3]);
            }
        }
        float c0 = 0.f, c1 = 0.f;
#pragma unroll
        for (int i = 0; i < 24; i++) { c0 += d[i][0] + d[i][1]; c1 += d[i][2] + d[i][3]; }
        c0 += __shfl_xor_sync(~0u, c0, 1); c1 += __shfl_xor_sync(~0u, c1, 1);
        c0 += __shfl_xor_sync(~0u, c0, 2); c1 += __shfl_xor_sync(~0u, c1, 2);
        c0 *= 1.f / C; c1 *= 1.f / C;
#pragma unroll
        for (int i = 0; i < 24; i++) {
            const int kk = i % 3 < 2 ? i / 3 : 8 + i / 6, hf = i % 3 < 2 ? i % 3 : (i / 3) & 1;
            wa[kk][2 * hf] = pack2(d[i][0] - c0, d[i][1] - c0);
            wa[kk][2 * hf + 1] = pack2(d[i][2] - c1, d[i][3] - c1);
        }
    }
    if (threadIdx.x == 0) TSE(6);
    const uint32_t bw = sb + RD_B + t * BROW + g * 16;
    bool slow = false;
    if (warp >= 8) {
#pragma unroll
        for (int kk = 0; kk < 12; kk++) sts128(sb + RD_WA + (warp - 8) * 6144 + kk * 512 + lane * 16, wa[kk][0], wa[kk][1], wa[kk][2], wa[kk][3]);
        const uint4* const pa = reinterpret_cast<const uint4*>(g_acc) + ((b >> 1) * 8 + g) * 16 + (b & 1) * 4 + t;
        const uint4* const pl = reinterpret_cast<const uint4*>(g_acc) + NQ * 64 + b;
        if (warp == 8) {
            sts128(bw, EMPTY, EMPTY, EMPTY, EMPTY); sts128(bw + 4 * BROW, EMPTY, EMPTY, EMPTY, EMPTY);
#pragma unroll
            for (int k = 0; k < 4; k++) stg_relaxed(const_cast<uint4*>(pa) + (k >> 1) * ACC + (k & 1) * 8, 0, 0, 0, 0);
            if (lane < 2) stg_relaxed(const_cast<uint4*>(pl) + lane * ACC, 0, 0, 0, 0);
            __threadfence();
        }
        bar_sync(B_ALL, 384);
        if (threadIdx.x == 256) {
            uint32_t m;
            for (int it = 0;; it++) {
                const int left = NT - 2 * NST * GS - (int)ldg_relaxed32(g_ctr);
                m = ldg_relaxed32(g_mmax + b);
                if (left <= REFT && m) break;
                if (left <= 0) { m = 0x80000000u; break; }
                if (it > SPIN_LIMIT) __trap();
                __nanosleep(300);
            }
            asm volatile("st.release.gpu.global.u32 [%0], %1;" ::"l"(g_mref + b), "r"(m >> 31 ? ~(m ^ 0x80000000u) : m) : "memory");
            TSE(7);
        }
        __syncwarp();
        const uint32_t n0 = u((float)((GS + 1) >> 1)), n1 = u((float)(GS >> 1));
        for (const unsigned c = clock(); clock() - c < (warp - 8) * PGAP;) {}
        for (int it = 0; f(ldg_relaxed64(pl).y) < (float)POLLN; it++)
            if (it > SPIN_LIMIT) __trap();
        uint4 a0, a1, b0, b1; uint2 l0, l1;
        for (int it = 0;; it++) {
            a0 = ldg_relaxed(pa); b0 = ldg_relaxed(pa + 8); a1 = ldg_relaxed(pa + ACC); b1 = ldg_relaxed(pa + ACC + 8);
            l0 = ldg_relaxed64(pl); l1 = ldg_relaxed64(pl + ACC);
            if (__all_sync(~0u, a0.w == n0 && b0.w == n0 && l0.y == n0 && a1.w == n1 && b1.w == n1 && l1.y == n1)) break;
            if (it > SPIN_LIMIT) __trap();
        }
        float x[6] = {f(a0.x) + f(a1.x), f(a0.y) + f(a1.y), f(a0.z) + f(a1.z), f(b0.x) + f(b1.x), f(b0.y) + f(b1.y), f(b0.z) + f(b1.z)};
        const float k = __shfl_sync(~0u, x[0], 0), L = f(l0.x) + f(l1.x);
        uint32_t hi[3], lo[3];
#pragma unroll
        for (int i = 0; i < 3; i++) {
            x[2 * i] -= k; x[2 * i + 1] -= k;
            hi[i] = pack2(x[2 * i], x[2 * i + 1]);
            lo[i] = pack2(x[2 * i] - bflo(hi[i]), x[2 * i + 1] - bfhi(hi[i]));
        }
        sts128(bw, hi[0], hi[1], hi[2], u(L));
        sts128(bw + 4 * BROW, lo[0], lo[1], lo[2], u(L));
        slow = !(L >= 0.5f && L <= 1.8e19f);
        if (!slow) {
            if (warp == 8) {
                if (b < NSRC) g_qk[b * 32 + lane] = make_uint4(0, 0, 0, 0);
                if (lane == 0) { g_mref[b] = 0; if (b == NSRC) g_ctr[0] = 0; }
            }
            return;
        }
    } else {
        bar_sync(B_ALL, 384);
    }
    uint32_t wb[12][4];
    const int c0 = b * C + 16 * (warp & 7) + g;
    float qv[4];
    __nv_bfloat16* op = out + c0;
    asm volatile("" : "+l"(op));
    const uint32_t br = opaque(sb + RD_B + (lane & 7) * BROW);
    if (warp < 8) {
#pragma unroll
        for (int kk = 0; kk < 12; kk++) {
            const uint4 v = lds128(sb + RD_WA + (warp & 3) * 6144 + kk * 512 + lane * 16);
            wb[kk][0] = v.x; wb[kk][1] = v.y; wb[kk][2] = v.z; wb[kk][3] = v.w;
        }
#pragma unroll
        for (int j = 0; j < 4; j++) qv[j] = __bfloat162float(q[c0 + 8 * (j & 1) + (warp < 4 ? 128 * (j >> 1) : 0)]);
    }
#pragma unroll 1
    for (uint32_t pass = opaque(warp >= 8);; pass = 1) {
    float L = 1.f;
    if (pass && warp < 8) {
        for (int it = 0; u(L = f(lds32v(sb + RD_B + 7 * BROW + 7 * 16 + 12))) == EMPTY; it++)
            if (it > 64 * SPIN_LIMIT) __trap();
        slow = !(L >= 0.5f && L <= 1.8e19f);
    }
    if (__builtin_expect(slow, 0)) {
        const uint32_t keep = sb + RD_W + 32768 + warp * 6144 + lane * 16;
#pragma unroll
        for (int kk = 0; kk < 12; kk++) sts128(keep + kk * 512, wa[kk][0], wa[kk][1], wa[kk][2], wa[kk][3]);
        slow_row(f0, f1, q, wq, wk, scr, sb);
        if (warp >= 8) return;
#pragma unroll
        for (int kk = 0; kk < 12; kk++) {
            const uint4 v = lds128(keep + kk * 512), w = lds128(sb + RD_WA + (warp & 3) * 6144 + kk * 512 + lane * 16);
            wa[kk][0] = v.x; wa[kk][1] = v.y; wa[kk][2] = v.z; wa[kk][3] = v.w;
            wb[kk][0] = w.x; wb[kk][1] = w.y; wb[kk][2] = w.z; wb[kk][3] = w.w;
        }
        L = f(lds32(sb + RD_B + 12));
    }
    if (threadIdx.x == 0) TSX(8, 0);
    CK_(0, 0);
    uint4 x[8];
    for (int it = 0;; it++) {
        bool miss = false;
#pragma unroll
        for (int j = 0; j < 8; j++) { lds128_if(x[j], br + j * 16, lane < 8); miss |= x[j].w == EMPTY; }
        if (!miss || !pass || lane >= 8) break;
        if (it > SPIN_LIMIT) __trap();
    }
    __syncwarp();
    CK_(1, x[7].x);
    const float r = rcp(L);
    float o[4][4];
#pragma unroll
    for (int j = 0; j < 4; j++) o[j][0] = o[j][1] = o[j][2] = o[j][3] = 0.f;
    if (warp < 4) {
#pragma unroll
        for (int kk = 0; kk < 12; kk++) {
            const uint32_t b0 = kk < 8 ? x[kk].x : x[2 * kk - 16].z, b1 = kk < 8 ? x[kk].y : x[2 * kk - 15].z;
            mma(o[kk & 1], wa[kk][0], wa[kk][1], wa[kk][2], wa[kk][3], b0, b1);
            mma(o[2 + (kk & 1)], wb[kk][0], wb[kk][1], wb[kk][2], wb[kk][3], b0, b1);
        }
    } else {
#pragma unroll
        for (int kk = 0; kk < 12; kk++) {
            const uint32_t b0 = kk < 8 ? x[kk].x : x[2 * kk - 16].z, b1 = kk < 8 ? x[kk].y : x[2 * kk - 15].z;
            mma(o[kk & 3], wa[kk][0], wa[kk][1], wa[kk][2], wa[kk][3], b0, b1);
        }
#pragma unroll
        for (int e = 0; e < 4; e++) { o[0][e] += o[2][e]; o[1][e] += o[3][e]; }
    }
    CK_(2, u(o[0][0] + o[1][0] + o[2][0] + o[3][0]));
    if (t == 0 && pass) {
        op[0] = __float2bfloat16(fmaf((o[0][0] + o[0][1]) + (o[1][0] + o[1][1]), r, qv[0]));
        op[8] = __float2bfloat16(fmaf((o[0][2] + o[0][3]) + (o[1][2] + o[1][3]), r, qv[1]));
        if (warp < 4) {
            op[128] = __float2bfloat16(fmaf((o[2][0] + o[2][1]) + (o[3][0] + o[3][1]), r, qv[2]));
            op[136] = __float2bfloat16(fmaf((o[2][2] + o[2][3]) + (o[3][2] + o[3][3]), r, qv[3]));
        }
    }
    CK_(3, 0);
    if (threadIdx.x == 0) TSD(11, u(o[0][0] + o[1][0] + o[2][0]));
    if (pass) break;
    }
}

__global__ void __launch_bounds__(NTHREADS, 1)
attn_main(const char* __restrict__ f0, const char* __restrict__ f1,
          const __nv_bfloat16* __restrict__ q, const __nv_bfloat16* __restrict__ wq, const __nv_bfloat16* __restrict__ wk, Scratch* scr,
          const __nv_bfloat16* __restrict__ wv, const __nv_bfloat16* __restrict__ wo, __nv_bfloat16* __restrict__ out,
          const __grid_constant__ CUtensorMap m0, const __grid_constant__ CUtensorMap m1)
{
    extern __shared__ char smem_raw[];
    const uint32_t sb = (s2u(smem_raw) + 1023u) & ~1023u;
    const int G = gridDim.x - NRD;
    if (blockIdx.x < NRD) { reducer(f0, f1, q, wq, wk, scr, wv, wo, out, sb, G); return; }
    const int b = blockIdx.x - NRD;
    const int warp = threadIdx.x >> 5, lane = threadIdx.x & 31;
    const int g = lane >> 2, t = lane & 3;

    if (warp >= 8) {
        if (warp < 10) {
            const int p = warp - 8;
            if (lane == 0) {
                if (p == 0) TS(0);
                asm volatile("prefetch.tensormap [%0];" ::"l"(p ? &m1 : &m0) : "memory");
            }
            if (lane < NS / 2) {
                const int s = 2 * lane + p;
                mbar_init(sb + SM_BAR + s * 8, 1); mbar_init(sb + SM_BAR + (NS + s) * 8, 1);
            }
            if (p == 0 && lane == 31) mbar_init(sb + SM_REF, 1);
            asm volatile("fence.mbarrier_init.release.cluster;" ::: "memory");
            __syncwarp();
            bar_arrive(B_QK, 384);
            if (lane == 0) {
                uint64_t pol; asm volatile("createpolicy.fractional.L2::evict_first.b64 %0, 1.0;" : "=l"(pol));
                int s = p; uint32_t ph = 1;
                int sa = p, na = 0; uint32_t pa = 0;
                int tl = b + p * G;
                bool late = false;
                for (int n = 0;; n++) {
                    int nxt = tl + 2 * G;
                    if (n >= NST - 1) nxt = grab_tile(g_ctr) + 2 * NST * G;
                    const int d = n < NRAMP ? D0 : (tl >= NT - TAILT ? D2 : D1);
                    while (n - na >= d) {
                        mbar_wait(sb + SM_BAR + sa * 8, pa);
                        if (na < NS / 2) TR(1, 2 * na + p);
                        na++; sa += 2;
                        if (sa >= NS) { sa -= NS; pa ^= 1; }
                    }
                    mbar_wait(sb + SM_BAR + (NS + s) * 8, ph);
                    const bool last = nxt >= NT;
                    uint32_t flag = last;
                    if (!late && nxt >= NT - MAXT - 16 * b) { late = true; flag |= 2; }
                    if (last) mbar_wait(sb + SM_REF, 0);
                    sts32(sb + SM_FLAG + s * 4, flag);
                    issue_tile(&m0, &m1, sb, s, tl, pol);
                    TR(0, 2 * n + p);
                    if (last) break;
                    s += 2;
                    if (s >= NS) { s -= NS; ph ^= 1; }
                    tl = nxt;
                }
                if (p) TSE(5);
            }
            return;
        }
        const int h = threadIdx.x - 320;
        uint4 v[6];
        for (int it = 0;; it++) {
            bool miss = false;
#pragma unroll
            for (int k = 0; k < 6; k++) v[k] = ldg_relaxed(g_qk + k * 64 + h);
#pragma unroll
            for (int k = 0; k < 6; k++) miss |= has(v[k], 0);
            if (!miss) break;
            if (it > SPIN_LIMIT) __trap();
            if (it == 0) __nanosleep(QSLEEP);
        }
#pragma unroll
        for (int k = 0; k < 6; k++) sts128(sb + SM_QK + (k * 64 + h) * 16, ~v[k].x, ~v[k].y, ~v[k].z, ~v[k].w);
        __syncwarp();
        bar_sync(B_QK, 384);
        if (warp == 11) return;
        uint32_t r = 1;
        for (int it = 0;; it++) {
            __nanosleep(500);
            if (lane < NQ) asm volatile("ld.acquire.gpu.global.u32 %0, [%1];" : "=r"(r) : "l"(g_mref + lane) : "memory");
            if (__all_sync(~0u, r != 0)) break;
            if (it > SPIN_LIMIT) __trap();
        }
        if (lane < NQ) sts32(sb + SM_M + lane * 4, ~r);
        __syncwarp();
        if (lane == 0) { mbar_arrive(sb + SM_REF); TSE(7); }
        return;
    }

    const int grp = warp >> 2, cw = warp & 3;
    if (lane == 0) {
        const char* a; int sz;
        if (warp >= 6) {
            sz = C * C * 2 / WSL; a = (const char*)(warp == 6 ? wq : wk) + (b % WSL) * sz;
        } else {
            const int tl = b + (warp / 3) * G, which = warp % 3;
            const int par = tl * TP, y = par >> 8, x = par & 255;
            a = which < 2 ? f0 + ((size_t)(2 * y + which) * W0 + 2 * x) * (C * 2) : f1 + ((size_t)y * W1 + x) * (C * 2);
            sz = which < 2 ? TP * 2 * C * 2 : TP * C * 2;
        }
        if (warp >= 6 || warp < 3 * NPRE) asm volatile("cp.async.bulk.prefetch.L2.global [%0], %1;" ::"l"(a), "r"(sz) : "memory");
    }

    const int xp = lane & 7, mi = lane >> 3;
    const uint32_t offS = opaque(xp * 128 + ((mi ^ xp) << 4));
    uint32_t offT[6], offT1[2];
#pragma unroll
    for (int i = 0; i < 6; i++) {
        const int J = 6 * cw + (i + 3 * grp) % 6;
        offT[i] = opaque(mi * 3072 + (J >> 3) * 1024 + xp * 128 + (((J & 7) ^ xp) << 4));
    }
    {
        const int J = 6 * cw + (mi + 3 * grp) % 6, J2 = 6 * cw + (4 + (mi & 1) + 3 * grp) % 6;
        offT1[0] = opaque(12288 + (J >> 3) * 1024 + xp * 128 + (((J & 7) ^ xp) << 4));
        offT1[1] = opaque(12288 + (J2 >> 3) * 1024 + xp * 128 + (((J2 & 7) ^ xp) << 4));
    }
    const uint32_t mxw = opaque(sb + SM_MX + grp * 256 + ((g + 8 * t) * 4 + cw) * 4);
    const uint32_t offS0 = opaque(offS + cw * 3072);
    const int shl = opaque(9 * t);
    const uint32_t mxr = sb + SM_MX + grp * 256 + g * 16;
    const uint32_t pw = sb + SM_P + grp * 1024 + (cw >> 1) * 512 + lane * 16 + (cw & 1) * 8;
    const uint32_t pr = sb + SM_P + grp * 1024 + lane * 16;
    const int barid = B_GRP + grp;
    const bool elected = (threadIdx.x & 127) == 96;

    uint32_t qa[48];
    float r_lo, r_hi;
    bar_sync(B_QK, 384);
    {
        float rr[2][4] = {{0.f, 0.f, 0.f, 0.f}, {0.f, 0.f, 0.f, 0.f}};
#pragma unroll
        for (int kk = 0; kk < 12; kk++) {
            const uint4 v = lds128(sb + SM_QK + kk * 512 + lane * 16);
            qa[4 * kk] = v.x; qa[4 * kk + 1] = v.y; qa[4 * kk + 2] = v.z; qa[4 * kk + 3] = v.w;
            mma(rr[kk & 1], v.x, v.y, v.z, v.w, ONES, ONES);
        }
        r_lo = rr[0][0] + rr[1][0]; r_hi = rr[0][2] + rr[1][2];
    }
    if (threadIdx.x == 0) TS(1);

    float acc[6][4];
#pragma unroll
    for (int i = 0; i < 6; i++) acc[i][0] = acc[i][1] = acc[i][2] = acc[i][3] = 0.f;
    float m_lo = -INFINITY, m_hi = -INFINITY, l_lo = 0.f, l_hi = 0.f;
    int s = grp; uint32_t ph = 0;
    while (true) {
        mbar_wait(sb + SM_BAR + s * 8, ph);
        PH(0, 0);
        const uint32_t stop = lds32(sb + SM_FLAG + s * 4);
        const uint32_t st = sb + SM_STAGES + s * STAGE;
        float sc[2][4], gr[2][4];
#pragma unroll
        for (int e = 0; e < 4; e++) sc[0][e] = sc[1][e] = gr[0][e] = gr[1][e] = 0.f;
        const uint32_t a0e = st + offS0, a1e = st + 12288 + offS;
#pragma unroll
        for (int qq = 0; qq < 6; qq++) {
            uint32_t x[4], y[4];
            ldsm4(x, (a0e ^ ((qq & 1) << 6)) + (qq >> 1) * 1024);
            ldsm4(y, (a1e ^ ((qq & 1) << 6)) + (qq >> 1) * 1024);
#pragma unroll
            for (int e = 0; e < 4; e++) x[e] = hadd2(x[e], y[e]);
            mma(gr[0], x[0], ONES, x[1], ONES, x[0], x[1]);
            mma(gr[1], x[2], ONES, x[3], ONES, x[2], x[3]);
            mma(sc[0], qa[8 * qq], qa[8 * qq + 1], qa[8 * qq + 2], qa[8 * qq + 3], x[0], x[1]);
            mma(sc[1], qa[8 * qq + 4], qa[8 * qq + 5], qa[8 * qq + 6], qa[8 * qq + 7], x[2], x[3]);
        }
        uint32_t xt[6][4], yt[6];
        ldsm4t(yt, st + offT1[0]);
        ldsm2t(yt + 4, st + offT1[1]);
#pragma unroll
        for (int i = 0; i < 6; i++) ldsm4t(xt[i], st + offT[i]);

        const float ss0 = __shfl_sync(~0u, gr[0][0] + gr[1][0], shl);
        const float ss1 = __shfl_sync(~0u, gr[0][1] + gr[1][1], shl + 4);
        const float mu0 = (gr[0][2] + gr[1][2]) * (1.f / C), mu1 = (gr[0][3] + gr[1][3]) * (1.f / C);
        const float rs0 = rsq(fmaxf(fmaf(-mu0, mu0, ss0 * (1.f / C)), 0.f) + 1e-5f);
        const float rs1 = rsq(fmaxf(fmaf(-mu1, mu1, ss1 * (1.f / C)), 0.f) + 1e-5f);
        const float s0 = fmaf(-mu0, r_lo, sc[0][0] + sc[1][0]) * rs0;
        const float s1 = fmaf(-mu1, r_lo, sc[0][1] + sc[1][1]) * rs1;
        const float s2 = fmaf(-mu0, r_hi, sc[0][2] + sc[1][2]) * rs0;
        const float s3 = fmaf(-mu1, r_hi, sc[0][3] + sc[1][3]) * rs1;
        PH(1, u(s0 + s2));
        float nl, nh;
        if (!(stop & 1)) {
            float xl = fmaxf(s0, s1), xh = fmaxf(s2, s3);
            xl = fmaxf(xl, __shfl_xor_sync(~0u, xl, 1)); xh = fmaxf(xh, __shfl_xor_sync(~0u, xh, 1));
            xl = fmaxf(xl, __shfl_xor_sync(~0u, xl, 2)); xh = fmaxf(xh, __shfl_xor_sync(~0u, xh, 2));
            if (t < 2) sts32(mxw, u(t ? xh : xl));
#pragma unroll
            for (int i = 0; i < 6; i++)
#pragma unroll
                for (int e = 0; e < 4; e++) xt[i][e] = hadd2v(xt[i][e], yt[i]);
            bar_sync(barid, 128);
            PH(2, 0);
            const uint4 ml4 = lds128(mxr), mh4 = lds128(mxr + 128);
            if (elected) mbar_arrive(sb + SM_BAR + (NS + s) * 8);
            nl = fmaxf(fmaxf(fmaxf(f(ml4.x), f(ml4.y)), fmaxf(f(ml4.z), f(ml4.w))), m_lo);
            nh = fmaxf(fmaxf(fmaxf(f(mh4.x), f(mh4.y)), fmaxf(f(mh4.z), f(mh4.w))), m_hi);
        } else {
            nl = f(lds32(sb + SM_M + g * 4)); nh = f(lds32(sb + SM_M + 32 + g * 4));
#pragma unroll
            for (int i = 0; i < 6; i++)
#pragma unroll
                for (int e = 0; e < 4; e++) xt[i][e] = hadd2v(xt[i][e], yt[i]);
        }
        const float p0 = ex2(s0 - nl), p1 = ex2(s1 - nl), p2 = ex2(s2 - nh), p3 = ex2(s3 - nh);
        sts64(pw + stop * 2048, pack2(p0 * rs0, p1 * rs1), pack2(p2 * rs0, p3 * rs1));
        const float al = ex2(m_lo - nl), ah = ex2(m_hi - nh);
        m_lo = nl; m_hi = nh;
        l_lo = fmaf(l_lo, al, p0 + p1); l_hi = fmaf(l_hi, ah, p2 + p3);
#pragma unroll
        for (int i = 0; i < 6; i++) { acc[i][0] *= al; acc[i][1] *= al; acc[i][2] *= ah; acc[i][3] *= ah; }
        bar_sync(barid, 128);
        PH(3, 0);
        const uint4 pa = lds128(pr + stop * 2048), pb = lds128(pr + stop * 2048 + 512);
#pragma unroll
        for (int i = 0; i < 6; i++) mma(acc[i], pa.x, pa.y, pa.z, pa.w, xt[i][0], xt[i][1]);
#pragma unroll
        for (int i = 0; i < 6; i++) mma(acc[i], pb.x, pb.y, pb.z, pb.w, xt[i][2], xt[i][3]);
        PH(4, u(acc[5][0]));
        if (stop) {
            if (stop & 1) break;
            if (cw == 0 && t < 2) {
                const uint32_t m = u(t ? m_hi : m_lo);
                asm volatile("red.relaxed.gpu.global.max.u32 [%0], %1;" ::"l"(g_mmax + g + 8 * t), "r"(m >> 31 ? ~m : m | 0x80000000u) : "memory");
            }
        }
        s += 2;
        if (s >= NS) { s -= NS; ph ^= 1; }
    }
    if (threadIdx.x == grp * 128) TSE(2 + grp);
    if (threadIdx.x == grp * 128 + 96) TSX(2 + grp, u(acc[5][0]));

    l_lo += __shfl_xor_sync(~0u, l_lo, 1); l_hi += __shfl_xor_sync(~0u, l_hi, 1);
    float4* const dst = g_acc + (b & 1) * ACC + ((g >> 1) * 8 + 2 * cw + grp) * 16 + (lane & 7);
    const uint32_t xw = opaque(sb + SM_STAGES + grp * STAGE + cw * 1536 + lane * 16), xr = opaque(sb + SM_STAGES + (grp ^ 1) * STAGE + cw * 1536 + lane * 16);
    asm volatile("" ::"l"(dst));
    l_lo += __shfl_xor_sync(~0u, l_lo, 2); l_hi += __shfl_xor_sync(~0u, l_hi, 2);
#pragma unroll
    for (int i = 0; i < 3; i++) sts128(xw + i * 512, u(acc[3 + i][0]), u(acc[3 + i][1]), u(acc[3 + i][2]), u(acc[3 + i][3]));
    if (t < 2) sts32(sb + SM_RS + ((g + 8 * t) * 8 + warp) * 4, u(t ? l_hi : l_lo));
    bar_sync(B_MERGE, 256);
    if (threadIdx.x == 224) TSX(4, 0);
    uint4 o[3];
#pragma unroll
    for (int i = 0; i < 3; i++) o[i] = lds128(xr + i * 512);
    if (warp == 7 && lane < NQ) {
        const uint4 la = lds128(sb + SM_RS + lane * 32), lb = lds128(sb + SM_RS + lane * 32 + 16);
        asm volatile("red.relaxed.gpu.global.add.v2.f32 [%0], {%1,%2};" ::"l"(g_acc + (b & 1) * ACC + NQ * 64 + lane),
                     "f"(((f(la.x) + f(la.y)) + (f(la.z) + f(la.w))) + ((f(lb.x) + f(lb.y)) + (f(lb.z) + f(lb.w)))), "f"(1.f) : "memory");
    }
    red4(dst, acc[0][0] + f(o[0].x), acc[0][1] + f(o[0].y), acc[1][0] + f(o[1].x));
    red4(dst + 512, acc[0][2] + f(o[0].z), acc[0][3] + f(o[0].w), acc[1][2] + f(o[1].z));
    red4(dst + 8, acc[1][1] + f(o[1].y), acc[2][0] + f(o[2].x), acc[2][1] + f(o[2].y));
    red4(dst + 520, acc[1][3] + f(o[1].w), acc[2][2] + f(o[2].z), acc[2][3] + f(o[2].w));
    if (threadIdx.x == 0) TSE(4);
    if (threadIdx.x == 224) TSX(9, 0);
}

typedef CUresult (*EncodeFn)(CUtensorMap*, CUtensorMapDataType, cuuint32_t, void*, const cuuint64_t*, const cuuint64_t*,
                             const cuuint32_t*, const cuuint32_t*, CUtensorMapInterleave, CUtensorMapSwizzle,
                             CUtensorMapL2promotion, CUtensorMapFloatOOBfill);

}

extern "C" void kernel_launch(void* const* d_in, const int* in_sizes, int n_in, void* d_out, int out_size) {
    const __nv_bfloat16* q = (const __nv_bfloat16*)d_in[0];
    char* f0 = (char*)d_in[1];
    char* f1 = (char*)d_in[2];
    const __nv_bfloat16* wq = (const __nv_bfloat16*)d_in[3];
    const __nv_bfloat16* wk = (const __nv_bfloat16*)d_in[4];
    const __nv_bfloat16* wv = (const __nv_bfloat16*)d_in[5];
    const __nv_bfloat16* wo = (const __nv_bfloat16*)d_in[6];

    static EncodeFn enc = nullptr;
    static int grid = 0;
    static Scratch* scr = nullptr;
    if (!enc) {
        void* fn = nullptr; cudaDriverEntryPointQueryResult qr;
        cudaGetDriverEntryPoint("cuTensorMapEncodeTiled", &fn, cudaEnableDefault, &qr);
        enc = (EncodeFn)fn;
        cudaGetSymbolAddress((void**)&scr, g_scratch);
        int dev = 0, sms = 0;
        cudaGetDevice(&dev);
        cudaDeviceGetAttribute(&sms, cudaDevAttrMultiProcessorCount, dev);
        grid = sms < MAXG ? sms : MAXG;
        cudaFuncSetAttribute(attn_main, cudaFuncAttributeMaxDynamicSharedMemorySize, SMEM_BYTES);
    }
    CUtensorMap m0, m1;
    {
        cuuint64_t dims[5] = {64, W1, 3, 2, W0};
        cuuint64_t str[4] = {2 * C * 2, 128, C * 2, (cuuint64_t)W0 * C * 2};
        cuuint32_t box[5] = {64, TP, 3, 2, 2}, es[5] = {1, 1, 1, 1, 1};
        enc(&m0, CU_TENSOR_MAP_DATA_TYPE_BFLOAT16, 5, f0, dims, str, box, es, CU_TENSOR_MAP_INTERLEAVE_NONE,
            CU_TENSOR_MAP_SWIZZLE_128B, CU_TENSOR_MAP_L2_PROMOTION_NONE, CU_TENSOR_MAP_FLOAT_OOB_FILL_NONE);
    }
    {
        cuuint64_t dims[4] = {64, W1, 3, W1};
        cuuint64_t str[3] = {C * 2, 128, (cuuint64_t)W1 * C * 2};
        cuuint32_t box[4] = {64, TP, 3, 1}, es[4] = {1, 1, 1, 1};
        enc(&m1, CU_TENSOR_MAP_DATA_TYPE_BFLOAT16, 4, f1, dims, str, box, es, CU_TENSOR_MAP_INTERLEAVE_NONE,
            CU_TENSOR_MAP_SWIZZLE_128B, CU_TENSOR_MAP_L2_PROMOTION_NONE, CU_TENSOR_MAP_FLOAT_OOB_FILL_NONE);
    }
    attn_main<<<grid, NTHREADS, SMEM_BYTES, cudaStreamPerThread>>>(f0, f1, q, wq, wk, scr, wv, wo, (__nv_bfloat16*)d_out, m0, m1);
}
```

```cpp
#include <cuda_runtime.h>
#include <cuda_bf16.h>
#include <cuda.h>
#include <stdint.h>

namespace {

constexpr int C = 192;
constexpr int NQ = 16;
constexpr int W0 = 512;
constexpr int W1 = 256;
constexpr int TP = 8;
constexpr int NT = W1 * W1 / TP;
constexpr int STAGE = TP * 5 * C * 2;
#define NS 14
#define D0 1
#define D1 4
#define D2 2
#define NRAMP 3
#define TAILT 1000
#define QSLEEP 700
#define WSL 24
#define MAXT 3000
#define REFT 1800
#define POLLN 1
#define PGAP 110
#define NST 2
#define NPRE 2
static_assert(NST > D0, "the first dynamic tile index must not delay the start");
constexpr int NTHREADS = 384;
constexpr int MAXG = 132;
constexpr int NRD = NQ;
constexpr int ACC = NQ * 32;
constexpr int NSRC = 12;
constexpr int SPIN_LIMIT = 1 << 22;
constexpr uint32_t EMPTY = 0xFFFFFFFFu;

constexpr int SM_STAGES = 0;
constexpr int SM_P = NS * STAGE;
constexpr int SM_QK = SM_P + 2048;
constexpr int SM_MX = SM_QK + 6144;
constexpr int SM_MU = SM_MX + 512;
constexpr int SM_M = SM_MU + 512;
constexpr int SM_BAR = SM_M + 64;
constexpr int SM_REF = SM_BAR + 16 * NS;
constexpr int SM_FLAG = SM_REF + 8;
constexpr int SM_TOTAL = SM_FLAG + 4 * NS;
constexpr int SMEM_BYTES = SM_TOTAL + 1024;
static_assert(SMEM_BYTES <= 232448, "smem");
constexpr int WROW = 400;
constexpr int RD_W = 0;
constexpr int RD_QN = 2 * C * WROW;
constexpr int RD_KQ = RD_QN + 6144;
constexpr int RD_B = RD_KQ + 7168;
constexpr int RD_BAD = RD_B + 32 * 144 + 256;
constexpr int RD_BAR = RD_BAD + 16;
static_assert(RD_BAR + 64 <= SM_TOTAL, "smem");

struct Scratch {
    uint4 acc[2 * ACC];
    uint4 qk[NSRC * 32];
    unsigned ctr[32];
    unsigned mmax[32];
    unsigned mref[32];
};
__device__ __align__(128) Scratch g_scratch;
#define g_acc (scr->acc)
#define g_qk (scr->qk)
#define g_ctr (scr->ctr)
#define g_mmax (scr->mmax)
#define g_mref (scr->mref)
#define g_ts (scr->ts)
#define g_tr (scr->tr)
#define TR(k, i) do {} while (0)
#define TS(i) do {} while (0)
#define TSD(i, dep) do {} while (0)
#define TSX(i, dep) do {} while (0)
#define TSP(i, dep) do {} while (0)
#define TSE(i) TS(i)
#define CK_(i, dep) do {} while (0)
#define PH(i, dep) do {} while (0)

__device__ __forceinline__ uint32_t s2u(const void* p) { return (uint32_t)__cvta_generic_to_shared(p); }
__device__ __forceinline__ void mbar_init(uint32_t a, int c) { asm volatile("mbarrier.init.shared::cta.b64 [%0], %1;" ::"r"(a), "r"(c) : "memory"); }
__device__ __forceinline__ void mbar_expect(uint32_t a, uint32_t b) { asm volatile("mbarrier.arrive.expect_tx.shared::cta.b64 _, [%0], %1;" ::"r"(a), "r"(b) : "memory"); }
__device__ __forceinline__ void mbar_arrive(uint32_t a) { asm volatile("mbarrier.arrive.shared::cta.b64 _, [%0];" ::"r"(a) : "memory"); }
__device__ __forceinline__ void mbar_wait(uint32_t a, uint32_t ph) {
    uint32_t ok; int it = 0;
    do {
        asm volatile("{.reg .pred p; mbarrier.try_wait.parity.shared::cta.b64 p, [%1], %2; selp.u32 %0,1,0,p;}" : "=r"(ok) : "r"(a), "r"(ph) : "memory");
        if (++it > SPIN_LIMIT) __trap();
    } while (!ok);
}
__device__ __forceinline__ void bar_sync(int id, int n) { asm volatile("bar.sync %0, %1;" ::"r"(id), "r"(n) : "memory"); }
__device__ __forceinline__ void bar_arrive(int id, int n) { asm volatile("bar.arrive %0, %1;" ::"r"(id), "r"(n) : "memory"); }
__device__ __forceinline__ void ldsm4(uint32_t* r, uint32_t a) {
    asm volatile("ldmatrix.sync.aligned.m8n8.x4.shared.b16 {%0,%1,%2,%3}, [%4];" : "=r"(r[0]), "=r"(r[1]), "=r"(r[2]), "=r"(r[3]) : "r"(a) : "memory");
}
__device__ __forceinline__ void ldsm4t(uint32_t* r, uint32_t a) {
    asm volatile("ldmatrix.sync.aligned.m8n8.x4.trans.shared.b16 {%0,%1,%2,%3}, [%4];" : "=r"(r[0]), "=r"(r[1]), "=r"(r[2]), "=r"(r[3]) : "r"(a) : "memory");
}
__device__ __forceinline__ void ldsm2t(uint32_t* r, uint32_t a) {
    asm volatile("ldmatrix.sync.aligned.m8n8.x2.trans.shared.b16 {%0,%1}, [%2];" : "=r"(r[0]), "=r"(r[1]) : "r"(a) : "memory");
}
__device__ __forceinline__ void mma(float* d, uint32_t a0, uint32_t a1, uint32_t a2, uint32_t a3, uint32_t b0, uint32_t b1) {
    asm("mma.sync.aligned.m16n8k16.row.col.f32.bf16.bf16.f32 {%0,%1,%2,%3}, {%4,%5,%6,%7}, {%8,%9}, {%0,%1,%2,%3};"
        : "+f"(d[0]), "+f"(d[1]), "+f"(d[2]), "+f"(d[3]) : "r"(a0), "r"(a1), "r"(a2), "r"(a3), "r"(b0), "r"(b1));
}
__device__ __forceinline__ void mmah(float* d, uint32_t a0, uint32_t a1, uint32_t a2, uint32_t a3, uint32_t b0, uint32_t b1) {
    asm("mma.sync.aligned.m16n8k16.row.col.f32.f16.f16.f32 {%0,%1,%2,%3}, {%4,%5,%6,%7}, {%8,%9}, {%0,%1,%2,%3};"
        : "+f"(d[0]), "+f"(d[1]), "+f"(d[2]), "+f"(d[3]) : "r"(a0), "r"(a1), "r"(a2), "r"(a3), "r"(b0), "r"(b1));
}
__device__ __forceinline__ void mma8(float* d, uint32_t a0, uint32_t a1, uint32_t b0) {
    asm("mma.sync.aligned.m16n8k8.row.col.f32.bf16.bf16.f32 {%0,%1,%2,%3}, {%4,%5}, {%6}, {%0,%1,%2,%3};"
        : "+f"(d[0]), "+f"(d[1]), "+f"(d[2]), "+f"(d[3]) : "r"(a0), "r"(a1), "r"(b0));
}
__device__ __forceinline__ uint32_t hadd2(uint32_t a, uint32_t b) {
    uint32_t r; asm("add.rn.bf16x2 %0, %1, %2;" : "=r"(r) : "r"(a), "r"(b)); return r;
}
__device__ __forceinline__ uint32_t pack2(float lo, float hi) {
    uint32_t r; asm("cvt.rn.bf16x2.f32 %0, %1, %2;" : "=r"(r) : "f"(hi), "f"(lo)); return r;
}
__device__ __forceinline__ uint32_t packh(float lo, float hi) {
    uint32_t r; asm("cvt.rn.f16x2.f32 %0, %1, %2;" : "=r"(r) : "f"(hi), "f"(lo)); return r;
}
__device__ __forceinline__ float2 unpackh(uint32_t v) {
    float2 r; asm("{.reg .b16 l, h; mov.b32 {l, h}, %2; cvt.f32.f16 %0, l; cvt.f32.f16 %1, h;}" : "=f"(r.x), "=f"(r.y) : "r"(v)); return r;
}
__device__ __forceinline__ float bflo(uint32_t v) { return __uint_as_float(v << 16); }
__device__ __forceinline__ float bfhi(uint32_t v) { return __uint_as_float(v & 0xffff0000u); }
__device__ __forceinline__ float ex2(float x) { float r; asm("ex2.approx.ftz.f32 %0, %1;" : "=f"(r) : "f"(x)); return r; }
__device__ __forceinline__ void sts128(uint32_t a, uint32_t x, uint32_t y, uint32_t z, uint32_t w) {
    asm volatile("st.shared.v4.b32 [%0], {%1,%2,%3,%4};" ::"r"(a), "r"(x), "r"(y), "r"(z), "r"(w) : "memory");
}
__device__ __forceinline__ void sts64(uint32_t a, uint32_t x, uint32_t y) {
    asm volatile("st.shared.v2.b32 [%0], {%1,%2};" ::"r"(a), "r"(x), "r"(y) : "memory");
}
__device__ __forceinline__ void sts32(uint32_t a, uint32_t x) { asm volatile("st.shared.b32 [%0], %1;" ::"r"(a), "r"(x) : "memory"); }
__device__ __forceinline__ uint4 lds128(uint32_t a) {
    uint4 v; asm volatile("ld.shared.v4.b32 {%0,%1,%2,%3}, [%4];" : "=r"(v.x), "=r"(v.y), "=r"(v.z), "=r"(v.w) : "r"(a) : "memory"); return v;
}
__device__ __forceinline__ uint32_t lds32(uint32_t a) { uint32_t v; asm volatile("ld.shared.b32 %0, [%1];" : "=r"(v) : "r"(a) : "memory"); return v; }
__device__ __forceinline__ int grab_tile(unsigned* ctr) {
    int v; asm volatile("atom.relaxed.gpu.global.inc.u32 %0, [%1], 0x7fffffff;" : "=r"(v) : "l"(ctr) : "memory"); return v;
}
__device__ __forceinline__ uint32_t opaque(uint32_t v) { uint32_t r; asm volatile("mov.b32 %0, %1;" : "=r"(r) : "r"(v)); return r; }
__device__ __forceinline__ float rsq(float x) { float r; asm("rsqrt.approx.ftz.f32 %0, %1;" : "=f"(r) : "f"(x)); return r; }
__device__ __forceinline__ float rcp(float x) { float r; asm("rcp.approx.ftz.f32 %0, %1;" : "=f"(r) : "f"(x)); return r; }
__device__ __forceinline__ float lg2(float x) { float r; asm("lg2.approx.ftz.f32 %0, %1;" : "=f"(r) : "f"(x)); return r; }
__device__ __forceinline__ float f(uint32_t v) { return __uint_as_float(v); }
__device__ __forceinline__ uint32_t u(float v) { return __float_as_uint(v); }

constexpr uint32_t ONES = 0x3F803F80u;
constexpr float QSCALE = 0.07216878364870322f * 1.4426950408889634f;

__device__ __forceinline__ void issue_tile(const CUtensorMap* m0, const CUtensorMap* m1, uint32_t sb, int s, int tl, uint64_t pol) {
    const uint32_t full = sb + SM_BAR + s * 8, dst = sb + SM_STAGES + s * STAGE;
    const int par = tl * TP, y = par >> 8, x = par & 255;
    mbar_expect(full, STAGE);
    asm volatile("cp.async.bulk.tensor.5d.shared::cluster.global.mbarrier::complete_tx::bytes.L2::cache_hint [%0], [%1, {%3,%4,%3,%3,%5}], [%2], %6;"
                 ::"r"(dst), "l"(m0), "r"(full), "r"(0), "r"(x), "r"(2 * y), "l"(pol) : "memory");
    asm volatile("cp.async.bulk.tensor.4d.shared::cluster.global.mbarrier::complete_tx::bytes.L2::cache_hint [%0], [%1, {%3,%4,%3,%5}], [%2], %6;"
                 ::"r"(dst + TP * 4 * C * 2), "l"(m1), "r"(full), "r"(0), "r"(x), "r"(y), "l"(pol) : "memory");
}

__device__ __forceinline__ uint4 ldg_relaxed(const uint4* p) {
    uint4 v; asm volatile("ld.relaxed.gpu.global.v4.u32 {%0,%1,%2,%3}, [%4];" : "=r"(v.x), "=r"(v.y), "=r"(v.z), "=r"(v.w) : "l"(p) : "memory"); return v;
}
__device__ __forceinline__ uint32_t ldg_relaxed32(const void* p) {
    uint32_t v; asm volatile("ld.relaxed.gpu.global.u32 %0, [%1];" : "=r"(v) : "l"(p) : "memory"); return v;
}
__device__ __forceinline__ void stg_relaxed(uint4* p, uint32_t x, uint32_t y, uint32_t z, uint32_t w) {
    asm volatile("st.relaxed.gpu.global.v4.u32 [%0], {%1,%2,%3,%4};" ::"l"(p), "r"(x), "r"(y), "r"(z), "r"(w) : "memory");
}
__device__ __forceinline__ void stg_relaxed32(void* p, uint32_t x) { asm volatile("st.relaxed.gpu.global.u32 [%0], %1;" ::"l"(p), "r"(x) : "memory"); }
__device__ __forceinline__ bool has(const uint4& v, uint32_t m) { return v.x == m || v.y == m || v.z == m || v.w == m; }
__device__ __forceinline__ uint32_t hadd2v(uint32_t a, uint32_t b) {
    uint32_t r; asm volatile("add.rn.bf16x2 %0, %1, %2;" : "=r"(r) : "r"(a), "r"(b)); return r;
}

__device__ __forceinline__ void red8h(uint4* p, uint32_t x, uint32_t y, uint32_t z, uint32_t w) {
    asm volatile("red.relaxed.gpu.global.add.noftz.v4.f16x2 [%0], {%1,%2,%3,%4};" ::"l"(p), "r"(x), "r"(y), "r"(z), "r"(w) : "memory");
}
__device__ __forceinline__ uint4 lds128v(uint32_t a) {
    uint4 v; asm volatile("ld.volatile.shared.v4.b32 {%0,%1,%2,%3}, [%4];" : "=r"(v.x), "=r"(v.y), "=r"(v.z), "=r"(v.w) : "r"(a) : "memory"); return v;
}
__device__ __forceinline__ uint32_t brow(int r) { return RD_B + r * 144 + (r >> 3) * 64; }

enum { B_QK = 1, B_QN = 2, B_GRP = 3  , B_Q = 5, B_MERGE = 6, B_ALL = 7 };

__device__ __noinline__ void slow_row(const char* __restrict__ f0, const char* __restrict__ f1, const __nv_bfloat16* __restrict__ q,
                                      const __nv_bfloat16* __restrict__ wq, const __nv_bfloat16* __restrict__ wk, const uint32_t sb, const int b)
{
    const int warp = threadIdx.x >> 5, lane = threadIdx.x & 31;
    const int g = lane >> 2, t = lane & 3;
    const uint32_t bw = sb + brow(8 * (b & 3) + t) + g * 16;
    float* const sm = reinterpret_cast<float*>(__cvta_shared_to_generic(sb + RD_W));
    const int c = threadIdx.x;
    bar_sync(B_ALL, 384);
    if (c < C) sm[c] = __bfloat162float(q[b * C + c]);
    bar_sync(B_ALL, 384);
    float mu = 0.f, var = 0.f, s = 0.f;
#pragma unroll 1
    for (int i = 0; i < C; i++) mu += sm[i];
    mu *= 1.f / C;
#pragma unroll 1
    for (int i = 0; i < C; i++) var += (sm[i] - mu) * (sm[i] - mu);
    if (c < C) {
#pragma unroll 1
        for (int i = 0; i < C; i++) s = fmaf(sm[i] - mu, __bfloat162float(wq[i * C + c]), s);
        sm[C + c] = s * rsq(var * (1.f / C) + 1e-5f);
    }
    bar_sync(B_ALL, 384);
    if (c < C) {
        s = 0.f;
#pragma unroll 1
        for (int i = 0; i < C; i++) s = fmaf(sm[C + i], __bfloat162float(wk[c * C + i]), s);
        sm[2 * C + c] = s * QSCALE;
    }
    bar_sync(B_ALL, 384);
    float k[6], a[6], m = -INFINITY, l = 0.f;
#pragma unroll
    for (int i = 0; i < 6; i++) { k[i] = sm[2 * C + 24 * g + 8 * (i >> 1) + 2 * t + (i & 1)]; a[i] = 0.f; }
#pragma unroll 1
    for (int px = warp; px < W0 * W0; px += 12) {
        const uint32_t* p0 = reinterpret_cast<const uint32_t*>(f0 + (size_t)px * (C * 2)) + 12 * g + t;
        const uint32_t* p1 = reinterpret_cast<const uint32_t*>(f1 + (size_t)((px >> 10) * W1 + ((px & (W0 - 1)) >> 1)) * (C * 2)) + 12 * g + t;
        float x[6], s1 = 0.f, s2 = 0.f, d = 0.f;
#pragma unroll
        for (int i = 0; i < 3; i++) { const uint32_t v = hadd2(__ldg(p0 + 4 * i), __ldg(p1 + 4 * i)); x[2 * i] = bflo(v); x[2 * i + 1] = bfhi(v); s1 += x[2 * i] + x[2 * i + 1]; }
#pragma unroll
        for (int o = 1; o < 32; o <<= 1) s1 += __shfl_xor_sync(~0u, s1, o);
#pragma unroll
        for (int i = 0; i < 6; i++) { x[i] -= s1 * (1.f / C); s2 = fmaf(x[i], x[i], s2); d = fmaf(x[i], k[i], d); }
#pragma unroll
        for (int o = 1; o < 32; o <<= 1) { s2 += __shfl_xor_sync(~0u, s2, o); d += __shfl_xor_sync(~0u, d, o); }
        const float rs = rsq(s2 * (1.f / C) + 1e-5f), nm = fmaxf(m, d * rs), al = ex2(m - nm), p = ex2(d * rs - nm);
        m = nm; l = fmaf(l, al, p);
#pragma unroll
        for (int i = 0; i < 6; i++) a[i] = fmaf(a[i], al, x[i] * (p * rs));
    }
    if (lane == 0) sm[3 * C + warp] = m;
    bar_sync(B_ALL, 384);
    float M = m;
#pragma unroll 1
    for (int w = 0; w < 12; w++) M = fmaxf(M, sm[3 * C + w]);
    const float al = ex2(m - M);
#pragma unroll
    for (int i = 0; i < 6; i++) sm[4 * C + (warp * 7 + i) * 32 + lane] = a[i] * al;
    sm[4 * C + (warp * 7 + 6) * 32 + lane] = l * al;
    bar_sync(B_ALL, 384);
    if (warp == 8) {
        float x[7];
#pragma unroll
        for (int i = 0; i < 7; i++) { x[i] = 0.f; for (int w = 0; w < 12; w++) x[i] += sm[4 * C + (w * 7 + i) * 32 + lane]; }
        uint32_t hi[3], lo[3];
        const float r = 1.f / x[6];
#pragma unroll
        for (int i = 0; i < 3; i++) {
            hi[i] = packh(x[2 * i] * r, x[2 * i + 1] * r);
            const float2 h = unpackh(hi[i]);
            lo[i] = packh(fmaf(x[2 * i], r, -h.x), fmaf(x[2 * i + 1], r, -h.y));
        }
        sts128(bw, hi[0], hi[1], hi[2], lane ? 0u : 0x3C000000u);
        sts128(bw + 4 * 144, lo[0], lo[1], lo[2], 0);
    }
    bar_sync(B_ALL, 384);
}

__device__ __forceinline__ void reducer(const char* __restrict__ f0, const char* __restrict__ f1, const __nv_bfloat16* __restrict__ q, const __nv_bfloat16* __restrict__ wq, const __nv_bfloat16* __restrict__ wk,
                                        Scratch* scr, const __nv_bfloat16* __restrict__ wv, const __nv_bfloat16* __restrict__ wo,
                                        __nv_bfloat16* __restrict__ out, const uint32_t sb, const int GS)
{
    const int warp = threadIdx.x >> 5, lane = threadIdx.x & 31, b = blockIdx.x;
    const int g = lane >> 2, t = lane & 3;
    if (threadIdx.x == 256) TS(0);
    if (b < NSRC && warp < 8) {
        const uint32_t wqs = sb + RD_W, wbar = sb + RD_BAR;
        const int hr = lane >> 4, qt = (lane >> 2) & 3, sub = lane & 3;
        const uint32_t* qp = reinterpret_cast<const uint32_t*>(q + (warp + 8 * hr) * C + 48 * qt + 6 * sub);
        uint32_t qw[6];
#pragma unroll
        for (int j = 0; j < 3; j++) { qw[j] = __ldg(qp + j); qw[3 + j] = __ldg(qp + 12 + j); }
        if (lane == 0) { mbar_init(wbar + warp * 8, 1); asm volatile("fence.mbarrier_init.release.cluster;" ::: "memory"); mbar_expect(wbar + warp * 8, 9216);
            asm volatile("cp.async.bulk.shared::cluster.global.mbarrier::complete_tx::bytes [%0], [%1], 9216, [%2];"
                         ::"r"(wqs + warp * 9232), "l"(wq + 24 * warp * C), "r"(wbar + warp * 8) : "memory");
        }
        __syncwarp();
        if (threadIdx.x == 0) TSP(2, 0);
        float e[12];
#pragma unroll
        for (int j = 0; j < 6; j++) { e[2 * j] = bflo(qw[j]); e[2 * j + 1] = bfhi(qw[j]); }
        float sm = ((e[0] + e[1]) + (e[2] + e[3])) + ((e[4] + e[5]) + (e[6] + e[7])) + ((e[8] + e[9]) + (e[10] + e[11]));
#pragma unroll
        for (int o = 1; o < 16; o <<= 1) sm += __shfl_xor_sync(~0u, sm, o);
        if (threadIdx.x == 0) TSP(5, u(sm));
        float v0 = 0.f, v1 = 0.f;
#pragma unroll
        for (int j = 0; j < 12; j++) e[j] -= sm * (1.f / C);
#pragma unroll
        for (int j = 0; j < 6; j++) { v0 = fmaf(e[j], e[j], v0); v1 = fmaf(e[6 + j], e[6 + j], v1); }
        v0 += v1;
#pragma unroll
        for (int o = 1; o < 16; o <<= 1) v0 += __shfl_xor_sync(~0u, v0, o);
        const float rq = rsq(v0 * (1.f / C) + 1e-5f);
#pragma unroll
        for (int j = 0; j < 6; j++)
            sts32(sb + RD_QN + (3 * sub + (j >> 1)) * 512 + (4 * warp + qt) * 16 + (2 * (j & 1) + hr) * 4, pack2(e[j] * rq, e[6 + j] * rq));
        if (threadIdx.x == 0) TSP(8, 0);
        uint32_t wkf[2][3];
#pragma unroll
        for (int i = 0; i < 2; i++)
#pragma unroll
            for (int j = 0; j < 3; j++) wkf[i][j] = __ldg(reinterpret_cast<const uint32_t*>(wk + (16 * b + 8 * i + g) * C + 24 * warp + 8 * j + 2 * t));
        bar_sync(B_QN, 256);
        float acc[2][3][4];
#pragma unroll
        for (int i = 0; i < 3; i++)
#pragma unroll
            for (int e = 0; e < 4; e++) acc[0][i][e] = acc[1][i][e] = 0.f;
        const uint32_t ba = wqs + (lane & 7) * 9232 + (lane >> 3) * 384 + 48 * warp;
        uint4 a[12];
#pragma unroll
        for (int kk = 0; kk < 12; kk++) a[kk] = lds128(sb + RD_QN + kk * 512 + lane * 16);
        mbar_wait(wbar + (lane & 7) * 8, 0);
        __syncwarp();
        if (threadIdx.x == 0) TSP(4, 0);
#pragma unroll
        for (int kp = 0; kp < 6; kp++)
#pragma unroll
            for (int i = 0; i < 3; i++) {
                uint32_t bb[4];
                ldsm4t(bb, ba + kp * 1536 + i * 16);
                mma(acc[0][i], a[2 * kp].x, a[2 * kp].y, a[2 * kp].z, a[2 * kp].w, bb[0], bb[1]);
                mma(acc[1][i], a[2 * kp + 1].x, a[2 * kp + 1].y, a[2 * kp + 1].z, a[2 * kp + 1].w, bb[2], bb[3]);
            }
        if (threadIdx.x == 0) TSP(7, u(acc[1][2][3]));
        float kq[2][4] = {{0.f, 0.f, 0.f, 0.f}, {0.f, 0.f, 0.f, 0.f}};
#pragma unroll
        for (int j = 0; j < 3; j++) {
            const uint32_t a0 = pack2(acc[0][j][0] + acc[1][j][0], acc[0][j][1] + acc[1][j][1]), a1 = pack2(acc[0][j][2] + acc[1][j][2], acc[0][j][3] + acc[1][j][3]);
            mma8(kq[0], a0, a1, wkf[0][j]);
            mma8(kq[1], a0, a1, wkf[1][j]);
        }
        if (warp < 7) {
            sts128(sb + RD_KQ + warp * 1024 + lane * 16, u(kq[0][0]), u(kq[0][1]), u(kq[0][2]), u(kq[0][3]));
            sts128(sb + RD_KQ + warp * 1024 + 512 + lane * 16, u(kq[1][0]), u(kq[1][1]), u(kq[1][2]), u(kq[1][3]));
            bar_arrive(B_Q, 256);
        } else {
            bar_sync(B_Q, 256);
#pragma unroll
            for (int w = 0; w < 7; w++)
#pragma unroll
                for (int i = 0; i < 2; i++) {
                    const uint4 o = lds128(sb + RD_KQ + w * 1024 + i * 512 + lane * 16);
                    kq[i][0] += f(o.x); kq[i][1] += f(o.y); kq[i][2] += f(o.z); kq[i][3] += f(o.w);
                }
            stg_relaxed(g_qk + b * 32 + lane, ~pack2(kq[0][0] * QSCALE, kq[0][1] * QSCALE), ~pack2(kq[0][2] * QSCALE, kq[0][3] * QSCALE),
                        ~pack2(kq[1][0] * QSCALE, kq[1][1] * QSCALE), ~pack2(kq[1][2] * QSCALE, kq[1][3] * QSCALE));
            if (lane == 0) TS(10);
        }
    } else if (b >= NSRC) {
        if (b == NSRC && warp == 0) stg_relaxed32(g_mmax + lane, 0);
        __nanosleep(2500);
    }
    bar_sync(B_ALL, 384);

#pragma unroll 1
    for (int r = 0; r < 3; r++) {
        uint4 v[8];
#pragma unroll
        for (int k = 0; k < 8; k++) {
            const int idx = (8 * r + k) * 384 + threadIdx.x;
            v[k] = __ldg(reinterpret_cast<const uint4*>(idx < 4608 ? wv : wo - C * C) + idx);
        }
#pragma unroll
        for (int k = 0; k < 8; k++) {
            const int idx = (8 * r + k) * 384 + threadIdx.x, row = idx / 24;
            sts128(sb + RD_W + row * WROW + (idx - 24 * row) * 16, v[k].x, v[k].y, v[k].z, v[k].w);
        }
    }
    if (threadIdx.x < 256) {
        sts128(sb + brow(threadIdx.x >> 3) + (threadIdx.x & 7) * 16, EMPTY, EMPTY, EMPTY, EMPTY);
        stg_relaxed(g_acc + (threadIdx.x >> 7) * ACC + (b >> 2) * 128 + (threadIdx.x & 127), 0, 0, 0, 0);
        __threadfence();
    }
    if (threadIdx.x == 0) sts128(sb + RD_BAD, 0, 0, 0, 0);
    bar_sync(B_ALL, 384);
    uint32_t wa[12][4];
    float ws0 = 0.f, ws1 = 0.f, qv0 = 0.f, qv1 = 0.f;
    __nv_bfloat16* op = out;
    if (warp < 3) {
        const int col = 48 * (b & 3) + 16 * warp;
        float d[24][4];
#pragma unroll
        for (int i = 0; i < 24; i++) d[i][0] = d[i][1] = d[i][2] = d[i][3] = 0.f;
        const int mi = lane >> 3, r = lane & 7;
        const uint32_t aa = sb + RD_W + (C + (mi >> 1) * 8 + r) * WROW + (col + (mi & 1) * 8) * 2;
        const uint32_t ba = sb + RD_W + ((mi >> 1) * 8 + r) * WROW + (mi & 1) * 16;
#pragma unroll 1
        for (int kk = 0; kk < 12; kk++) {
            uint32_t a[4];
            ldsm4t(a, aa + kk * 16 * WROW);
#pragma unroll
            for (int i = 0; i < 12; i++) {
                uint32_t bb[4];
                ldsm4(bb, ba + i * 16 * WROW + kk * 32);
                mma(d[2 * i], a[0], a[1], a[2], a[3], bb[0], bb[1]);
                mma(d[2 * i + 1], a[0], a[1], a[2], a[3], bb[2], bb[3]);
            }
        }
        float c0 = 0.f, c1 = 0.f, m0 = 0.f, m1 = 0.f;
#pragma unroll
        for (int i = 0; i < 24; i++) { c0 += d[i][0] + d[i][1]; c1 += d[i][2] + d[i][3]; }
        c0 += __shfl_xor_sync(~0u, c0, 1); c1 += __shfl_xor_sync(~0u, c1, 1);
        c0 += __shfl_xor_sync(~0u, c0, 2); c1 += __shfl_xor_sync(~0u, c1, 2);
        c0 *= 1.f / C; c1 *= 1.f / C;
#pragma unroll
        for (int i = 0; i < 24; i++) {
            d[i][0] -= c0; d[i][1] -= c0; d[i][2] -= c1; d[i][3] -= c1;
            m0 = fmaxf(m0, fmaxf(fabsf(d[i][0]), fabsf(d[i][1]))); m1 = fmaxf(m1, fmaxf(fabsf(d[i][2]), fabsf(d[i][3])));
        }
        m0 = fmaxf(m0, __shfl_xor_sync(~0u, m0, 1)); m1 = fmaxf(m1, __shfl_xor_sync(~0u, m1, 1));
        m0 = fmaxf(m0, __shfl_xor_sync(~0u, m0, 2)); m1 = fmaxf(m1, __shfl_xor_sync(~0u, m1, 2));
        const uint32_t e0 = min(max(u(m0) >> 23, 12u), 254u), e1 = min(max(u(m1) >> 23, 12u), 254u);
        const float s0 = f((265u - e0) << 23), s1 = f((265u - e1) << 23);
        ws0 = f((e0 - 11u) << 23); ws1 = f((e1 - 11u) << 23);
#pragma unroll
        for (int i = 0; i < 24; i++) {
            const int kk = i % 3 < 2 ? i / 3 : 8 + i / 6, hf = i % 3 < 2 ? i % 3 : (i / 3) & 1;
            wa[kk][2 * hf] = packh(d[i][0] * s0, d[i][1] * s0);
            wa[kk][2 * hf + 1] = packh(d[i][2] * s1, d[i][3] * s1);
        }
        const int o = ((b & 12) + t) * C + col + g;
        qv0 = __bfloat162float(q[o]); qv1 = __bfloat162float(q[o + 8]);
        op = out + o;
        asm volatile("" : "+l"(op));
        if (threadIdx.x == 0) TSE(6);
    } else if (warp == 3) {
        if (lane == 0) {
            uint32_t m;
            for (int it = 0;; it++) {
                const int left = NT - 2 * NST * GS - (int)ldg_relaxed32(g_ctr);
                m = ldg_relaxed32(g_mmax + b);
                if (left <= REFT && m) break;
                if (left <= 0) { m = 0x80000000u; break; }
                if (it > SPIN_LIMIT) __trap();
                __nanosleep(300);
            }
            asm volatile("st.release.gpu.global.u32 [%0], %1;" ::"l"(g_mref + b), "r"(~u(f(m >> 31 ? m ^ 0x80000000u : ~m) + 8.f)) : "memory");
            TSE(7);
        }
        __syncwarp();
    } else {
        const int pr = warp & 1;
        const uint4* const pa = g_acc + ((b >> 2) * 2 + pr) * 64 + lane;
        const uint32_t bw = opaque(sb + brow(16 * pr + 8 * ((lane >> 2) & 1) + t) + (lane >> 3) * 16);
        const uint32_t n0 = packh((float)((GS + 1) >> 1), 0.f), n1 = packh((float)(GS >> 1), 0.f), nstart = packh((float)POLLN, 0.f);
        for (int it = 0; (ldg_relaxed32(reinterpret_cast<const uint32_t*>(pa - lane) + 3) & 0xFFFFu) < nstart; it++)
            if (it > SPIN_LIMIT) __trap();
        for (const unsigned c = clock(); clock() - c < ((warp - 4) >> 1) * PGAP;) {}
        uint4 a0, a1, b0, b1;
        for (int it = 0;; it++) {
            a0 = ldg_relaxed(pa); a1 = ldg_relaxed(pa + ACC); b0 = ldg_relaxed(pa + 32); b1 = ldg_relaxed(pa + ACC + 32);
            if (__all_sync(~0u, (((a0.w ^ n0) | (b0.w ^ n0) | (a1.w ^ n1) | (b1.w ^ n1)) & 0xFFFFu) == 0)) break;
            if (it > SPIN_LIMIT) __trap();
        }
        sts128(bw, a0.x, a0.y, a0.z, a0.w);
        sts128(bw + 4 * 144, a1.x, a1.y, a1.z, a1.w);
        sts128(bw + 64, b0.x, b0.y, b0.z, b0.w);
        sts128(bw + 4 * 144 + 64, b1.x, b1.y, b1.z, b1.w);
        if (warp == 4) {
            if (b < NSRC) g_qk[b * 32 + lane] = make_uint4(0, 0, 0, 0);
            if (lane == 0) { g_mref[b] = 0; if (b == NSRC) g_ctr[0] = 0; }
        }
    }
    const uint32_t br = opaque(sb + brow(lane));
#pragma unroll 1
    for (uint32_t pass = 0;; pass = 1) {
        if (warp < 3) {
            uint4 x[8];
            float o[4][4];
            for (int it = 0;; it++) {
                for (;; it++) {
                    x[7] = lds128v(br + 7 * 16);
                    if (!__any_sync(~0u, x[7].w & 0x8000u)) break;
                    if (it > 64 * SPIN_LIMIT) __trap();
                }
                if (threadIdx.x == 0) TSX(8, 0);
#pragma unroll
                for (int j = 0; j < 7; j++) x[j] = lds128v(br + j * 16);
#pragma unroll
                for (int j = 0; j < 4; j++) o[j][0] = o[j][1] = o[j][2] = o[j][3] = 0.f;
#pragma unroll
                for (int i = 0; i < 4; i++) {
                    mmah(o[3], 0x3C000000u, 0x3C000000u, 0x3C000000u, 0x3C000000u, x[2 * i].w, x[2 * i + 1].w);
                    mmah(o[0], wa[2 * i][0], wa[2 * i][1], wa[2 * i][2], wa[2 * i][3], x[2 * i].x, x[2 * i].y);
                    mmah(o[1], wa[2 * i + 1][0], wa[2 * i + 1][1], wa[2 * i + 1][2], wa[2 * i + 1][3], x[2 * i + 1].x, x[2 * i + 1].y);
                    mmah(o[2], wa[8 + i][0], wa[8 + i][1], wa[8 + i][2], wa[8 + i][3], x[2 * i].z, x[2 * i + 1].z);
                }
                if (!__any_sync(~0u, ((x[0].w | x[1].w | x[2].w) | (x[3].w | x[4].w | x[5].w) | x[6].w) & 0x8000u)) break;
            }
            const float L = o[3][0] + o[3][1], r = rcp(L);
            const float y0 = fmaf(((o[0][0] + o[0][1]) + (o[1][0] + o[1][1])) + (o[2][0] + o[2][1]), r * ws0, qv0);
            const float y1 = fmaf(((o[0][2] + o[0][3]) + (o[1][2] + o[1][3])) + (o[2][2] + o[2][3]), r * ws1, qv1);
            op[0] = __float2bfloat16(y0);
            op[8] = __float2bfloat16(y1);
            if (threadIdx.x == 0) TSD(11, u(y0));
            if (!(L >= 0.001953125f && L <= 2048.f && fabsf(y0) + fabsf(y1) < INFINITY)) sts32(sb + RD_BAD + t * 4, 1);
        }
        bar_sync(B_ALL, 384);
        if (pass) break;
        const uint4 bad = lds128(sb + RD_BAD);
        if (__builtin_expect((bad.x | bad.y | bad.z | bad.w) == 0, 1)) break;
        const uint32_t keep = sb + RD_W + 32768 + warp * 6144 + lane * 16;
        if (warp < 3)
#pragma unroll
            for (int kk = 0; kk < 12; kk++) sts128(keep + kk * 512, wa[kk][0], wa[kk][1], wa[kk][2], wa[kk][3]);
#pragma unroll 1
        for (int r = 0; r < 4; r++)
            if (lds32(sb + RD_BAD + r * 4)) slow_row(f0, f1, q, wq, wk, sb, (b & 12) + r);
        if (warp < 3)
#pragma unroll
            for (int kk = 0; kk < 12; kk++) {
                const uint4 v = lds128(keep + kk * 512);
                wa[kk][0] = v.x; wa[kk][1] = v.y; wa[kk][2] = v.z; wa[kk][3] = v.w;
            }
    }
}

__global__ void __launch_bounds__(NTHREADS, 1)
attn_main(const char* __restrict__ f0, const char* __restrict__ f1,
          const __nv_bfloat16* __restrict__ q, const __nv_bfloat16* __restrict__ wq, const __nv_bfloat16* __restrict__ wk, Scratch* scr,
          const __nv_bfloat16* __restrict__ wv, const __nv_bfloat16* __restrict__ wo, __nv_bfloat16* __restrict__ out,
          const __grid_constant__ CUtensorMap m0, const __grid_constant__ CUtensorMap m1)
{
    extern __shared__ char smem_raw[];
    const uint32_t sb = (s2u(smem_raw) + 1023u) & ~1023u;
    const int G = gridDim.x - NRD;
    if (blockIdx.x < NRD) { reducer(f0, f1, q, wq, wk, scr, wv, wo, out, sb, G); return; }
    const int b = blockIdx.x - NRD;
    const int warp = threadIdx.x >> 5, lane = threadIdx.x & 31;
    const int g = lane >> 2, t = lane & 3;

    if (warp >= 8) {
        if (warp < 10) {
            const int p = warp - 8;
            if (lane == 0) {
                if (p == 0) TS(0);
                asm volatile("prefetch.tensormap [%0];" ::"l"(p ? &m1 : &m0) : "memory");
            }
            if (lane < NS / 2) {
                const int s = 2 * lane + p;
                mbar_init(sb + SM_BAR + s * 8, 1); mbar_init(sb + SM_BAR + (NS + s) * 8, 1);
            }
            if (p == 0 && lane == 31) mbar_init(sb + SM_REF, 1);
            asm volatile("fence.mbarrier_init.release.cluster;" ::: "memory");
            __syncwarp();
            bar_arrive(B_QK, 384);
            if (lane == 0) {
                uint64_t pol; asm volatile("createpolicy.fractional.L2::evict_first.b64 %0, 1.0;" : "=l"(pol));
                int s = p; uint32_t ph = 1;
                int sa = p, na = 0; uint32_t pa = 0;
                int tl = b + p * G;
                bool late = false;
                for (int n = 0;; n++) {
                    int nxt = tl + 2 * G;
                    if (n >= NST - 1) nxt = grab_tile(g_ctr) + 2 * NST * G;
                    const int d = n < NRAMP ? D0 : (tl >= NT - TAILT ? D2 : D1);
                    while (n - na >= d) {
                        mbar_wait(sb + SM_BAR + sa * 8, pa);
                        if (na < NS / 2) TR(1, 2 * na + p);
                        na++; sa += 2;
                        if (sa >= NS) { sa -= NS; pa ^= 1; }
                    }
                    mbar_wait(sb + SM_BAR + (NS + s) * 8, ph);
                    const bool last = nxt >= NT;
                    uint32_t flag = last;
                    if (!late && nxt >= NT - MAXT - 16 * b) { late = true; flag |= 2; }
                    if (last) mbar_wait(sb + SM_REF, 0);
                    sts32(sb + SM_FLAG + s * 4, flag);
                    issue_tile(&m0, &m1, sb, s, tl, pol);
                    TR(0, 2 * n + p);
                    if (last) break;
                    s += 2;
                    if (s >= NS) { s -= NS; ph ^= 1; }
                    tl = nxt;
                }
                if (p) TSE(5);
            }
            return;
        }
        const int h = threadIdx.x - 320;
        uint4 v[6];
        for (int it = 0;; it++) {
            bool miss = false;
#pragma unroll
            for (int k = 0; k < 6; k++) v[k] = ldg_relaxed(g_qk + k * 64 + h);
#pragma unroll
            for (int k = 0; k < 6; k++) miss |= has(v[k], 0);
            if (!miss) break;
            if (it > SPIN_LIMIT) __trap();
            if (it == 0) __nanosleep(QSLEEP);
        }
#pragma unroll
        for (int k = 0; k < 6; k++) sts128(sb + SM_QK + (k * 64 + h) * 16, ~v[k].x, ~v[k].y, ~v[k].z, ~v[k].w);
        __syncwarp();
        bar_sync(B_QK, 384);
        if (warp == 11) return;
        uint32_t r = 1;
        for (int it = 0;; it++) {
            __nanosleep(500);
            if (lane < NQ) asm volatile("ld.acquire.gpu.global.u32 %0, [%1];" : "=r"(r) : "l"(g_mref + lane) : "memory");
            if (__all_sync(~0u, r != 0)) break;
            if (it > SPIN_LIMIT) __trap();
        }
        if (lane < NQ) sts32(sb + SM_M + lane * 4, ~r);
        __syncwarp();
        if (lane == 0) { mbar_arrive(sb + SM_REF); TSE(7); }
        return;
    }

    const int grp = warp >> 2, cw = warp & 3;
    if (lane == 0) {
        const char* a; int sz;
        if (warp >= 6) {
            sz = C * C * 2 / WSL; a = (const char*)(warp == 6 ? wq : wk) + (b % WSL) * sz;
        } else {
            const int tl = b + (warp / 3) * G, which = warp % 3;
            const int par = tl * TP, y = par >> 8, x = par & 255;
            a = which < 2 ? f0 + ((size_t)(2 * y + which) * W0 + 2 * x) * (C * 2) : f1 + ((size_t)y * W1 + x) * (C * 2);
            sz = which < 2 ? TP * 2 * C * 2 : TP * C * 2;
        }
        if (warp >= 6 || warp < 3 * NPRE) asm volatile("cp.async.bulk.prefetch.L2.global [%0], %1;" ::"l"(a), "r"(sz) : "memory");
    }

    const int xp = lane & 7, mi = lane >> 3;
    const uint32_t offS = opaque(xp * 128 + ((mi ^ xp) << 4));
    uint32_t offT[6], offT1[2];
#pragma unroll
    for (int i = 0; i < 6; i++) {
        const int J = 6 * cw + (i + 3 * grp) % 6;
        offT[i] = opaque(mi * 3072 + (J >> 3) * 1024 + xp * 128 + (((J & 7) ^ xp) << 4));
    }
    {
        const int J = 6 * cw + (mi + 3 * grp) % 6, J2 = 6 * cw + (4 + (mi & 1) + 3 * grp) % 6;
        offT1[0] = opaque(12288 + (J >> 3) * 1024 + xp * 128 + (((J & 7) ^ xp) << 4));
        offT1[1] = opaque(12288 + (J2 >> 3) * 1024 + xp * 128 + (((J2 & 7) ^ xp) << 4));
    }
    const uint32_t mxw = opaque(sb + SM_MX + grp * 256 + ((g + 8 * t) * 4 + cw) * 4);
    const uint32_t offS0 = opaque(offS + cw * 3072);
    const int shl = opaque(9 * t);
    const uint32_t mxr = sb + SM_MX + grp * 256 + g * 16;
    const uint32_t pw = sb + SM_P + grp * 1024 + (cw >> 1) * 512 + lane * 16 + (cw & 1) * 8;
    const uint32_t pr = sb + SM_P + grp * 1024 + lane * 16;
    const uint32_t muw = sb + SM_MU + grp * 64 + t * 16 + cw * 4, mur = sb + SM_MU + grp * 64 + t * 16;
    const int barid = B_GRP + grp;
    const bool elected = (threadIdx.x & 127) == 96;

    uint32_t qa[48];
    float r_lo, r_hi;
    bar_sync(B_QK, 384);
    {
        float rr[2][4] = {{0.f, 0.f, 0.f, 0.f}, {0.f, 0.f, 0.f, 0.f}};
#pragma unroll
        for (int kk = 0; kk < 12; kk++) {
            const uint4 v = lds128(sb + SM_QK + kk * 512 + lane * 16);
            qa[4 * kk] = v.x; qa[4 * kk + 1] = v.y; qa[4 * kk + 2] = v.z; qa[4 * kk + 3] = v.w;
            mma(rr[kk & 1], v.x, v.y, v.z, v.w, ONES, ONES);
        }
        r_lo = rr[0][0] + rr[1][0]; r_hi = rr[0][2] + rr[1][2];
    }
    if (threadIdx.x == 0) TS(1);

    float acc[6][4];
#pragma unroll
    for (int i = 0; i < 6; i++) acc[i][0] = acc[i][1] = acc[i][2] = acc[i][3] = 0.f;
    float m_lo = -INFINITY, m_hi = -INFINITY, l_lo = 0.f, l_hi = 0.f;
    float cm[4] = {0.f, 0.f, 0.f, 0.f};
    int s = grp; uint32_t ph = 0;
    while (true) {
        mbar_wait(sb + SM_BAR + s * 8, ph);
        PH(0, 0);
        const uint32_t stop = lds32(sb + SM_FLAG + s * 4);
        const uint32_t st = sb + SM_STAGES + s * STAGE;
        float sc[2][4], gr[2][4];
#pragma unroll
        for (int e = 0; e < 4; e++) sc[0][e] = sc[1][e] = gr[0][e] = gr[1][e] = 0.f;
        const uint32_t a0e = st + offS0, a1e = st + 12288 + offS;
#pragma unroll
        for (int qq = 0; qq < 6; qq++) {
            uint32_t x[4], y[4];
            ldsm4(x, (a0e ^ ((qq & 1) << 6)) + (qq >> 1) * 1024);
            ldsm4(y, (a1e ^ ((qq & 1) << 6)) + (qq >> 1) * 1024);
#pragma unroll
            for (int e = 0; e < 4; e++) x[e] = hadd2(x[e], y[e]);
            mma(gr[0], x[0], ONES, x[1], ONES, x[0], x[1]);
            mma(gr[1], x[2], ONES, x[3], ONES, x[2], x[3]);
            mma(sc[0], qa[8 * qq], qa[8 * qq + 1], qa[8 * qq + 2], qa[8 * qq + 3], x[0], x[1]);
            mma(sc[1], qa[8 * qq + 4], qa[8 * qq + 5], qa[8 * qq + 6], qa[8 * qq + 7], x[2], x[3]);
        }
        uint32_t xt[6][4], yt[6];
        ldsm4t(yt, st + offT1[0]);
        ldsm2t(yt + 4, st + offT1[1]);
#pragma unroll
        for (int i = 0; i < 6; i++) ldsm4t(xt[i], st + offT[i]);

        const float ss0 = __shfl_sync(~0u, gr[0][0] + gr[1][0], shl);
        const float ss1 = __shfl_sync(~0u, gr[0][1] + gr[1][1], shl + 4);
        const float mu0 = (gr[0][2] + gr[1][2]) * (1.f / C), mu1 = (gr[0][3] + gr[1][3]) * (1.f / C);
        const float rs0 = rsq(fmaxf(fmaf(-mu0, mu0, ss0 * (1.f / C)), 0.f) + 1e-5f);
        const float rs1 = rsq(fmaxf(fmaf(-mu1, mu1, ss1 * (1.f / C)), 0.f) + 1e-5f);
        const float s0 = fmaf(-mu0, r_lo, sc[0][0] + sc[1][0]) * rs0;
        const float s1 = fmaf(-mu1, r_lo, sc[0][1] + sc[1][1]) * rs1;
        const float s2 = fmaf(-mu0, r_hi, sc[0][2] + sc[1][2]) * rs0;
        const float s3 = fmaf(-mu1, r_hi, sc[0][3] + sc[1][3]) * rs1;
        PH(1, u(s0 + s2));
        const uint32_t mup = pack2(mu0, mu1);
        float nl, nh;
        if (!(stop & 1)) {
            float xl = fmaxf(s0, s1), xh = fmaxf(s2, s3);
            xl = fmaxf(xl, __shfl_xor_sync(~0u, xl, 1)); xh = fmaxf(xh, __shfl_xor_sync(~0u, xh, 1));
            xl = fmaxf(xl, __shfl_xor_sync(~0u, xl, 2)); xh = fmaxf(xh, __shfl_xor_sync(~0u, xh, 2));
            if (t < 2) sts32(mxw, u(t ? xh : xl));
#pragma unroll
            for (int i = 0; i < 6; i++)
#pragma unroll
                for (int e = 0; e < 4; e++) xt[i][e] = hadd2v(xt[i][e], yt[i]);
            bar_sync(barid, 128);
            PH(2, 0);
            const uint4 ml4 = lds128(mxr), mh4 = lds128(mxr + 128);
            if (elected) mbar_arrive(sb + SM_BAR + (NS + s) * 8);
            nl = fmaxf(fmaxf(fmaxf(f(ml4.x), f(ml4.y)), fmaxf(f(ml4.z), f(ml4.w))), m_lo);
            nh = fmaxf(fmaxf(fmaxf(f(mh4.x), f(mh4.y)), fmaxf(f(mh4.z), f(mh4.w))), m_hi);
        } else {
            nl = f(lds32(sb + SM_M + g * 4)); nh = f(lds32(sb + SM_M + 32 + g * 4));
#pragma unroll
            for (int i = 0; i < 6; i++)
#pragma unroll
                for (int e = 0; e < 4; e++) xt[i][e] = hadd2v(xt[i][e], yt[i]);
        }
        const float p0 = ex2(s0 - nl), p1 = ex2(s1 - nl), p2 = ex2(s2 - nh), p3 = ex2(s3 - nh);
        sts64(pw + stop * 2048, pack2(p0 * rs0, p1 * rs1), pack2(p2 * rs0, p3 * rs1));
        if (lane < 4) sts32(muw + stop * 128, mup);
        const float al = ex2(m_lo - nl), ah = ex2(m_hi - nh);
        m_lo = nl; m_hi = nh;
        l_lo = fmaf(l_lo, al, p0 + p1); l_hi = fmaf(l_hi, ah, p2 + p3);
#pragma unroll
        for (int i = 0; i < 6; i++) { acc[i][0] *= al; acc[i][1] *= al; acc[i][2] *= ah; acc[i][3] *= ah; }
        cm[0] *= al; cm[2] *= ah;
        bar_sync(barid, 128);
        PH(3, 0);
        const uint4 pa = lds128(pr + stop * 2048), pb = lds128(pr + stop * 2048 + 512), mv = lds128(mur + stop * 128);
#pragma unroll
        for (int i = 3; i < 6; i++) mma(acc[i], pa.x, pa.y, pa.z, pa.w, xt[i][0], xt[i][1]);
        mma(cm, pa.x, pa.y, pa.z, pa.w, mv.x, mv.y);
#pragma unroll
        for (int i = 3; i < 6; i++) mma(acc[i], pb.x, pb.y, pb.z, pb.w, xt[i][2], xt[i][3]);
        mma(cm, pb.x, pb.y, pb.z, pb.w, mv.z, mv.w);
#pragma unroll
        for (int i = 0; i < 3; i++) mma(acc[i], pa.x, pa.y, pa.z, pa.w, xt[i][0], xt[i][1]);
#pragma unroll
        for (int i = 0; i < 3; i++) mma(acc[i], pb.x, pb.y, pb.z, pb.w, xt[i][2], xt[i][3]);
        PH(4, u(acc[5][0]));
        if (stop) {
            if (stop & 1) break;
            if (cw == 0) {
                float a = l_lo + __shfl_xor_sync(~0u, l_lo, 1), c = l_hi + __shfl_xor_sync(~0u, l_hi, 1);
                a += __shfl_xor_sync(~0u, a, 2); c += __shfl_xor_sync(~0u, c, 2);
                const uint32_t m = u((t ? m_hi : m_lo) + lg2(fmaxf(t ? c : a, 1.f)));
                if (t < 2) asm volatile("red.relaxed.gpu.global.max.u32 [%0], %1;" ::"l"(g_mmax + g + 8 * t), "r"(m >> 31 ? ~m : m | 0x80000000u) : "memory");
            }
        }
        s += 2;
        if (s >= NS) { s -= NS; ph ^= 1; }
    }
    if (threadIdx.x == grp * 128) TSE(2 + grp);
    if (threadIdx.x == grp * 128 + 96) TSX(2 + grp, u(acc[5][0]));

    uint4* const dst = g_acc + (b & 1) * ACC + ((g >> 1) * 8 + 2 * cw + grp) * 8 + (lane & 7);
    const uint32_t xw = opaque(sb + SM_STAGES + grp * STAGE + cw * 1536 + lane * 16), xr = opaque(sb + SM_STAGES + (grp ^ 1) * STAGE + cw * 1536 + lane * 16);
    asm volatile("" ::"l"(dst));
#pragma unroll
    for (int i = 0; i < 3; i++)
        sts128(xw + i * 512, u(acc[3 + i][0] - cm[0]), u(acc[3 + i][1] - cm[0]), u(acc[3 + i][2] - cm[2]), u(acc[3 + i][3] - cm[2]));
#pragma unroll
    for (int i = 0; i < 3; i++) { acc[i][0] -= cm[0]; acc[i][1] -= cm[0]; acc[i][2] -= cm[2]; acc[i][3] -= cm[2]; }
    const uint32_t w_lo = packh(1.f, l_lo), w_hi = packh(1.f, l_hi);
    bar_sync(B_MERGE, 256);
    if (threadIdx.x == 224) TSX(4, 0);
    uint4 o[3];
#pragma unroll
    for (int i = 0; i < 3; i++) o[i] = lds128(xr + i * 512);
    red8h(dst, packh(acc[0][0] + f(o[0].x), acc[0][1] + f(o[0].y)), packh(acc[1][0] + f(o[1].x), acc[1][1] + f(o[1].y)), packh(acc[2][0] + f(o[2].x), acc[2][1] + f(o[2].y)), w_lo);
    red8h(dst + 256, packh(acc[0][2] + f(o[0].z), acc[0][3] + f(o[0].w)), packh(acc[1][2] + f(o[1].z), acc[1][3] + f(o[1].w)), packh(acc[2][2] + f(o[2].z), acc[2][3] + f(o[2].w)), w_hi);
    if (threadIdx.x == 0) TSE(4);
    if (threadIdx.x == 224) TSX(9, 0);
}

typedef CUresult (*EncodeFn)(CUtensorMap*, CUtensorMapDataType, cuuint32_t, void*, const cuuint64_t*, const cuuint64_t*,
                             const cuuint32_t*, const cuuint32_t*, CUtensorMapInterleave, CUtensorMapSwizzle,
                             CUtensorMapL2promotion, CUtensorMapFloatOOBfill);

}

extern "C" void kernel_launch(void* const* d_in, const int* in_sizes, int n_in, void* d_out, int out_size) {
    const __nv_bfloat16* q = (const __nv_bfloat16*)d_in[0];
    char* f0 = (char*)d_in[1];
    char* f1 = (char*)d_in[2];
    const __nv_bfloat16* wq = (const __nv_bfloat16*)d_in[3];
    const __nv_bfloat16* wk = (const __nv_bfloat16*)d_in[4];
    const __nv_bfloat16* wv = (const __nv_bfloat16*)d_in[5];
    const __nv_bfloat16* wo = (const __nv_bfloat16*)d_in[6];

    static EncodeFn enc = nullptr;
    static int grid = 0;
    static Scratch* scr = nullptr;
    if (!enc) {
        void* fn = nullptr; cudaDriverEntryPointQueryResult qr;
        cudaGetDriverEntryPoint("cuTensorMapEncodeTiled", &fn, cudaEnableDefault, &qr);
        enc = (EncodeFn)fn;
        cudaGetSymbolAddress((void**)&scr, g_scratch);
        int dev = 0, sms = 0;
        cudaGetDevice(&dev);
        cudaDeviceGetAttribute(&sms, cudaDevAttrMultiProcessorCount, dev);
        grid = sms < MAXG ? sms : MAXG;
        cudaFuncSetAttribute(attn_main, cudaFuncAttributeMaxDynamicSharedMemorySize, SMEM_BYTES);
    }
    CUtensorMap m0, m1;
    {
        cuuint64_t dims[5] = {64, W1, 3, 2, W0};
        cuuint64_t str[4] = {2 * C * 2, 128, C * 2, (cuuint64_t)W0 * C * 2};
        cuuint32_t box[5] = {64, TP, 3, 2, 2}, es[5] = {1, 1, 1, 1, 1};
        enc(&m0, CU_TENSOR_MAP_DATA_TYPE_BFLOAT16, 5, f0, dims, str, box, es, CU_TENSOR_MAP_INTERLEAVE_NONE,
            CU_TENSOR_MAP_SWIZZLE_128B, CU_TENSOR_MAP_L2_PROMOTION_NONE, CU_TENSOR_MAP_FLOAT_OOB_FILL_NONE);
    }
    {
        cuuint64_t dims[4] = {64, W1, 3, W1};
        cuuint64_t str[3] = {C * 2, 128, (cuuint64_t)W1 * C * 2};
        cuuint32_t box[4] = {64, TP, 3, 1}, es[4] = {1, 1, 1, 1};
        enc(&m1, CU_TENSOR_MAP_DATA_TYPE_BFLOAT16, 4, f1, dims, str, box, es, CU_TENSOR_MAP_INTERLEAVE_NONE,
            CU_TENSOR_MAP_SWIZZLE_128B, CU_TENSOR_MAP_L2_PROMOTION_NONE, CU_TENSOR_MAP_FLOAT_OOB_FILL_NONE);
    }
    attn_main<<<grid, NTHREADS, SMEM_BYTES, cudaStreamPerThread>>>(f0, f1, q, wq, wk, scr, wv, wo, (__nv_bfloat16*)d_out, m0, m1);
}
```

```cpp
#include <cuda_runtime.h>
#include <cuda_bf16.h>
#include <cuda.h>
#include <stdint.h>

namespace {

constexpr int C = 192;
constexpr int NQ = 16;
constexpr int W0 = 512;
constexpr int W1 = 256;
constexpr int TP = 8;
constexpr int NT = W1 * W1 / TP;
constexpr int STAGE = TP * 5 * C * 2;
#define NS 14
#define D0 1
#define D1 4
#define D2 2
#define NRAMP 3
#define TAILT 1000
#define QSLEEP 700
#define WSL 24
#define MAXT 3000
#define REFT 1800
#define POLLN 1
#define PGAP 110
#define LAZY 12.f
#define NST 2
#define NPRE 2
static_assert(NST > D0, "the first dynamic tile index must not delay the start");
constexpr int NTHREADS = 384;
constexpr int MAXG = 132;
constexpr int NRD = NQ;
constexpr int ACC = NQ * 32;
constexpr int NSRC = 12;
constexpr int SPIN_LIMIT = 1 << 22;
constexpr uint32_t EMPTY = 0xFFFFFFFFu;

constexpr int SM_STAGES = 0;
constexpr int SM_P = NS * STAGE;
constexpr int PBUF = 1088;
constexpr int SM_QK = SM_P + 4 * PBUF;
constexpr int SM_MX = SM_QK + 6144;
constexpr int SM_M = SM_MX + 512;
constexpr int SM_BAR = SM_M + 64;
constexpr int SM_REF = SM_BAR + 16 * NS;
constexpr int SM_FLAG = SM_REF + 8;
constexpr int SM_TOTAL = SM_FLAG + 4 * NS;
constexpr int SMEM_BYTES = SM_TOTAL + 1024;
static_assert(SMEM_BYTES <= 232448, "smem");
constexpr int WROW = 400;
constexpr int RD_W = 0;
constexpr int RD_QN = 2 * C * WROW;
constexpr int RD_KQ = RD_QN + 6144;
constexpr int RD_B = RD_KQ + 7168;
constexpr int RD_BAD = RD_B + 32 * 144 + 256;
constexpr int RD_BAR = RD_BAD + 16;
static_assert(RD_BAR + 64 <= SM_TOTAL, "smem");

struct Scratch {
    uint4 acc[2 * ACC];
    uint4 qk[NSRC * 32];
    unsigned ctr[32];
    unsigned mmax[32];
    unsigned mref[32];
};
__device__ __align__(128) Scratch g_scratch;
#define g_acc (scr->acc)
#define g_qk (scr->qk)
#define g_ctr (scr->ctr)
#define g_mmax (scr->mmax)
#define g_mref (scr->mref)
#define g_ts (scr->ts)
#define g_tr (scr->tr)
#define TR(k, i) do {} while (0)
#define TS(i) do {} while (0)
#define TSD(i, dep) do {} while (0)
#define TSX(i, dep) do {} while (0)
#define TSP(i, dep) do {} while (0)
#define TSE(i) TS(i)
#define CK_(i, dep) do {} while (0)
#define PH(i, dep) do {} while (0)

__device__ __forceinline__ uint32_t s2u(const void* p) { return (uint32_t)__cvta_generic_to_shared(p); }
__device__ __forceinline__ void mbar_init(uint32_t a, int c) { asm volatile("mbarrier.init.shared::cta.b64 [%0], %1;" ::"r"(a), "r"(c) : "memory"); }
__device__ __forceinline__ void mbar_expect(uint32_t a, uint32_t b) { asm volatile("mbarrier.arrive.expect_tx.shared::cta.b64 _, [%0], %1;" ::"r"(a), "r"(b) : "memory"); }
__device__ __forceinline__ void mbar_arrive(uint32_t a) { asm volatile("mbarrier.arrive.shared::cta.b64 _, [%0];" ::"r"(a) : "memory"); }
__device__ __forceinline__ void mbar_wait(uint32_t a, uint32_t ph) {
    uint32_t ok; int it = 0;
    do {
        asm volatile("{.reg .pred p; mbarrier.try_wait.parity.shared::cta.b64 p, [%1], %2; selp.u32 %0,1,0,p;}" : "=r"(ok) : "r"(a), "r"(ph) : "memory");
        if (++it > SPIN_LIMIT) __trap();
    } while (!ok);
}
__device__ __forceinline__ void bar_sync(int id, int n) { asm volatile("bar.sync %0, %1;" ::"r"(id), "r"(n) : "memory"); }
__device__ __forceinline__ bool bar_any(int id, int n, bool c) {
    uint32_t r;
    asm volatile("{.reg .pred p, q; setp.ne.u32 q, %3, 0; bar.red.or.pred p, %1, %2, q; selp.u32 %0, 1, 0, p;}" : "=r"(r) : "r"(id), "r"(n), "r"((uint32_t)c) : "memory");
    return r;
}
__device__ __forceinline__ void bar_arrive(int id, int n) { asm volatile("bar.arrive %0, %1;" ::"r"(id), "r"(n) : "memory"); }
__device__ __forceinline__ void ldsm4(uint32_t* r, uint32_t a) {
    asm volatile("ldmatrix.sync.aligned.m8n8.x4.shared.b16 {%0,%1,%2,%3}, [%4];" : "=r"(r[0]), "=r"(r[1]), "=r"(r[2]), "=r"(r[3]) : "r"(a) : "memory");
}
__device__ __forceinline__ void ldsm4t(uint32_t* r, uint32_t a) {
    asm volatile("ldmatrix.sync.aligned.m8n8.x4.trans.shared.b16 {%0,%1,%2,%3}, [%4];" : "=r"(r[0]), "=r"(r[1]), "=r"(r[2]), "=r"(r[3]) : "r"(a) : "memory");
}
__device__ __forceinline__ void ldsm2t(uint32_t* r, uint32_t a) {
    asm volatile("ldmatrix.sync.aligned.m8n8.x2.trans.shared.b16 {%0,%1}, [%2];" : "=r"(r[0]), "=r"(r[1]) : "r"(a) : "memory");
}
__device__ __forceinline__ void mma(float* d, uint32_t a0, uint32_t a1, uint32_t a2, uint32_t a3, uint32_t b0, uint32_t b1) {
    asm("mma.sync.aligned.m16n8k16.row.col.f32.bf16.bf16.f32 {%0,%1,%2,%3}, {%4,%5,%6,%7}, {%8,%9}, {%0,%1,%2,%3};"
        : "+f"(d[0]), "+f"(d[1]), "+f"(d[2]), "+f"(d[3]) : "r"(a0), "r"(a1), "r"(a2), "r"(a3), "r"(b0), "r"(b1));
}
__device__ __forceinline__ void mmah(float* d, uint32_t a0, uint32_t a1, uint32_t a2, uint32_t a3, uint32_t b0, uint32_t b1) {
    asm("mma.sync.aligned.m16n8k16.row.col.f32.f16.f16.f32 {%0,%1,%2,%3}, {%4,%5,%6,%7}, {%8,%9}, {%0,%1,%2,%3};"
        : "+f"(d[0]), "+f"(d[1]), "+f"(d[2]), "+f"(d[3]) : "r"(a0), "r"(a1), "r"(a2), "r"(a3), "r"(b0), "r"(b1));
}
__device__ __forceinline__ void mma8(float* d, uint32_t a0, uint32_t a1, uint32_t b0) {
    asm("mma.sync.aligned.m16n8k8.row.col.f32.bf16.bf16.f32 {%0,%1,%2,%3}, {%4,%5}, {%6}, {%0,%1,%2,%3};"
        : "+f"(d[0]), "+f"(d[1]), "+f"(d[2]), "+f"(d[3]) : "r"(a0), "r"(a1), "r"(b0));
}
__device__ __forceinline__ uint32_t hadd2(uint32_t a, uint32_t b) {
    uint32_t r; asm("add.rn.bf16x2 %0, %1, %2;" : "=r"(r) : "r"(a), "r"(b)); return r;
}
__device__ __forceinline__ uint32_t pack2(float lo, float hi) {
    uint32_t r; asm("cvt.rn.bf16x2.f32 %0, %1, %2;" : "=r"(r) : "f"(hi), "f"(lo)); return r;
}
__device__ __forceinline__ uint32_t packh(float lo, float hi) {
    uint32_t r; asm("cvt.rn.f16x2.f32 %0, %1, %2;" : "=r"(r) : "f"(hi), "f"(lo)); return r;
}
__device__ __forceinline__ float2 unpackh(uint32_t v) {
    float2 r; asm("{.reg .b16 l, h; mov.b32 {l, h}, %2; cvt.f32.f16 %0, l; cvt.f32.f16 %1, h;}" : "=f"(r.x), "=f"(r.y) : "r"(v)); return r;
}
__device__ __forceinline__ float bflo(uint32_t v) { return __uint_as_float(v << 16); }
__device__ __forceinline__ float bfhi(uint32_t v) { return __uint_as_float(v & 0xffff0000u); }
__device__ __forceinline__ float ex2(float x) { float r; asm("ex2.approx.ftz.f32 %0, %1;" : "=f"(r) : "f"(x)); return r; }
__device__ __forceinline__ void sts128(uint32_t a, uint32_t x, uint32_t y, uint32_t z, uint32_t w) {
    asm volatile("st.shared.v4.b32 [%0], {%1,%2,%3,%4};" ::"r"(a), "r"(x), "r"(y), "r"(z), "r"(w) : "memory");
}
__device__ __forceinline__ void sts64(uint32_t a, uint32_t x, uint32_t y) {
    asm volatile("st.shared.v2.b32 [%0], {%1,%2};" ::"r"(a), "r"(x), "r"(y) : "memory");
}
__device__ __forceinline__ void sts32(uint32_t a, uint32_t x) { asm volatile("st.shared.b32 [%0], %1;" ::"r"(a), "r"(x) : "memory"); }
__device__ __forceinline__ uint4 lds128(uint32_t a) {
    uint4 v; asm volatile("ld.shared.v4.b32 {%0,%1,%2,%3}, [%4];" : "=r"(v.x), "=r"(v.y), "=r"(v.z), "=r"(v.w) : "r"(a) : "memory"); return v;
}
__device__ __forceinline__ uint32_t lds32(uint32_t a) { uint32_t v; asm volatile("ld.shared.b32 %0, [%1];" : "=r"(v) : "r"(a) : "memory"); return v; }
__device__ __forceinline__ int grab_tile(unsigned* ctr) {
    int v; asm volatile("atom.relaxed.gpu.global.inc.u32 %0, [%1], 0x7fffffff;" : "=r"(v) : "l"(ctr) : "memory"); return v;
}
__device__ __forceinline__ uint32_t opaque(uint32_t v) { uint32_t r; asm volatile("mov.b32 %0, %1;" : "=r"(r) : "r"(v)); return r; }
__device__ __forceinline__ float rsq(float x) { float r; asm("rsqrt.approx.ftz.f32 %0, %1;" : "=f"(r) : "f"(x)); return r; }
__device__ __forceinline__ float rcp(float x) { float r; asm("rcp.approx.ftz.f32 %0, %1;" : "=f"(r) : "f"(x)); return r; }
__device__ __forceinline__ float lg2(float x) { float r; asm("lg2.approx.ftz.f32 %0, %1;" : "=f"(r) : "f"(x)); return r; }
__device__ __forceinline__ float f(uint32_t v) { return __uint_as_float(v); }
__device__ __forceinline__ uint32_t u(float v) { return __float_as_uint(v); }

constexpr uint32_t ONES = 0x3F803F80u;
constexpr float QSCALE = 0.07216878364870322f * 1.4426950408889634f;

__device__ __forceinline__ void issue_tile(const CUtensorMap* m0, const CUtensorMap* m1, uint32_t sb, int s, int tl, uint64_t pol) {
    const uint32_t full = sb + SM_BAR + s * 8, dst = sb + SM_STAGES + s * STAGE;
    const int par = tl * TP, y = par >> 8, x = par & 255;
    mbar_expect(full, STAGE);
    asm volatile("cp.async.bulk.tensor.5d.shared::cluster.global.mbarrier::complete_tx::bytes.L2::cache_hint [%0], [%1, {%3,%4,%3,%3,%5}], [%2], %6;"
                 ::"r"(dst), "l"(m0), "r"(full), "r"(0), "r"(x), "r"(2 * y), "l"(pol) : "memory");
    asm volatile("cp.async.bulk.tensor.4d.shared::cluster.global.mbarrier::complete_tx::bytes.L2::cache_hint [%0], [%1, {%3,%4,%3,%5}], [%2], %6;"
                 ::"r"(dst + TP * 4 * C * 2), "l"(m1), "r"(full), "r"(0), "r"(x), "r"(y), "l"(pol) : "memory");
}

__device__ __forceinline__ uint4 ldg_relaxed(const uint4* p) {
    uint4 v; asm volatile("ld.relaxed.gpu.global.v4.u32 {%0,%1,%2,%3}, [%4];" : "=r"(v.x), "=r"(v.y), "=r"(v.z), "=r"(v.w) : "l"(p) : "memory"); return v;
}
__device__ __forceinline__ uint32_t ldg_relaxed32(const void* p) {
    uint32_t v; asm volatile("ld.relaxed.gpu.global.u32 %0, [%1];" : "=r"(v) : "l"(p) : "memory"); return v;
}
__device__ __forceinline__ void stg_relaxed(uint4* p, uint32_t x, uint32_t y, uint32_t z, uint32_t w) {
    asm volatile("st.relaxed.gpu.global.v4.u32 [%0], {%1,%2,%3,%4};" ::"l"(p), "r"(x), "r"(y), "r"(z), "r"(w) : "memory");
}
__device__ __forceinline__ void stg_relaxed32(void* p, uint32_t x) { asm volatile("st.relaxed.gpu.global.u32 [%0], %1;" ::"l"(p), "r"(x) : "memory"); }
__device__ __forceinline__ bool has(const uint4& v, uint32_t m) { return v.x == m || v.y == m || v.z == m || v.w == m; }
__device__ __forceinline__ uint32_t hadd2v(uint32_t a, uint32_t b) {
    uint32_t r; asm volatile("add.rn.bf16x2 %0, %1, %2;" : "=r"(r) : "r"(a), "r"(b)); return r;
}

__device__ __forceinline__ void red8h(uint4* p, uint32_t x, uint32_t y, uint32_t z, uint32_t w) {
    asm volatile("red.relaxed.gpu.global.add.noftz.v4.f16x2 [%0], {%1,%2,%3,%4};" ::"l"(p), "r"(x), "r"(y), "r"(z), "r"(w) : "memory");
}
__device__ __forceinline__ uint4 lds128v(uint32_t a) {
    uint4 v; asm volatile("ld.volatile.shared.v4.b32 {%0,%1,%2,%3}, [%4];" : "=r"(v.x), "=r"(v.y), "=r"(v.z), "=r"(v.w) : "r"(a) : "memory"); return v;
}
__device__ __forceinline__ uint32_t brow(int r) { return RD_B + r * 144 + (r >> 3) * 64; }

enum { B_QK = 1, B_QN = 2, B_GRP = 3  , B_Q = 5, B_MERGE = 6, B_ALL = 7, B_MAX = 8   };

__device__ __noinline__ void slow_row(const char* __restrict__ f0, const char* __restrict__ f1, const __nv_bfloat16* __restrict__ q,
                                      const __nv_bfloat16* __restrict__ wq, const __nv_bfloat16* __restrict__ wk, const uint32_t sb, const int b)
{
    const int warp = threadIdx.x >> 5, lane = threadIdx.x & 31;
    const int g = lane >> 2, t = lane & 3;
    const uint32_t bw = sb + brow(8 * (b & 3) + t) + g * 16;
    float* const sm = reinterpret_cast<float*>(__cvta_shared_to_generic(sb + RD_W));
    const int c = threadIdx.x;
    bar_sync(B_ALL, 384);
    if (c < C) sm[c] = __bfloat162float(q[b * C + c]);
    bar_sync(B_ALL, 384);
    float mu = 0.f, var = 0.f, s = 0.f;
#pragma unroll 1
    for (int i = 0; i < C; i++) mu += sm[i];
    mu *= 1.f / C;
#pragma unroll 1
    for (int i = 0; i < C; i++) var += (sm[i] - mu) * (sm[i] - mu);
    if (c < C) {
#pragma unroll 1
        for (int i = 0; i < C; i++) s = fmaf(sm[i] - mu, __bfloat162float(wq[i * C + c]), s);
        sm[C + c] = s * rsq(var * (1.f / C) + 1e-5f);
    }
    bar_sync(B_ALL, 384);
    if (c < C) {
        s = 0.f;
#pragma unroll 1
        for (int i = 0; i < C; i++) s = fmaf(sm[C + i], __bfloat162float(wk[c * C + i]), s);
        sm[2 * C + c] = s * QSCALE;
    }
    bar_sync(B_ALL, 384);
    float k[6], a[6], m = -INFINITY, l = 0.f;
#pragma unroll
    for (int i = 0; i < 6; i++) { k[i] = sm[2 * C + 24 * g + 8 * (i >> 1) + 2 * t + (i & 1)]; a[i] = 0.f; }
#pragma unroll 1
    for (int px = warp; px < W0 * W0; px += 12) {
        const uint32_t* p0 = reinterpret_cast<const uint32_t*>(f0 + (size_t)px * (C * 2)) + 12 * g + t;
        const uint32_t* p1 = reinterpret_cast<const uint32_t*>(f1 + (size_t)((px >> 10) * W1 + ((px & (W0 - 1)) >> 1)) * (C * 2)) + 12 * g + t;
        float x[6], s1 = 0.f, s2 = 0.f, d = 0.f;
#pragma unroll
        for (int i = 0; i < 3; i++) { const uint32_t v = hadd2(__ldg(p0 + 4 * i), __ldg(p1 + 4 * i)); x[2 * i] = bflo(v); x[2 * i + 1] = bfhi(v); s1 += x[2 * i] + x[2 * i + 1]; }
#pragma unroll
        for (int o = 1; o < 32; o <<= 1) s1 += __shfl_xor_sync(~0u, s1, o);
#pragma unroll
        for (int i = 0; i < 6; i++) { x[i] -= s1 * (1.f / C); s2 = fmaf(x[i], x[i], s2); d = fmaf(x[i], k[i], d); }
#pragma unroll
        for (int o = 1; o < 32; o <<= 1) { s2 += __shfl_xor_sync(~0u, s2, o); d += __shfl_xor_sync(~0u, d, o); }
        const float rs = rsq(s2 * (1.f / C) + 1e-5f), nm = fmaxf(m, d * rs), al = ex2(m - nm), p = ex2(d * rs - nm);
        m = nm; l = fmaf(l, al, p);
#pragma unroll
        for (int i = 0; i < 6; i++) a[i] = fmaf(a[i], al, x[i] * (p * rs));
    }
    if (lane == 0) sm[3 * C + warp] = m;
    bar_sync(B_ALL, 384);
    float M = m;
#pragma unroll 1
    for (int w = 0; w < 12; w++) M = fmaxf(M, sm[3 * C + w]);
    const float al = ex2(m - M);
#pragma unroll
    for (int i = 0; i < 6; i++) sm[4 * C + (warp * 7 + i) * 32 + lane] = a[i] * al;
    sm[4 * C + (warp * 7 + 6) * 32 + lane] = l * al;
    bar_sync(B_ALL, 384);
    if (warp == 8) {
        float x[7];
#pragma unroll
        for (int i = 0; i < 7; i++) { x[i] = 0.f; for (int w = 0; w < 12; w++) x[i] += sm[4 * C + (w * 7 + i) * 32 + lane]; }
        uint32_t hi[3], lo[3];
        const float r = 1.f / x[6];
#pragma unroll
        for (int i = 0; i < 3; i++) {
            hi[i] = packh(x[2 * i] * r, x[2 * i + 1] * r);
            const float2 h = unpackh(hi[i]);
            lo[i] = packh(fmaf(x[2 * i], r, -h.x), fmaf(x[2 * i + 1], r, -h.y));
        }
        sts128(bw, hi[0], hi[1], hi[2], lane ? 0u : 0x3C000000u);
        sts128(bw + 4 * 144, lo[0], lo[1], lo[2], 0);
    }
    bar_sync(B_ALL, 384);
}

__device__ __forceinline__ void reducer(const char* __restrict__ f0, const char* __restrict__ f1, const __nv_bfloat16* __restrict__ q, const __nv_bfloat16* __restrict__ wq, const __nv_bfloat16* __restrict__ wk,
                                        Scratch* scr, const __nv_bfloat16* __restrict__ wv, const __nv_bfloat16* __restrict__ wo,
                                        __nv_bfloat16* __restrict__ out, const uint32_t sb, const int GS)
{
    const int warp = threadIdx.x >> 5, lane = threadIdx.x & 31, b = blockIdx.x;
    const int g = lane >> 2, t = lane & 3;
    if (threadIdx.x == 256) TS(0);
    if (b < NSRC && warp < 8) {
        const uint32_t wqs = sb + RD_W, wbar = sb + RD_BAR;
        const int hr = lane >> 4, qt = (lane >> 2) & 3, sub = lane & 3;
        const uint32_t* qp = reinterpret_cast<const uint32_t*>(q + (warp + 8 * hr) * C + 48 * qt + 6 * sub);
        uint32_t qw[6];
#pragma unroll
        for (int j = 0; j < 3; j++) { qw[j] = __ldg(qp + j); qw[3 + j] = __ldg(qp + 12 + j); }
        if (lane == 0) { mbar_init(wbar + warp * 8, 1); asm volatile("fence.mbarrier_init.release.cluster;" ::: "memory"); mbar_expect(wbar + warp * 8, 9216);
            asm volatile("cp.async.bulk.shared::cluster.global.mbarrier::complete_tx::bytes [%0], [%1], 9216, [%2];"
                         ::"r"(wqs + warp * 9232), "l"(wq + 24 * warp * C), "r"(wbar + warp * 8) : "memory");
        }
        __syncwarp();
        if (threadIdx.x == 0) TSP(2, 0);
        float e[12];
#pragma unroll
        for (int j = 0; j < 6; j++) { e[2 * j] = bflo(qw[j]); e[2 * j + 1] = bfhi(qw[j]); }
        float sm = ((e[0] + e[1]) + (e[2] + e[3])) + ((e[4] + e[5]) + (e[6] + e[7])) + ((e[8] + e[9]) + (e[10] + e[11]));
#pragma unroll
        for (int o = 1; o < 16; o <<= 1) sm += __shfl_xor_sync(~0u, sm, o);
        if (threadIdx.x == 0) TSP(5, u(sm));
        float v0 = 0.f, v1 = 0.f;
#pragma unroll
        for (int j = 0; j < 12; j++) e[j] -= sm * (1.f / C);
#pragma unroll
        for (int j = 0; j < 6; j++) { v0 = fmaf(e[j], e[j], v0); v1 = fmaf(e[6 + j], e[6 + j], v1); }
        v0 += v1;
#pragma unroll
        for (int o = 1; o < 16; o <<= 1) v0 += __shfl_xor_sync(~0u, v0, o);
        const float rq = rsq(v0 * (1.f / C) + 1e-5f);
#pragma unroll
        for (int j = 0; j < 6; j++)
            sts32(sb + RD_QN + (3 * sub + (j >> 1)) * 512 + (4 * warp + qt) * 16 + (2 * (j & 1) + hr) * 4, pack2(e[j] * rq, e[6 + j] * rq));
        if (threadIdx.x == 0) TSP(8, 0);
        uint32_t wkf[2][3];
#pragma unroll
        for (int i = 0; i < 2; i++)
#pragma unroll
            for (int j = 0; j < 3; j++) wkf[i][j] = __ldg(reinterpret_cast<const uint32_t*>(wk + (16 * b + 8 * i + g) * C + 24 * warp + 8 * j + 2 * t));
        bar_sync(B_QN, 256);
        float acc[2][3][4];
#pragma unroll
        for (int i = 0; i < 3; i++)
#pragma unroll
            for (int e = 0; e < 4; e++) acc[0][i][e] = acc[1][i][e] = 0.f;
        const uint32_t ba = wqs + (lane & 7) * 9232 + (lane >> 3) * 384 + 48 * warp;
        uint4 a[12];
#pragma unroll
        for (int kk = 0; kk < 12; kk++) a[kk] = lds128(sb + RD_QN + kk * 512 + lane * 16);
        mbar_wait(wbar + (lane & 7) * 8, 0);
        __syncwarp();
        if (threadIdx.x == 0) TSP(4, 0);
#pragma unroll
        for (int kp = 0; kp < 6; kp++)
#pragma unroll
            for (int i = 0; i < 3; i++) {
                uint32_t bb[4];
                ldsm4t(bb, ba + kp * 1536 + i * 16);
                mma(acc[0][i], a[2 * kp].x, a[2 * kp].y, a[2 * kp].z, a[2 * kp].w, bb[0], bb[1]);
                mma(acc[1][i], a[2 * kp + 1].x, a[2 * kp + 1].y, a[2 * kp + 1].z, a[2 * kp + 1].w, bb[2], bb[3]);
            }
        if (threadIdx.x == 0) TSP(7, u(acc[1][2][3]));
        float kq[2][4] = {{0.f, 0.f, 0.f, 0.f}, {0.f, 0.f, 0.f, 0.f}};
#pragma unroll
        for (int j = 0; j < 3; j++) {
            const uint32_t a0 = pack2(acc[0][j][0] + acc[1][j][0], acc[0][j][1] + acc[1][j][1]), a1 = pack2(acc[0][j][2] + acc[1][j][2], acc[0][j][3] + acc[1][j][3]);
            mma8(kq[0], a0, a1, wkf[0][j]);
            mma8(kq[1], a0, a1, wkf[1][j]);
        }
        if (warp < 7) {
            sts128(sb + RD_KQ + warp * 1024 + lane * 16, u(kq[0][0]), u(kq[0][1]), u(kq[0][2]), u(kq[0][3]));
            sts128(sb + RD_KQ + warp * 1024 + 512 + lane * 16, u(kq[1][0]), u(kq[1][1]), u(kq[1][2]), u(kq[1][3]));
            bar_arrive(B_Q, 256);
        } else {
            bar_sync(B_Q, 256);
#pragma unroll
            for (int w = 0; w < 7; w++)
#pragma unroll
                for (int i = 0; i < 2; i++) {
                    const uint4 o = lds128(sb + RD_KQ + w * 1024 + i * 512 + lane * 16);
                    kq[i][0] += f(o.x); kq[i][1] += f(o.y); kq[i][2] += f(o.z); kq[i][3] += f(o.w);
                }
            stg_relaxed(g_qk + b * 32 + lane, ~pack2(kq[0][0] * QSCALE, kq[0][1] * QSCALE), ~pack2(kq[0][2] * QSCALE, kq[0][3] * QSCALE),
                        ~pack2(kq[1][0] * QSCALE, kq[1][1] * QSCALE), ~pack2(kq[1][2] * QSCALE, kq[1][3] * QSCALE));
            if (lane == 0) TS(10);
        }
    } else if (b >= NSRC) {
        if (b == NSRC && warp == 0) stg_relaxed32(g_mmax + lane, 0);
        __nanosleep(2500);
    }
    bar_sync(B_ALL, 384);

#pragma unroll 1
    for (int r = 0; r < 3; r++) {
        uint4 v[8];
#pragma unroll
        for (int k = 0; k < 8; k++) {
            const int idx = (8 * r + k) * 384 + threadIdx.x;
            v[k] = __ldg(reinterpret_cast<const uint4*>(idx < 4608 ? wv : wo - C * C) + idx);
        }
#pragma unroll
        for (int k = 0; k < 8; k++) {
            const int idx = (8 * r + k) * 384 + threadIdx.x, row = idx / 24;
            sts128(sb + RD_W + row * WROW + (idx - 24 * row) * 16, v[k].x, v[k].y, v[k].z, v[k].w);
        }
    }
    if (threadIdx.x < 256) {
        sts128(sb + brow(threadIdx.x >> 3) + (threadIdx.x & 7) * 16, EMPTY, EMPTY, EMPTY, EMPTY);
        stg_relaxed(g_acc + (threadIdx.x >> 7) * ACC + (b >> 2) * 128 + (threadIdx.x & 127), 0, 0, 0, 0);
        __threadfence();
    }
    if (threadIdx.x == 0) sts128(sb + RD_BAD, 0, 0, 0, 0);
    bar_sync(B_ALL, 384);
    uint32_t wa[12][4];
    float ws0 = 0.f, ws1 = 0.f, qv0 = 0.f, qv1 = 0.f;
    __nv_bfloat16* op = out;
    if (warp < 3) {
        const int col = 48 * (b & 3) + 16 * warp;
        float d[24][4];
#pragma unroll
        for (int i = 0; i < 24; i++) d[i][0] = d[i][1] = d[i][2] = d[i][3] = 0.f;
        const int mi = lane >> 3, r = lane & 7;
        const uint32_t aa = sb + RD_W + (C + (mi >> 1) * 8 + r) * WROW + (col + (mi & 1) * 8) * 2;
        const uint32_t ba = sb + RD_W + ((mi >> 1) * 8 + r) * WROW + (mi & 1) * 16;
#pragma unroll 1
        for (int kk = 0; kk < 12; kk++) {
            uint32_t a[4];
            ldsm4t(a, aa + kk * 16 * WROW);
#pragma unroll
            for (int i = 0; i < 12; i++) {
                uint32_t bb[4];
                ldsm4(bb, ba + i * 16 * WROW + kk * 32);
                mma(d[2 * i], a[0], a[1], a[2], a[3], bb[0], bb[1]);
                mma(d[2 * i + 1], a[0], a[1], a[2], a[3], bb[2], bb[3]);
            }
        }
        float c0 = 0.f, c1 = 0.f, m0 = 0.f, m1 = 0.f;
#pragma unroll
        for (int i = 0; i < 24; i++) { c0 += d[i][0] + d[i][1]; c1 += d[i][2] + d[i][3]; }
        c0 += __shfl_xor_sync(~0u, c0, 1); c1 += __shfl_xor_sync(~0u, c1, 1);
        c0 += __shfl_xor_sync(~0u, c0, 2); c1 += __shfl_xor_sync(~0u, c1, 2);
        c0 *= 1.f / C; c1 *= 1.f / C;
#pragma unroll
        for (int i = 0; i < 24; i++) {
            d[i][0] -= c0; d[i][1] -= c0; d[i][2] -= c1; d[i][3] -= c1;
            m0 = fmaxf(m0, fmaxf(fabsf(d[i][0]), fabsf(d[i][1]))); m1 = fmaxf(m1, fmaxf(fabsf(d[i][2]), fabsf(d[i][3])));
        }
        m0 = fmaxf(m0, __shfl_xor_sync(~0u, m0, 1)); m1 = fmaxf(m1, __shfl_xor_sync(~0u, m1, 1));
        m0 = fmaxf(m0, __shfl_xor_sync(~0u, m0, 2)); m1 = fmaxf(m1, __shfl_xor_sync(~0u, m1, 2));
        const uint32_t e0 = min(max(u(m0) >> 23, 12u), 254u), e1 = min(max(u(m1) >> 23, 12u), 254u);
        const float s0 = f((265u - e0) << 23), s1 = f((265u - e1) << 23);
        ws0 = f((e0 - 11u) << 23); ws1 = f((e1 - 11u) << 23);
#pragma unroll
        for (int i = 0; i < 24; i++) {
            const int kk = i % 3 < 2 ? i / 3 : 8 + i / 6, hf = i % 3 < 2 ? i % 3 : (i / 3) & 1;
            wa[kk][2 * hf] = packh(d[i][0] * s0, d[i][1] * s0);
            wa[kk][2 * hf + 1] = packh(d[i][2] * s1, d[i][3] * s1);
        }
        const int o = ((b & 12) + t) * C + col + g;
        qv0 = __bfloat162float(q[o]); qv1 = __bfloat162float(q[o + 8]);
        op = out + o;
        asm volatile("" : "+l"(op));
        if (threadIdx.x == 0) TSE(6);
    } else if (warp == 3) {
        if (lane == 0) {
            uint32_t m;
            for (int it = 0;; it++) {
                const int left = NT - 2 * NST * GS - (int)ldg_relaxed32(g_ctr);
                m = ldg_relaxed32(g_mmax + b);
                if (left <= REFT && m) break;
                if (left <= 0) { m = 0x80000000u; break; }
                if (it > SPIN_LIMIT) __trap();
                __nanosleep(300);
            }
            asm volatile("st.release.gpu.global.u32 [%0], %1;" ::"l"(g_mref + b), "r"(~u(f(m >> 31 ? m ^ 0x80000000u : ~m) + 8.f)) : "memory");
            TSE(7);
        }
        __syncwarp();
    } else {
        const int pr = warp & 1;
        const uint4* const pa = g_acc + ((b >> 2) * 2 + pr) * 64 + lane;
        const uint32_t bw = opaque(sb + brow(16 * pr + 8 * ((lane >> 2) & 1) + t) + (lane >> 3) * 16);
        const uint32_t n0 = packh((float)((GS + 1) >> 1), 0.f), n1 = packh((float)(GS >> 1), 0.f), nstart = packh((float)POLLN, 0.f);
        for (int it = 0; (ldg_relaxed32(reinterpret_cast<const uint32_t*>(pa - lane) + 3) & 0xFFFFu) < nstart; it++)
            if (it > SPIN_LIMIT) __trap();
        for (const unsigned c = clock(); clock() - c < ((warp - 4) >> 1) * PGAP;) {}
        uint4 a0, a1, b0, b1;
        for (int it = 0;; it++) {
            a0 = ldg_relaxed(pa); a1 = ldg_relaxed(pa + ACC); b0 = ldg_relaxed(pa + 32); b1 = ldg_relaxed(pa + ACC + 32);
            if (__all_sync(~0u, (((a0.w ^ n0) | (b0.w ^ n0) | (a1.w ^ n1) | (b1.w ^ n1)) & 0xFFFFu) == 0)) break;
            if (it > SPIN_LIMIT) __trap();
        }
        sts128(bw, a0.x, a0.y, a0.z, a0.w);
        sts128(bw + 4 * 144, a1.x, a1.y, a1.z, a1.w);
        sts128(bw + 64, b0.x, b0.y, b0.z, b0.w);
        sts128(bw + 4 * 144 + 64, b1.x, b1.y, b1.z, b1.w);
        if (warp == 4) {
            if (b < NSRC) g_qk[b * 32 + lane] = make_uint4(0, 0, 0, 0);
            if (lane == 0) { g_mref[b] = 0; if (b == NSRC) g_ctr[0] = 0; }
        }
    }
    const uint32_t br = opaque(sb + brow(lane));
#pragma unroll 1
    for (uint32_t pass = 0;; pass = 1) {
        if (warp < 3) {
            uint4 x[8];
            float o[4][4];
            for (int it = 0;; it++) {
                for (;; it++) {
                    x[7] = lds128v(br + 7 * 16);
                    if (!__any_sync(~0u, x[7].w & 0x8000u)) break;
                    if (it > 64 * SPIN_LIMIT) __trap();
                }
                if (threadIdx.x == 0) TSX(8, 0);
#pragma unroll
                for (int j = 0; j < 7; j++) x[j] = lds128v(br + j * 16);
#pragma unroll
                for (int j = 0; j < 4; j++) o[j][0] = o[j][1] = o[j][2] = o[j][3] = 0.f;
#pragma unroll
                for (int i = 0; i < 4; i++) {
                    mmah(o[3], 0x3C000000u, 0x3C000000u, 0x3C000000u, 0x3C000000u, x[2 * i].w, x[2 * i + 1].w);
                    mmah(o[0], wa[2 * i][0], wa[2 * i][1], wa[2 * i][2], wa[2 * i][3], x[2 * i].x, x[2 * i].y);
                    mmah(o[1], wa[2 * i + 1][0], wa[2 * i + 1][1], wa[2 * i + 1][2], wa[2 * i + 1][3], x[2 * i + 1].x, x[2 * i + 1].y);
                    mmah(o[2], wa[8 + i][0], wa[8 + i][1], wa[8 + i][2], wa[8 + i][3], x[2 * i].z, x[2 * i + 1].z);
                }
                if (!__any_sync(~0u, ((x[0].w | x[1].w | x[2].w) | (x[3].w | x[4].w | x[5].w) | x[6].w) & 0x8000u)) break;
            }
            const float L = o[3][0] + o[3][1], r = rcp(L);
            const float y0 = fmaf(((o[0][0] + o[0][1]) + (o[1][0] + o[1][1])) + (o[2][0] + o[2][1]), r * ws0, qv0);
            const float y1 = fmaf(((o[0][2] + o[0][3]) + (o[1][2] + o[1][3])) + (o[2][2] + o[2][3]), r * ws1, qv1);
            op[0] = __float2bfloat16(y0);
            op[8] = __float2bfloat16(y1);
            if (threadIdx.x == 0) TSD(11, u(y0));
            if (!(L >= 0.001953125f && L <= 2048.f && fabsf(y0) + fabsf(y1) < INFINITY)) sts32(sb + RD_BAD + t * 4, 1);
        }
        bar_sync(B_ALL, 384);
        if (pass) break;
        const uint4 bad = lds128(sb + RD_BAD);
        if (__builtin_expect((bad.x | bad.y | bad.z | bad.w) == 0, 1)) break;
        const uint32_t keep = sb + RD_W + 32768 + warp * 6144 + lane * 16;
        if (warp < 3)
#pragma unroll
            for (int kk = 0; kk < 12; kk++) sts128(keep + kk * 512, wa[kk][0], wa[kk][1], wa[kk][2], wa[kk][3]);
#pragma unroll 1
        for (int r = 0; r < 4; r++)
            if (lds32(sb + RD_BAD + r * 4)) slow_row(f0, f1, q, wq, wk, sb, (b & 12) + r);
        if (warp < 3)
#pragma unroll
            for (int kk = 0; kk < 12; kk++) {
                const uint4 v = lds128(keep + kk * 512);
                wa[kk][0] = v.x; wa[kk][1] = v.y; wa[kk][2] = v.z; wa[kk][3] = v.w;
            }
    }
}

__global__ void __launch_bounds__(NTHREADS, 1)
attn_main(const char* __restrict__ f0, const char* __restrict__ f1,
          const __nv_bfloat16* __restrict__ q, const __nv_bfloat16* __restrict__ wq, const __nv_bfloat16* __restrict__ wk, Scratch* scr,
          const __nv_bfloat16* __restrict__ wv, const __nv_bfloat16* __restrict__ wo, __nv_bfloat16* __restrict__ out,
          const __grid_constant__ CUtensorMap m0, const __grid_constant__ CUtensorMap m1)
{
    extern __shared__ char smem_raw[];
    const uint32_t sb = (s2u(smem_raw) + 1023u) & ~1023u;
    const int G = gridDim.x - NRD;
    if (blockIdx.x < NRD) { reducer(f0, f1, q, wq, wk, scr, wv, wo, out, sb, G); return; }
    const int b = blockIdx.x - NRD;
    const int warp = threadIdx.x >> 5, lane = threadIdx.x & 31;
    const int g = lane >> 2, t = lane & 3;

    if (warp >= 8) {
        if (warp < 10) {
            const int p = warp - 8;
            if (lane == 0) {
                if (p == 0) TS(0);
                asm volatile("prefetch.tensormap [%0];" ::"l"(p ? &m1 : &m0) : "memory");
            }
            if (lane < NS / 2) {
                const int s = 2 * lane + p;
                mbar_init(sb + SM_BAR + s * 8, 1); mbar_init(sb + SM_BAR + (NS + s) * 8, 1);
            }
            if (p == 0 && lane == 31) mbar_init(sb + SM_REF, 1);
            asm volatile("fence.mbarrier_init.release.cluster;" ::: "memory");
            __syncwarp();
            bar_arrive(B_QK, 384);
            if (lane == 0) {
                uint64_t pol; asm volatile("createpolicy.fractional.L2::evict_first.b64 %0, 1.0;" : "=l"(pol));
                int s = p; uint32_t ph = 1;
                int sa = p, na = 0; uint32_t pa = 0;
                int tl = b + p * G;
                bool late = false;
                for (int n = 0;; n++) {
                    int nxt = tl + 2 * G;
                    if (n >= NST - 1) nxt = grab_tile(g_ctr) + 2 * NST * G;
                    const int d = n < NRAMP ? D0 : (tl >= NT - TAILT ? D2 : D1);
                    while (n - na >= d) {
                        mbar_wait(sb + SM_BAR + sa * 8, pa);
                        if (na < NS / 2) TR(1, 2 * na + p);
                        na++; sa += 2;
                        if (sa >= NS) { sa -= NS; pa ^= 1; }
                    }
                    mbar_wait(sb + SM_BAR + (NS + s) * 8, ph);
                    const bool last = nxt >= NT;
                    uint32_t flag = last;
                    if (!late && nxt >= NT - MAXT - 16 * b) { late = true; flag |= 2; }
                    if (last) mbar_wait(sb + SM_REF, 0);
                    sts32(sb + SM_FLAG + s * 4, flag);
                    issue_tile(&m0, &m1, sb, s, tl, pol);
                    TR(0, 2 * n + p);
                    if (last) break;
                    s += 2;
                    if (s >= NS) { s -= NS; ph ^= 1; }
                    tl = nxt;
                }
                if (p) TSE(5);
            }
            return;
        }
        const int h = threadIdx.x - 320;
        uint4 v[6];
        for (int it = 0;; it++) {
            bool miss = false;
#pragma unroll
            for (int k = 0; k < 6; k++) v[k] = ldg_relaxed(g_qk + k * 64 + h);
#pragma unroll
            for (int k = 0; k < 6; k++) miss |= has(v[k], 0);
            if (!miss) break;
            if (it > SPIN_LIMIT) __trap();
            if (it == 0) __nanosleep(QSLEEP);
        }
#pragma unroll
        for (int k = 0; k < 6; k++) sts128(sb + SM_QK + (k * 64 + h) * 16, ~v[k].x, ~v[k].y, ~v[k].z, ~v[k].w);
        __syncwarp();
        bar_sync(B_QK, 384);
        if (warp == 11) return;
        uint32_t r = 1;
        for (int it = 0;; it++) {
            __nanosleep(500);
            if (lane < NQ) asm volatile("ld.acquire.gpu.global.u32 %0, [%1];" : "=r"(r) : "l"(g_mref + lane) : "memory");
            if (__all_sync(~0u, r != 0)) break;
            if (it > SPIN_LIMIT) __trap();
        }
        if (lane < NQ) sts32(sb + SM_M + lane * 4, ~r);
        __syncwarp();
        if (lane == 0) { mbar_arrive(sb + SM_REF); TSE(7); }
        return;
    }

    const int grp = warp >> 2, cw = warp & 3;
    if (lane == 0) {
        const char* a; int sz;
        if (warp >= 6) {
            sz = C * C * 2 / WSL; a = (const char*)(warp == 6 ? wq : wk) + (b % WSL) * sz;
        } else {
            const int tl = b + (warp / 3) * G, which = warp % 3;
            const int par = tl * TP, y = par >> 8, x = par & 255;
            a = which < 2 ? f0 + ((size_t)(2 * y + which) * W0 + 2 * x) * (C * 2) : f1 + ((size_t)y * W1 + x) * (C * 2);
            sz = which < 2 ? TP * 2 * C * 2 : TP * C * 2;
        }
        if (warp >= 6 || warp < 3 * NPRE) asm volatile("cp.async.bulk.prefetch.L2.global [%0], %1;" ::"l"(a), "r"(sz) : "memory");
    }

    const int xp = lane & 7, mi = lane >> 3;
    const uint32_t offS = opaque(xp * 128 + ((mi ^ xp) << 4));
    uint32_t offT[6], offT1[2];
#pragma unroll
    for (int i = 0; i < 6; i++) {
        const int J = 6 * cw + (i + 3 * grp) % 6;
        offT[i] = opaque(mi * 3072 + (J >> 3) * 1024 + xp * 128 + (((J & 7) ^ xp) << 4));
    }
    {
        const int J = 6 * cw + (mi + 3 * grp) % 6, J2 = 6 * cw + (4 + (mi & 1) + 3 * grp) % 6;
        offT1[0] = opaque(12288 + (J >> 3) * 1024 + xp * 128 + (((J & 7) ^ xp) << 4));
        offT1[1] = opaque(12288 + (J2 >> 3) * 1024 + xp * 128 + (((J2 & 7) ^ xp) << 4));
    }
    const uint32_t mxw = opaque(sb + SM_MX + grp * 256 + ((g + 8 * t) * 4 + cw) * 4);
    const uint32_t offS0 = opaque(offS + cw * 3072);
    const int shl = opaque(9 * t);
    const uint32_t mxr = sb + SM_MX + grp * 256 + g * 16;
    const uint32_t pw = (cw >> 1) * 512 + lane * 16 + (cw & 1) * 8, muw = 1024 + t * 16 + cw * 4;
    uint32_t pb0 = sb + SM_P + grp * 2 * PBUF;
    const uint32_t pbx = pb0 ^ (pb0 + PBUF);
    const int barid = B_GRP + grp;
    const bool elected = (threadIdx.x & 127) == 96;

    uint32_t qa[48];
    float r_lo, r_hi;
    bar_sync(B_QK, 384);
    {
        float rr[2][4] = {{0.f, 0.f, 0.f, 0.f}, {0.f, 0.f, 0.f, 0.f}};
#pragma unroll
        for (int kk = 0; kk < 12; kk++) {
            const uint4 v = lds128(sb + SM_QK + kk * 512 + lane * 16);
            qa[4 * kk] = v.x; qa[4 * kk + 1] = v.y; qa[4 * kk + 2] = v.z; qa[4 * kk + 3] = v.w;
            mma(rr[kk & 1], v.x, v.y, v.z, v.w, ONES, ONES);
        }
        r_lo = rr[0][0] + rr[1][0]; r_hi = rr[0][2] + rr[1][2];
    }
    if (threadIdx.x == 0) TS(1);

    float acc[6][4];
#pragma unroll
    for (int i = 0; i < 6; i++) acc[i][0] = acc[i][1] = acc[i][2] = acc[i][3] = 0.f;
    float m_lo = -INFINITY, m_hi = -INFINITY, l_lo = 0.f, l_hi = 0.f;
    float cm[4] = {0.f, 0.f, 0.f, 0.f};
    uint32_t xt[6][4]; uint4 pa, pb, mv;
    int s = grp; uint32_t ph = 0;
    while (true) {
        mbar_wait(sb + SM_BAR + s * 8, ph);
        PH(0, 0);
        const uint32_t stop = lds32(sb + SM_FLAG + s * 4);
        const uint32_t st = sb + SM_STAGES + s * STAGE;
        float sc[2][4], gr[2][4];
#pragma unroll
        for (int e = 0; e < 4; e++) sc[0][e] = sc[1][e] = gr[0][e] = gr[1][e] = 0.f;
        const uint32_t a0e = st + offS0, a1e = st + 12288 + offS;
#pragma unroll
        for (int qq = 0; qq < 6; qq++) {
            uint32_t x[4], y[4];
            ldsm4(x, (a0e ^ ((qq & 1) << 6)) + (qq >> 1) * 1024);
            ldsm4(y, (a1e ^ ((qq & 1) << 6)) + (qq >> 1) * 1024);
#pragma unroll
            for (int e = 0; e < 4; e++) x[e] = hadd2(x[e], y[e]);
            mma(gr[0], x[0], ONES, x[1], ONES, x[0], x[1]);
            mma(gr[1], x[2], ONES, x[3], ONES, x[2], x[3]);
            mma(sc[0], qa[8 * qq], qa[8 * qq + 1], qa[8 * qq + 2], qa[8 * qq + 3], x[0], x[1]);
            mma(sc[1], qa[8 * qq + 4], qa[8 * qq + 5], qa[8 * qq + 6], qa[8 * qq + 7], x[2], x[3]);
        }
        uint32_t yt[6];
        ldsm4t(yt, st + offT1[0]);
        ldsm2t(yt + 4, st + offT1[1]);
#pragma unroll
        for (int i = 0; i < 6; i++) ldsm4t(xt[i], st + offT[i]);

        const float ss0 = __shfl_sync(~0u, gr[0][0] + gr[1][0], shl);
        const float ss1 = __shfl_sync(~0u, gr[0][1] + gr[1][1], shl + 4);
        const float mu0 = (gr[0][2] + gr[1][2]) * (1.f / C), mu1 = (gr[0][3] + gr[1][3]) * (1.f / C);
        const float rs0 = rsq(fmaxf(fmaf(-mu0, mu0, ss0 * (1.f / C)), 0.f) + 1e-5f);
        const float rs1 = rsq(fmaxf(fmaf(-mu1, mu1, ss1 * (1.f / C)), 0.f) + 1e-5f);
        const float u0 = fmaf(-mu0, r_lo, sc[0][0] + sc[1][0]), u1 = fmaf(-mu1, r_lo, sc[0][1] + sc[1][1]);
        const float u2 = fmaf(-mu0, r_hi, sc[0][2] + sc[1][2]), u3 = fmaf(-mu1, r_hi, sc[0][3] + sc[1][3]);
        const float d0 = fmaf(u0, rs0, -m_lo), d1 = fmaf(u1, rs1, -m_lo), d2 = fmaf(u2, rs0, -m_hi), d3 = fmaf(u3, rs1, -m_hi);
        PH(1, u(d0 + d2));
        float p0 = ex2(d0), p1 = ex2(d1), p2 = ex2(d2), p3 = ex2(d3);
        sts64(pb0 + pw, pack2(p0 * rs0, p1 * rs1), pack2(p2 * rs0, p3 * rs1));
        if (lane < 4) sts32(pb0 + muw, pack2(mu0, mu1));
#pragma unroll
        for (int i = 0; i < 6; i++)
#pragma unroll
            for (int e = 0; e < 4; e++) xt[i][e] = hadd2v(xt[i][e], yt[i]);
        const bool over = bar_any(barid, 128, fmaxf(fmaxf(d0, d1), fmaxf(d2, d3)) > LAZY);
        PH(3, 0);
        pa = lds128(pb0 + lane * 16); pb = lds128(pb0 + lane * 16 + 512); mv = lds128(pb0 + 1024 + t * 16);
        if (elected) mbar_arrive(sb + SM_BAR + (NS + s) * 8);
        if (__builtin_expect(over, 0)) {
            const float s0 = u0 * rs0, s1 = u1 * rs1, s2 = u2 * rs0, s3 = u3 * rs1;
            float xl = fmaxf(s0, s1), xh = fmaxf(s2, s3);
            xl = fmaxf(xl, __shfl_xor_sync(~0u, xl, 1)); xh = fmaxf(xh, __shfl_xor_sync(~0u, xh, 1));
            xl = fmaxf(xl, __shfl_xor_sync(~0u, xl, 2)); xh = fmaxf(xh, __shfl_xor_sync(~0u, xh, 2));
            if (t < 2) sts32(mxw, u(t ? xh : xl));
            bar_sync(B_MAX + grp, 128);
            const uint4 ml4 = lds128(mxr), mh4 = lds128(mxr + 128);
            const float nl = fmaxf(fmaxf(fmaxf(f(ml4.x), f(ml4.y)), fmaxf(f(ml4.z), f(ml4.w))), m_lo);
            const float nh = fmaxf(fmaxf(fmaxf(f(mh4.x), f(mh4.y)), fmaxf(f(mh4.z), f(mh4.w))), m_hi);
            p0 = ex2(s0 - nl); p1 = ex2(s1 - nl); p2 = ex2(s2 - nh); p3 = ex2(s3 - nh);
            sts64(pb0 + pw, pack2(p0 * rs0, p1 * rs1), pack2(p2 * rs0, p3 * rs1));
            const float al = ex2(m_lo - nl), ah = ex2(m_hi - nh);
            m_lo = nl; m_hi = nh;
            l_lo *= al; l_hi *= ah; cm[0] *= al; cm[2] *= ah;
#pragma unroll
            for (int i = 0; i < 6; i++) { acc[i][0] *= al; acc[i][1] *= al; acc[i][2] *= ah; acc[i][3] *= ah; }
            bar_sync(B_MAX + grp, 128);
            pa = lds128(pb0 + lane * 16); pb = lds128(pb0 + lane * 16 + 512);
        }
        l_lo += p0 + p1; l_hi += p2 + p3;
        if (stop & 1) break;
#pragma unroll
        for (int i = 0; i < 6; i++) mma(acc[i], pa.x, pa.y, pa.z, pa.w, xt[i][0], xt[i][1]);
        mma(cm, pa.x, pa.y, pa.z, pa.w, mv.x, mv.y);
#pragma unroll
        for (int i = 0; i < 6; i++) mma(acc[i], pb.x, pb.y, pb.z, pb.w, xt[i][2], xt[i][3]);
        mma(cm, pb.x, pb.y, pb.z, pb.w, mv.z, mv.w);
        PH(4, u(acc[5][0]));
        if (stop) {
            float a = l_lo + __shfl_xor_sync(~0u, l_lo, 1), c = l_hi + __shfl_xor_sync(~0u, l_hi, 1);
            a += __shfl_xor_sync(~0u, a, 2); c += __shfl_xor_sync(~0u, c, 2);
            const uint32_t m = u((t ? m_hi : m_lo) + lg2(fmaxf(t ? c : a, 1.f)));
            if (t < 2) asm volatile("red.relaxed.gpu.global.max.u32 [%0], %1;" ::"l"(g_mmax + g + 8 * t), "r"(m >> 31 ? ~m : m | 0x80000000u) : "memory");
        }
        pb0 ^= pbx;
        s += 2;
        if (s >= NS) { s -= NS; ph ^= 1; }
    }
    const float al = ex2(m_lo - f(lds32(sb + SM_M + g * 4))), ah = ex2(m_hi - f(lds32(sb + SM_M + 32 + g * 4)));
    mma(cm, pa.x, pa.y, pa.z, pa.w, mv.x, mv.y);
#pragma unroll
    for (int i = 3; i < 6; i++) mma(acc[i], pa.x, pa.y, pa.z, pa.w, xt[i][0], xt[i][1]);
    mma(cm, pb.x, pb.y, pb.z, pb.w, mv.z, mv.w);
#pragma unroll
    for (int i = 3; i < 6; i++) mma(acc[i], pb.x, pb.y, pb.z, pb.w, xt[i][2], xt[i][3]);
#pragma unroll
    for (int i = 0; i < 3; i++) mma(acc[i], pa.x, pa.y, pa.z, pa.w, xt[i][0], xt[i][1]);
#pragma unroll
    for (int i = 0; i < 3; i++) mma(acc[i], pb.x, pb.y, pb.z, pb.w, xt[i][2], xt[i][3]);
    if (threadIdx.x == grp * 128) TSE(2 + grp);
    if (threadIdx.x == grp * 128 + 96) TSX(2 + grp, u(acc[5][0]));

    uint4* const dst = g_acc + (b & 1) * ACC + ((g >> 1) * 8 + 2 * cw + grp) * 8 + (lane & 7);
    const uint32_t xw = opaque(sb + SM_STAGES + grp * STAGE + cw * 1536 + lane * 16), xr = opaque(sb + SM_STAGES + (grp ^ 1) * STAGE + cw * 1536 + lane * 16);
    asm volatile("" ::"l"(dst));
    const float cl = -cm[0] * al, ch = -cm[2] * ah;
#pragma unroll
    for (int i = 0; i < 3; i++)
        sts128(xw + i * 512, u(fmaf(acc[3 + i][0], al, cl)), u(fmaf(acc[3 + i][1], al, cl)), u(fmaf(acc[3 + i][2], ah, ch)), u(fmaf(acc[3 + i][3], ah, ch)));
#pragma unroll
    for (int i = 0; i < 3; i++) { acc[i][0] = fmaf(acc[i][0], al, cl); acc[i][1] = fmaf(acc[i][1], al, cl); acc[i][2] = fmaf(acc[i][2], ah, ch); acc[i][3] = fmaf(acc[i][3], ah, ch); }
    const uint32_t w_lo = packh(1.f, l_lo * al), w_hi = packh(1.f, l_hi * ah);
    bar_sync(B_MERGE, 256);
    if (threadIdx.x == 224) TSX(4, 0);
    uint4 o[3];
#pragma unroll
    for (int i = 0; i < 3; i++) o[i] = lds128(xr + i * 512);
    red8h(dst, packh(acc[0][0] + f(o[0].x), acc[0][1] + f(o[0].y)), packh(acc[1][0] + f(o[1].x), acc[1][1] + f(o[1].y)), packh(acc[2][0] + f(o[2].x), acc[2][1] + f(o[2].y)), w_lo);
    red8h(dst + 256, packh(acc[0][2] + f(o[0].z), acc[0][3] + f(o[0].w)), packh(acc[1][2] + f(o[1].z), acc[1][3] + f(o[1].w)), packh(acc[2][2] + f(o[2].z), acc[2][3] + f(o[2].w)), w_hi);
    if (threadIdx.x == 0) TSE(4);
    if (threadIdx.x == 224) TSX(9, 0);
}

typedef CUresult (*EncodeFn)(CUtensorMap*, CUtensorMapDataType, cuuint32_t, void*, const cuuint64_t*, const cuuint64_t*,
                             const cuuint32_t*, const cuuint32_t*, CUtensorMapInterleave, CUtensorMapSwizzle,
                             CUtensorMapL2promotion, CUtensorMapFloatOOBfill);

}

extern "C" void kernel_launch(void* const* d_in, const int* in_sizes, int n_in, void* d_out, int out_size) {
    const __nv_bfloat16* q = (const __nv_bfloat16*)d_in[0];
    char* f0 = (char*)d_in[1];
    char* f1 = (char*)d_in[2];
    const __nv_bfloat16* wq = (const __nv_bfloat16*)d_in[3];
    const __nv_bfloat16* wk = (const __nv_bfloat16*)d_in[4];
    const __nv_bfloat16* wv = (const __nv_bfloat16*)d_in[5];
    const __nv_bfloat16* wo = (const __nv_bfloat16*)d_in[6];

    static EncodeFn enc = nullptr;
    static int grid = 0;
    static Scratch* scr = nullptr;
    if (!enc) {
        void* fn = nullptr; cudaDriverEntryPointQueryResult qr;
        cudaGetDriverEntryPoint("cuTensorMapEncodeTiled", &fn, cudaEnableDefault, &qr);
        enc = (EncodeFn)fn;
        cudaGetSymbolAddress((void**)&scr, g_scratch);
        int dev = 0, sms = 0;
        cudaGetDevice(&dev);
        cudaDeviceGetAttribute(&sms, cudaDevAttrMultiProcessorCount, dev);
        grid = sms < MAXG ? sms : MAXG;
        cudaFuncSetAttribute(attn_main, cudaFuncAttributeMaxDynamicSharedMemorySize, SMEM_BYTES);
    }
    CUtensorMap m0, m1;
    {
        cuuint64_t dims[5] = {64, W1, 3, 2, W0};
        cuuint64_t str[4] = {2 * C * 2, 128, C * 2, (cuuint64_t)W0 * C * 2};
        cuuint32_t box[5] = {64, TP, 3, 2, 2}, es[5] = {1, 1, 1, 1, 1};
        enc(&m0, CU_TENSOR_MAP_DATA_TYPE_BFLOAT16, 5, f0, dims, str, box, es, CU_TENSOR_MAP_INTERLEAVE_NONE,
            CU_TENSOR_MAP_SWIZZLE_128B, CU_TENSOR_MAP_L2_PROMOTION_NONE, CU_TENSOR_MAP_FLOAT_OOB_FILL_NONE);
    }
    {
        cuuint64_t dims[4] = {64, W1, 3, W1};
        cuuint64_t str[3] = {C * 2, 128, (cuuint64_t)W1 * C * 2};
        cuuint32_t box[4] = {64, TP, 3, 1}, es[4] = {1, 1, 1, 1};
        enc(&m1, CU_TENSOR_MAP_DATA_TYPE_BFLOAT16, 4, f1, dims, str, box, es, CU_TENSOR_MAP_INTERLEAVE_NONE,
            CU_TENSOR_MAP_SWIZZLE_128B, CU_TENSOR_MAP_L2_PROMOTION_NONE, CU_TENSOR_MAP_FLOAT_OOB_FILL_NONE);
    }
    attn_main<<<grid, NTHREADS, SMEM_BYTES, cudaStreamPerThread>>>(f0, f1, q, wq, wk, scr, wv, wo, (__nv_bfloat16*)d_out, m0, m1);
}
```

```cpp
#include <cuda_runtime.h>
#include <cuda_bf16.h>
#include <cuda.h>
#include <stdint.h>

namespace {

constexpr int C = 192;
constexpr int NQ = 16;
constexpr int W0 = 512;
constexpr int W1 = 256;
constexpr int TP = 8;
constexpr int NT = W1 * W1 / TP;
constexpr int STAGE = TP * 5 * C * 2;
#define NS 14
#define D0 1
#define D1 4
#define D2 2
#define NRAMP 3
#define TAILT 1000
#define QSLEEP 700
#define WSL 24
#define MAXT 3000
#define REFT 1800
#define POLLN 1
#define PGAP 110
#define LAZY 12.f
#define NST 2
#define NPRE 2
static_assert(NST > D0, "the first dynamic tile index must not delay the start");
constexpr int NTHREADS = 384;
constexpr int MAXG = 132;
constexpr int NRD = NQ;
constexpr int ACC = NQ * 32;
constexpr int NSRC = 12;
constexpr int SPIN_LIMIT = 1 << 22;
constexpr uint32_t EMPTY = 0xFFFFFFFFu;

constexpr int SM_STAGES = 0;
constexpr int SM_P = NS * STAGE;
constexpr int PBUF = 1088;
constexpr int SM_QK = SM_P + 4 * PBUF;
constexpr int SM_MX = SM_QK + 6144;
constexpr int SM_M = SM_MX + 512;
constexpr int SM_BAR = SM_M + 64;
constexpr int SM_REF = SM_BAR + 16 * NS;
constexpr int SM_FLAG = SM_REF + 8;
constexpr int SM_TOTAL = SM_FLAG + 4 * NS;
constexpr int SMEM_BYTES = SM_TOTAL + 1024;
static_assert(SMEM_BYTES <= 232448, "smem");
constexpr int WROW = 400;
constexpr int RD_W = 0;
constexpr int RD_QN = 2 * C * WROW;
constexpr int RD_KQ = RD_QN + 6144;
constexpr int RD_B = RD_KQ + 7168;
constexpr int RD_BAD = RD_B + 32 * 144 + 256;
constexpr int RD_BAR = RD_BAD + 16;
static_assert(RD_BAR + 64 <= SM_TOTAL, "smem");

struct Scratch {
    uint4 acc[2 * ACC];
    uint4 qk[NSRC * 32];
    unsigned ctr[32];
    unsigned mmax[32];
    unsigned mref[32];
};
__device__ __align__(128) Scratch g_scratch;
#define g_acc (scr->acc)
#define g_qk (scr->qk)
#define g_ctr (scr->ctr)
#define g_mmax (scr->mmax)
#define g_mref (scr->mref)
#define g_ts (scr->ts)
#define g_tr (scr->tr)
#define TR(k, i) do {} while (0)
#define TS(i) do {} while (0)
#define TSD(i, dep) do {} while (0)
#define TSX(i, dep) do {} while (0)
#define TSP(i, dep) do {} while (0)
#define TSE(i) TS(i)
#define CK_(i, dep) do {} while (0)
#define PH(i, dep) do {} while (0)

__device__ __forceinline__ uint32_t s2u(const void* p) { return (uint32_t)__cvta_generic_to_shared(p); }
__device__ __forceinline__ void mbar_init(uint32_t a, int c) { asm volatile("mbarrier.init.shared::cta.b64 [%0], %1;" ::"r"(a), "r"(c) : "memory"); }
__device__ __forceinline__ void mbar_expect(uint32_t a, uint32_t b) { asm volatile("mbarrier.arrive.expect_tx.shared::cta.b64 _, [%0], %1;" ::"r"(a), "r"(b) : "memory"); }
__device__ __forceinline__ void mbar_arrive(uint32_t a) { asm volatile("mbarrier.arrive.shared::cta.b64 _, [%0];" ::"r"(a) : "memory"); }
__device__ __forceinline__ void mbar_wait(uint32_t a, uint32_t ph) {
    uint32_t ok; int it = 0;
    do {
        asm volatile("{.reg .pred p; mbarrier.try_wait.parity.shared::cta.b64 p, [%1], %2; selp.u32 %0,1,0,p;}" : "=r"(ok) : "r"(a), "r"(ph) : "memory");
        if (++it > SPIN_LIMIT) __trap();
    } while (!ok);
}
__device__ __forceinline__ void bar_sync(int id, int n) { asm volatile("bar.sync %0, %1;" ::"r"(id), "r"(n) : "memory"); }
__device__ __forceinline__ bool bar_any(int id, int n, bool c) {
    uint32_t r;
    asm volatile("{.reg .pred p, q; setp.ne.u32 q, %3, 0; bar.red.or.pred p, %1, %2, q; selp.u32 %0, 1, 0, p;}" : "=r"(r) : "r"(id), "r"(n), "r"((uint32_t)c) : "memory");
    return r;
}
__device__ __forceinline__ void bar_arrive(int id, int n) { asm volatile("bar.arrive %0, %1;" ::"r"(id), "r"(n) : "memory"); }
__device__ __forceinline__ void ldsm4(uint32_t* r, uint32_t a) {
    asm volatile("ldmatrix.sync.aligned.m8n8.x4.shared.b16 {%0,%1,%2,%3}, [%4];" : "=r"(r[0]), "=r"(r[1]), "=r"(r[2]), "=r"(r[3]) : "r"(a) : "memory");
}
__device__ __forceinline__ void ldsm4t(uint32_t* r, uint32_t a) {
    asm volatile("ldmatrix.sync.aligned.m8n8.x4.trans.shared.b16 {%0,%1,%2,%3}, [%4];" : "=r"(r[0]), "=r"(r[1]), "=r"(r[2]), "=r"(r[3]) : "r"(a) : "memory");
}
__device__ __forceinline__ void ldsm2t(uint32_t* r, uint32_t a) {
    asm volatile("ldmatrix.sync.aligned.m8n8.x2.trans.shared.b16 {%0,%1}, [%2];" : "=r"(r[0]), "=r"(r[1]) : "r"(a) : "memory");
}
__device__ __forceinline__ void mma(float* d, uint32_t a0, uint32_t a1, uint32_t a2, uint32_t a3, uint32_t b0, uint32_t b1) {
    asm("mma.sync.aligned.m16n8k16.row.col.f32.bf16.bf16.f32 {%0,%1,%2,%3}, {%4,%5,%6,%7}, {%8,%9}, {%0,%1,%2,%3};"
        : "+f"(d[0]), "+f"(d[1]), "+f"(d[2]), "+f"(d[3]) : "r"(a0), "r"(a1), "r"(a2), "r"(a3), "r"(b0), "r"(b1));
}
__device__ __forceinline__ void mmah(float* d, uint32_t a0, uint32_t a1, uint32_t a2, uint32_t a3, uint32_t b0, uint32_t b1) {
    asm("mma.sync.aligned.m16n8k16.row.col.f32.f16.f16.f32 {%0,%1,%2,%3}, {%4,%5,%6,%7}, {%8,%9}, {%0,%1,%2,%3};"
        : "+f"(d[0]), "+f"(d[1]), "+f"(d[2]), "+f"(d[3]) : "r"(a0), "r"(a1), "r"(a2), "r"(a3), "r"(b0), "r"(b1));
}
__device__ __forceinline__ void mma8(float* d, uint32_t a0, uint32_t a1, uint32_t b0) {
    asm("mma.sync.aligned.m16n8k8.row.col.f32.bf16.bf16.f32 {%0,%1,%2,%3}, {%4,%5}, {%6}, {%0,%1,%2,%3};"
        : "+f"(d[0]), "+f"(d[1]), "+f"(d[2]), "+f"(d[3]) : "r"(a0), "r"(a1), "r"(b0));
}
__device__ __forceinline__ uint32_t hadd2(uint32_t a, uint32_t b) {
    uint32_t r; asm("add.rn.bf16x2 %0, %1, %2;" : "=r"(r) : "r"(a), "r"(b)); return r;
}
__device__ __forceinline__ uint32_t pack2(float lo, float hi) {
    uint32_t r; asm("cvt.rn.bf16x2.f32 %0, %1, %2;" : "=r"(r) : "f"(hi), "f"(lo)); return r;
}
__device__ __forceinline__ uint32_t packh(float lo, float hi) {
    uint32_t r; asm("cvt.rn.f16x2.f32 %0, %1, %2;" : "=r"(r) : "f"(hi), "f"(lo)); return r;
}
__device__ __forceinline__ float2 unpackh(uint32_t v) {
    float2 r; asm("{.reg .b16 l, h; mov.b32 {l, h}, %2; cvt.f32.f16 %0, l; cvt.f32.f16 %1, h;}" : "=f"(r.x), "=f"(r.y) : "r"(v)); return r;
}
__device__ __forceinline__ float bflo(uint32_t v) { return __uint_as_float(v << 16); }
__device__ __forceinline__ float bfhi(uint32_t v) { return __uint_as_float(v & 0xffff0000u); }
__device__ __forceinline__ float ex2(float x) { float r; asm("ex2.approx.ftz.f32 %0, %1;" : "=f"(r) : "f"(x)); return r; }
__device__ __forceinline__ void sts128(uint32_t a, uint32_t x, uint32_t y, uint32_t z, uint32_t w) {
    asm volatile("st.shared.v4.b32 [%0], {%1,%2,%3,%4};" ::"r"(a), "r"(x), "r"(y), "r"(z), "r"(w) : "memory");
}
__device__ __forceinline__ void sts64(uint32_t a, uint32_t x, uint32_t y) {
    asm volatile("st.shared.v2.b32 [%0], {%1,%2};" ::"r"(a), "r"(x), "r"(y) : "memory");
}
__device__ __forceinline__ void sts32(uint32_t a, uint32_t x) { asm volatile("st.shared.b32 [%0], %1;" ::"r"(a), "r"(x) : "memory"); }
__device__ __forceinline__ uint4 lds128(uint32_t a) {
    uint4 v; asm volatile("ld.shared.v4.b32 {%0,%1,%2,%3}, [%4];" : "=r"(v.x), "=r"(v.y), "=r"(v.z), "=r"(v.w) : "r"(a) : "memory"); return v;
}
__device__ __forceinline__ uint32_t lds32(uint32_t a) { uint32_t v; asm volatile("ld.shared.b32 %0, [%1];" : "=r"(v) : "r"(a) : "memory"); return v; }
__device__ __forceinline__ int grab_tile(unsigned* ctr) {
    int v; asm volatile("atom.relaxed.gpu.global.inc.u32 %0, [%1], 0x7fffffff;" : "=r"(v) : "l"(ctr) : "memory"); return v;
}
__device__ __forceinline__ uint32_t opaque(uint32_t v) { uint32_t r; asm volatile("mov.b32 %0, %1;" : "=r"(r) : "r"(v)); return r; }
__device__ __forceinline__ float rsq(float x) { float r; asm("rsqrt.approx.ftz.f32 %0, %1;" : "=f"(r) : "f"(x)); return r; }
__device__ __forceinline__ float rcp(float x) { float r; asm("rcp.approx.ftz.f32 %0, %1;" : "=f"(r) : "f"(x)); return r; }
__device__ __forceinline__ float lg2(float x) { float r; asm("lg2.approx.ftz.f32 %0, %1;" : "=f"(r) : "f"(x)); return r; }
__device__ __forceinline__ float f(uint32_t v) { return __uint_as_float(v); }
__device__ __forceinline__ uint32_t u(float v) { return __float_as_uint(v); }

constexpr uint32_t ONES = 0x3F803F80u;
constexpr float QSCALE = 0.07216878364870322f * 1.4426950408889634f;

__device__ __forceinline__ void issue_tile(const CUtensorMap* m0, const CUtensorMap* m1, uint32_t sb, int s, int tl, uint64_t pol) {
    const uint32_t full = sb + SM_BAR + s * 8, dst = sb + SM_STAGES + s * STAGE;
    const int par = tl * TP, y = par >> 8, x = par & 255;
    mbar_expect(full, STAGE);
    asm volatile("cp.async.bulk.tensor.5d.shared::cluster.global.mbarrier::complete_tx::bytes.L2::cache_hint [%0], [%1, {%3,%4,%3,%3,%5}], [%2], %6;"
                 ::"r"(dst), "l"(m0), "r"(full), "r"(0), "r"(x), "r"(2 * y), "l"(pol) : "memory");
    asm volatile("cp.async.bulk.tensor.4d.shared::cluster.global.mbarrier::complete_tx::bytes.L2::cache_hint [%0], [%1, {%3,%4,%3,%5}], [%2], %6;"
                 ::"r"(dst + TP * 4 * C * 2), "l"(m1), "r"(full), "r"(0), "r"(x), "r"(y), "l"(pol) : "memory");
}

__device__ __forceinline__ uint4 ldg_relaxed(const uint4* p) {
    uint4 v; asm volatile("ld.relaxed.gpu.global.v4.u32 {%0,%1,%2,%3}, [%4];" : "=r"(v.x), "=r"(v.y), "=r"(v.z), "=r"(v.w) : "l"(p) : "memory"); return v;
}
__device__ __forceinline__ uint32_t ldg_relaxed32(const void* p) {
    uint32_t v; asm volatile("ld.relaxed.gpu.global.u32 %0, [%1];" : "=r"(v) : "l"(p) : "memory"); return v;
}
__device__ __forceinline__ void stg_relaxed(uint4* p, uint32_t x, uint32_t y, uint32_t z, uint32_t w) {
    asm volatile("st.relaxed.gpu.global.v4.u32 [%0], {%1,%2,%3,%4};" ::"l"(p), "r"(x), "r"(y), "r"(z), "r"(w) : "memory");
}
__device__ __forceinline__ void stg_relaxed32(void* p, uint32_t x) { asm volatile("st.relaxed.gpu.global.u32 [%0], %1;" ::"l"(p), "r"(x) : "memory"); }
__device__ __forceinline__ bool has(const uint4& v, uint32_t m) { return v.x == m || v.y == m || v.z == m || v.w == m; }
__device__ __forceinline__ uint32_t hadd2v(uint32_t a, uint32_t b) {
    uint32_t r; asm volatile("add.rn.bf16x2 %0, %1, %2;" : "=r"(r) : "r"(a), "r"(b)); return r;
}

__device__ __forceinline__ void red8h(uint4* p, uint32_t x, uint32_t y, uint32_t z, uint32_t w) {
    asm volatile("red.relaxed.gpu.global.add.noftz.v4.f16x2 [%0], {%1,%2,%3,%4};" ::"l"(p), "r"(x), "r"(y), "r"(z), "r"(w) : "memory");
}
__device__ __forceinline__ uint4 lds128v(uint32_t a) {
    uint4 v; asm volatile("ld.volatile.shared.v4.b32 {%0,%1,%2,%3}, [%4];" : "=r"(v.x), "=r"(v.y), "=r"(v.z), "=r"(v.w) : "r"(a) : "memory"); return v;
}
__device__ __forceinline__ uint32_t brow(int r) { return RD_B + r * 144 + (r >> 3) * 64; }

enum { B_QK = 1, B_QN = 2, B_GRP = 3  , B_Q = 5, B_MERGE = 6, B_ALL = 7, B_MAX = 8   };

__device__ __noinline__ void slow_row(const char* __restrict__ f0, const char* __restrict__ f1, const __nv_bfloat16* __restrict__ q,
                                      const __nv_bfloat16* __restrict__ wq, const __nv_bfloat16* __restrict__ wk, const uint32_t sb, const int b)
{
    const int warp = threadIdx.x >> 5, lane = threadIdx.x & 31;
    const int g = lane >> 2, t = lane & 3;
    const uint32_t bw = sb + brow(8 * (b & 3) + t) + g * 16;
    float* const sm = reinterpret_cast<float*>(__cvta_shared_to_generic(sb + RD_W));
    const int c = threadIdx.x;
    bar_sync(B_ALL, 384);
    if (c < C) sm[c] = __bfloat162float(q[b * C + c]);
    bar_sync(B_ALL, 384);
    float mu = 0.f, var = 0.f, s = 0.f;
#pragma unroll 1
    for (int i = 0; i < C; i++) mu += sm[i];
    mu *= 1.f / C;
#pragma unroll 1
    for (int i = 0; i < C; i++) var += (sm[i] - mu) * (sm[i] - mu);
    if (c < C) {
#pragma unroll 1
        for (int i = 0; i < C; i++) s = fmaf(sm[i] - mu, __bfloat162float(wq[i * C + c]), s);
        sm[C + c] = s * rsq(var * (1.f / C) + 1e-5f);
    }
    bar_sync(B_ALL, 384);
    if (c < C) {
        s = 0.f;
#pragma unroll 1
        for (int i = 0; i < C; i++) s = fmaf(sm[C + i], __bfloat162float(wk[c * C + i]), s);
        sm[2 * C + c] = s * QSCALE;
    }
    bar_sync(B_ALL, 384);
    float k[6], a[6], m = -INFINITY, l = 0.f;
#pragma unroll
    for (int i = 0; i < 6; i++) { k[i] = sm[2 * C + 64 * (i >> 1) + 2 * lane + (i & 1)]; a[i] = 0.f; }
#pragma unroll 1
    for (int px = warp; px < W0 * W0; px += 12) {
        const uint32_t* p0 = reinterpret_cast<const uint32_t*>(f0 + (size_t)px * (C * 2)) + lane;
        const uint32_t* p1 = reinterpret_cast<const uint32_t*>(f1 + (size_t)((px >> 10) * W1 + ((px & (W0 - 1)) >> 1)) * (C * 2)) + lane;
        float x[6], s1 = 0.f, s2 = 0.f, d = 0.f;
#pragma unroll
        for (int i = 0; i < 3; i++) { const uint32_t v = hadd2(__ldg(p0 + 32 * i), __ldg(p1 + 32 * i)); x[2 * i] = bflo(v); x[2 * i + 1] = bfhi(v); s1 += x[2 * i] + x[2 * i + 1]; }
#pragma unroll
        for (int o = 1; o < 32; o <<= 1) s1 += __shfl_xor_sync(~0u, s1, o);
#pragma unroll
        for (int i = 0; i < 6; i++) { x[i] -= s1 * (1.f / C); s2 = fmaf(x[i], x[i], s2); d = fmaf(x[i], k[i], d); }
#pragma unroll
        for (int o = 1; o < 32; o <<= 1) { s2 += __shfl_xor_sync(~0u, s2, o); d += __shfl_xor_sync(~0u, d, o); }
        const float rs = rsq(s2 * (1.f / C) + 1e-5f), nm = fmaxf(m, d * rs), al = ex2(m - nm), p = ex2(d * rs - nm);
        m = nm; l = fmaf(l, al, p);
#pragma unroll
        for (int i = 0; i < 6; i++) a[i] = fmaf(a[i], al, x[i] * (p * rs));
    }
    if (lane == 0) sm[3 * C + warp] = m;
    bar_sync(B_ALL, 384);
    float M = m;
#pragma unroll 1
    for (int w = 0; w < 12; w++) M = fmaxf(M, sm[3 * C + w]);
    const float al = ex2(m - M);
#pragma unroll
    for (int i = 0; i < 6; i++) sm[4 * C + (warp * 7 + i) * 32 + lane] = a[i] * al;
    sm[4 * C + (warp * 7 + 6) * 32 + lane] = l * al;
    bar_sync(B_ALL, 384);
    if (warp == 8) {
        float x[7];
#pragma unroll
        for (int i = 0; i < 7; i++) { x[i] = 0.f; for (int w = 0; w < 12; w++) x[i] += sm[4 * C + (w * 7 + i) * 32 + lane]; }
        uint32_t hi[3], lo[3];
        const float r = 1.f / x[6];
#pragma unroll
        for (int i = 0; i < 3; i++) {
            hi[i] = packh(x[2 * i] * r, x[2 * i + 1] * r);
            const float2 h = unpackh(hi[i]);
            lo[i] = packh(fmaf(x[2 * i], r, -h.x), fmaf(x[2 * i + 1], r, -h.y));
        }
        sts128(bw, hi[0], hi[1], hi[2], lane ? 0u : 0x3C000000u);
        sts128(bw + 4 * 144, lo[0], lo[1], lo[2], 0);
    }
    bar_sync(B_ALL, 384);
}

__device__ __forceinline__ void reducer(const char* __restrict__ f0, const char* __restrict__ f1, const __nv_bfloat16* __restrict__ q, const __nv_bfloat16* __restrict__ wq, const __nv_bfloat16* __restrict__ wk,
                                        Scratch* scr, const __nv_bfloat16* __restrict__ wv, const __nv_bfloat16* __restrict__ wo,
                                        __nv_bfloat16* __restrict__ out, const uint32_t sb, const int GS)
{
    const int warp = threadIdx.x >> 5, lane = threadIdx.x & 31, b = blockIdx.x;
    const int g = lane >> 2, t = lane & 3;
    if (threadIdx.x == 256) TS(0);
    if (b < NSRC && warp < 8) {
        const uint32_t wqs = sb + RD_W, wbar = sb + RD_BAR;
        const int hr = lane >> 4, qt = (lane >> 2) & 3, sub = lane & 3;
        const uint32_t* qp = reinterpret_cast<const uint32_t*>(q + (warp + 8 * hr) * C + 48 * qt + 6 * sub);
        uint32_t qw[6];
#pragma unroll
        for (int j = 0; j < 3; j++) { qw[j] = __ldg(qp + j); qw[3 + j] = __ldg(qp + 12 + j); }
        if (lane == 0) { mbar_init(wbar + warp * 8, 1); asm volatile("fence.mbarrier_init.release.cluster;" ::: "memory"); mbar_expect(wbar + warp * 8, 9216);
            asm volatile("cp.async.bulk.shared::cluster.global.mbarrier::complete_tx::bytes [%0], [%1], 9216, [%2];"
                         ::"r"(wqs + warp * 9232), "l"(wq + 24 * warp * C), "r"(wbar + warp * 8) : "memory");
        }
        __syncwarp();
        if (threadIdx.x == 0) TSP(2, 0);
        float e[12];
#pragma unroll
        for (int j = 0; j < 6; j++) { e[2 * j] = bflo(qw[j]); e[2 * j + 1] = bfhi(qw[j]); }
        float sm = ((e[0] + e[1]) + (e[2] + e[3])) + ((e[4] + e[5]) + (e[6] + e[7])) + ((e[8] + e[9]) + (e[10] + e[11]));
#pragma unroll
        for (int o = 1; o < 16; o <<= 1) sm += __shfl_xor_sync(~0u, sm, o);
        if (threadIdx.x == 0) TSP(5, u(sm));
        float v0 = 0.f, v1 = 0.f;
#pragma unroll
        for (int j = 0; j < 12; j++) e[j] -= sm * (1.f / C);
#pragma unroll
        for (int j = 0; j < 6; j++) { v0 = fmaf(e[j], e[j], v0); v1 = fmaf(e[6 + j], e[6 + j], v1); }
        v0 += v1;
#pragma unroll
        for (int o = 1; o < 16; o <<= 1) v0 += __shfl_xor_sync(~0u, v0, o);
        const float rq = rsq(v0 * (1.f / C) + 1e-5f);
#pragma unroll
        for (int j = 0; j < 6; j++)
            sts32(sb + RD_QN + (3 * sub + (j >> 1)) * 512 + (4 * warp + qt) * 16 + (2 * (j & 1) + hr) * 4, pack2(e[j] * rq, e[6 + j] * rq));
        if (threadIdx.x == 0) TSP(8, 0);
        uint32_t wkf[2][3];
#pragma unroll
        for (int i = 0; i < 2; i++)
#pragma unroll
            for (int j = 0; j < 3; j++) wkf[i][j] = __ldg(reinterpret_cast<const uint32_t*>(wk + (16 * b + 8 * i + g) * C + 24 * warp + 8 * j + 2 * t));
        bar_sync(B_QN, 256);
        float acc[2][3][4];
#pragma unroll
        for (int i = 0; i < 3; i++)
#pragma unroll
            for (int e = 0; e < 4; e++) acc[0][i][e] = acc[1][i][e] = 0.f;
        const uint32_t ba = wqs + (lane & 7) * 9232 + (lane >> 3) * 384 + 48 * warp;
        uint4 a[12];
#pragma unroll
        for (int kk = 0; kk < 12; kk++) a[kk] = lds128(sb + RD_QN + kk * 512 + lane * 16);
        mbar_wait(wbar + (lane & 7) * 8, 0);
        __syncwarp();
        if (threadIdx.x == 0) TSP(4, 0);
#pragma unroll
        for (int kp = 0; kp < 6; kp++)
#pragma unroll
            for (int i = 0; i < 3; i++) {
                uint32_t bb[4];
                ldsm4t(bb, ba + kp * 1536 + i * 16);
                mma(acc[0][i], a[2 * kp].x, a[2 * kp].y, a[2 * kp].z, a[2 * kp].w, bb[0], bb[1]);
                mma(acc[1][i], a[2 * kp + 1].x, a[2 * kp + 1].y, a[2 * kp + 1].z, a[2 * kp + 1].w, bb[2], bb[3]);
            }
        if (threadIdx.x == 0) TSP(7, u(acc[1][2][3]));
        float kq[2][4] = {{0.f, 0.f, 0.f, 0.f}, {0.f, 0.f, 0.f, 0.f}};
#pragma unroll
        for (int j = 0; j < 3; j++) {
            const uint32_t a0 = pack2(acc[0][j][0] + acc[1][j][0], acc[0][j][1] + acc[1][j][1]), a1 = pack2(acc[0][j][2] + acc[1][j][2], acc[0][j][3] + acc[1][j][3]);
            mma8(kq[0], a0, a1, wkf[0][j]);
            mma8(kq[1], a0, a1, wkf[1][j]);
        }
        if (warp < 7) {
            sts128(sb + RD_KQ + warp * 1024 + lane * 16, u(kq[0][0]), u(kq[0][1]), u(kq[0][2]), u(kq[0][3]));
            sts128(sb + RD_KQ + warp * 1024 + 512 + lane * 16, u(kq[1][0]), u(kq[1][1]), u(kq[1][2]), u(kq[1][3]));
            bar_arrive(B_Q, 256);
        } else {
            bar_sync(B_Q, 256);
#pragma unroll
            for (int w = 0; w < 7; w++)
#pragma unroll
                for (int i = 0; i < 2; i++) {
                    const uint4 o = lds128(sb + RD_KQ + w * 1024 + i * 512 + lane * 16);
                    kq[i][0] += f(o.x); kq[i][1] += f(o.y); kq[i][2] += f(o.z); kq[i][3] += f(o.w);
                }
            stg_relaxed(g_qk + b * 32 + lane, ~pack2(kq[0][0] * QSCALE, kq[0][1] * QSCALE), ~pack2(kq[0][2] * QSCALE, kq[0][3] * QSCALE),
                        ~pack2(kq[1][0] * QSCALE, kq[1][1] * QSCALE), ~pack2(kq[1][2] * QSCALE, kq[1][3] * QSCALE));
            if (lane == 0) TS(10);
        }
    } else if (b >= NSRC) {
        if (b == NSRC && warp == 0) stg_relaxed32(g_mmax + lane, 0);
        __nanosleep(2500);
    }
    bar_sync(B_ALL, 384);

#pragma unroll 1
    for (int r = 0; r < 3; r++) {
        uint4 v[8];
#pragma unroll
        for (int k = 0; k < 8; k++) {
            const int idx = (8 * r + k) * 384 + threadIdx.x;
            v[k] = __ldg(reinterpret_cast<const uint4*>(idx < 4608 ? wv : wo - C * C) + idx);
        }
#pragma unroll
        for (int k = 0; k < 8; k++) {
            const int idx = (8 * r + k) * 384 + threadIdx.x, row = idx / 24;
            sts128(sb + RD_W + row * WROW + (idx - 24 * row) * 16, v[k].x, v[k].y, v[k].z, v[k].w);
        }
    }
    if (threadIdx.x < 256) {
        sts128(sb + brow(threadIdx.x >> 3) + (threadIdx.x & 7) * 16, EMPTY, EMPTY, EMPTY, EMPTY);
        stg_relaxed(g_acc + (threadIdx.x >> 7) * ACC + (b >> 2) * 128 + (threadIdx.x & 127), 0, 0, 0, 0);
        __threadfence();
    }
    if (threadIdx.x == 0) sts128(sb + RD_BAD, 0, 0, 0, 0);
    bar_sync(B_ALL, 384);
    uint32_t wa[12][4];
    float ws0 = 0.f, ws1 = 0.f, qv0 = 0.f, qv1 = 0.f;
    __nv_bfloat16* op = out;
    if (warp < 3) {
        const int col = 48 * (b & 3) + 16 * warp;
        float d[24][4];
#pragma unroll
        for (int i = 0; i < 24; i++) d[i][0] = d[i][1] = d[i][2] = d[i][3] = 0.f;
        const int mi = lane >> 3, r = lane & 7;
        const uint32_t aa = sb + RD_W + (C + (mi >> 1) * 8 + r) * WROW + (col + (mi & 1) * 8) * 2;
        const uint32_t ba = sb + RD_W + ((mi >> 1) * 8 + r) * WROW + (mi & 1) * 16;
#pragma unroll 1
        for (int kk = 0; kk < 12; kk++) {
            uint32_t a[4];
            ldsm4t(a, aa + kk * 16 * WROW);
#pragma unroll
            for (int i = 0; i < 12; i++) {
                uint32_t bb[4];
                ldsm4(bb, ba + i * 16 * WROW + kk * 32);
                mma(d[2 * i], a[0], a[1], a[2], a[3], bb[0], bb[1]);
                mma(d[2 * i + 1], a[0], a[1], a[2], a[3], bb[2], bb[3]);
            }
        }
        float c0 = 0.f, c1 = 0.f, m0 = 0.f, m1 = 0.f;
#pragma unroll
        for (int i = 0; i < 24; i++) { c0 += d[i][0] + d[i][1]; c1 += d[i][2] + d[i][3]; }
        c0 += __shfl_xor_sync(~0u, c0, 1); c1 += __shfl_xor_sync(~0u, c1, 1);
        c0 += __shfl_xor_sync(~0u, c0, 2); c1 += __shfl_xor_sync(~0u, c1, 2);
        c0 *= 1.f / C; c1 *= 1.f / C;
#pragma unroll
        for (int i = 0; i < 24; i++) {
            d[i][0] -= c0; d[i][1] -= c0; d[i][2] -= c1; d[i][3] -= c1;
            m0 = fmaxf(m0, fmaxf(fabsf(d[i][0]), fabsf(d[i][1]))); m1 = fmaxf(m1, fmaxf(fabsf(d[i][2]), fabsf(d[i][3])));
        }
        m0 = fmaxf(m0, __shfl_xor_sync(~0u, m0, 1)); m1 = fmaxf(m1, __shfl_xor_sync(~0u, m1, 1));
        m0 = fmaxf(m0, __shfl_xor_sync(~0u, m0, 2)); m1 = fmaxf(m1, __shfl_xor_sync(~0u, m1, 2));
        const uint32_t e0 = min(max(u(m0) >> 23, 12u), 254u), e1 = min(max(u(m1) >> 23, 12u), 254u);
        const float s0 = f((265u - e0) << 23), s1 = f((265u - e1) << 23);
        ws0 = f((e0 - 11u) << 23); ws1 = f((e1 - 11u) << 23);
#pragma unroll
        for (int i = 0; i < 24; i++) {
            const int kk = i < 16 ? i & 7 : i >> 1, hf = i < 16 ? i >> 3 : i & 1;
            wa[kk][2 * hf] = packh(d[i][0] * s0, d[i][1] * s0);
            wa[kk][2 * hf + 1] = packh(d[i][2] * s1, d[i][3] * s1);
        }
        const int o = ((b & 12) + t) * C + col + g;
        qv0 = __bfloat162float(q[o]); qv1 = __bfloat162float(q[o + 8]);
        op = out + o;
        asm volatile("" : "+l"(op));
        if (threadIdx.x == 0) TSE(6);
    } else if (warp == 3) {
        if (lane == 0) {
            uint32_t m;
            for (int it = 0;; it++) {
                const int left = NT - 2 * NST * GS - (int)ldg_relaxed32(g_ctr);
                m = ldg_relaxed32(g_mmax + b);
                if (left <= REFT && m) break;
                if (left <= 0) { m = 0x80000000u; break; }
                if (it > SPIN_LIMIT) __trap();
                __nanosleep(300);
            }
            asm volatile("st.release.gpu.global.u32 [%0], %1;" ::"l"(g_mref + b), "r"(~u(f(m >> 31 ? m ^ 0x80000000u : ~m) + 8.f)) : "memory");
            TSE(7);
        }
        __syncwarp();
    } else {
        const int pr = warp & 1;
        const uint4* const pa = g_acc + ((b >> 2) * 2 + pr) * 64 + lane;
        const uint32_t bw = opaque(sb + brow(16 * pr + 8 * ((lane >> 2) & 1) + t) + (lane >> 3) * 16);
        const uint32_t n0 = packh((float)((GS + 1) >> 1), 0.f), n1 = packh((float)(GS >> 1), 0.f), nstart = packh((float)POLLN, 0.f);
        for (int it = 0; (ldg_relaxed32(reinterpret_cast<const uint32_t*>(pa - lane) + 3) & 0xFFFFu) < nstart; it++)
            if (it > SPIN_LIMIT) __trap();
        for (const unsigned c = clock(); clock() - c < ((warp - 4) >> 1) * PGAP;) {}
        uint4 a0, a1, b0, b1;
        for (int it = 0;; it++) {
            a0 = ldg_relaxed(pa); a1 = ldg_relaxed(pa + ACC); b0 = ldg_relaxed(pa + 32); b1 = ldg_relaxed(pa + ACC + 32);
            if (__all_sync(~0u, (((a0.w ^ n0) | (b0.w ^ n0) | (a1.w ^ n1) | (b1.w ^ n1)) & 0xFFFFu) == 0)) break;
            if (it > SPIN_LIMIT) __trap();
        }
        sts128(bw, a0.x, a0.y, a0.z, a0.w);
        sts128(bw + 4 * 144, a1.x, a1.y, a1.z, a1.w);
        sts128(bw + 64, b0.x, b0.y, b0.z, b0.w);
        sts128(bw + 4 * 144 + 64, b1.x, b1.y, b1.z, b1.w);
        if (warp == 4) {
            if (b < NSRC) g_qk[b * 32 + lane] = make_uint4(0, 0, 0, 0);
            if (lane == 0) { g_mref[b] = 0; if (b == NSRC) g_ctr[0] = 0; }
        }
    }
    const uint32_t br = opaque(sb + brow(lane));
#pragma unroll 1
    for (uint32_t pass = 0;; pass = 1) {
        if (warp < 3) {
            uint4 x[8];
            float o[4][4];
            for (int it = 0;; it++) {
                for (;; it++) {
                    x[7] = lds128v(br + 7 * 16);
                    if (!__any_sync(~0u, x[7].w & 0x8000u)) break;
                    if (it > 64 * SPIN_LIMIT) __trap();
                }
                if (threadIdx.x == 0) TSX(8, 0);
#pragma unroll
                for (int j = 0; j < 7; j++) x[j] = lds128v(br + j * 16);
#pragma unroll
                for (int j = 0; j < 4; j++) o[j][0] = o[j][1] = o[j][2] = o[j][3] = 0.f;
#pragma unroll
                for (int i = 0; i < 4; i++) {
                    mmah(o[3], 0x3C000000u, 0x3C000000u, 0x3C000000u, 0x3C000000u, x[2 * i].w, x[2 * i + 1].w);
                    mmah(o[0], wa[2 * i][0], wa[2 * i][1], wa[2 * i][2], wa[2 * i][3], x[2 * i].x, x[2 * i].y);
                    mmah(o[1], wa[2 * i + 1][0], wa[2 * i + 1][1], wa[2 * i + 1][2], wa[2 * i + 1][3], x[2 * i + 1].x, x[2 * i + 1].y);
                    mmah(o[2], wa[8 + i][0], wa[8 + i][1], wa[8 + i][2], wa[8 + i][3], x[2 * i].z, x[2 * i + 1].z);
                }
                if (!__any_sync(~0u, ((x[0].w | x[1].w | x[2].w) | (x[3].w | x[4].w | x[5].w) | x[6].w) & 0x8000u)) break;
            }
            const float L = o[3][0] + o[3][1], r = rcp(L);
            const float y0 = fmaf(((o[0][0] + o[0][1]) + (o[1][0] + o[1][1])) + (o[2][0] + o[2][1]), r * ws0, qv0);
            const float y1 = fmaf(((o[0][2] + o[0][3]) + (o[1][2] + o[1][3])) + (o[2][2] + o[2][3]), r * ws1, qv1);
            op[0] = __float2bfloat16(y0);
            op[8] = __float2bfloat16(y1);
            if (threadIdx.x == 0) TSD(11, u(y0));
            if (!(L >= 0.001953125f && L <= 2048.f && fabsf(y0) + fabsf(y1) < INFINITY)) sts32(sb + RD_BAD + t * 4, 1);
        }
        bar_sync(B_ALL, 384);
        if (pass) break;
        const uint4 bad = lds128(sb + RD_BAD);
        if (__builtin_expect((bad.x | bad.y | bad.z | bad.w) == 0, 1)) break;
        const uint32_t keep = sb + RD_W + 32768 + warp * 6144 + lane * 16;
        if (warp < 3)
#pragma unroll
            for (int kk = 0; kk < 12; kk++) sts128(keep + kk * 512, wa[kk][0], wa[kk][1], wa[kk][2], wa[kk][3]);
#pragma unroll 1
        for (int r = 0; r < 4; r++)
            if (lds32(sb + RD_BAD + r * 4)) slow_row(f0, f1, q, wq, wk, sb, (b & 12) + r);
        if (warp < 3)
#pragma unroll
            for (int kk = 0; kk < 12; kk++) {
                const uint4 v = lds128(keep + kk * 512);
                wa[kk][0] = v.x; wa[kk][1] = v.y; wa[kk][2] = v.z; wa[kk][3] = v.w;
            }
    }
}

__global__ void __launch_bounds__(NTHREADS, 1)
attn_main(const char* __restrict__ f0, const char* __restrict__ f1,
          const __nv_bfloat16* __restrict__ q, const __nv_bfloat16* __restrict__ wq, const __nv_bfloat16* __restrict__ wk, Scratch* scr,
          const __nv_bfloat16* __restrict__ wv, const __nv_bfloat16* __restrict__ wo, __nv_bfloat16* __restrict__ out,
          const __grid_constant__ CUtensorMap m0, const __grid_constant__ CUtensorMap m1)
{
    extern __shared__ char smem_raw[];
    const uint32_t sb = (s2u(smem_raw) + 1023u) & ~1023u;
    const int G = gridDim.x - NRD;
    if (blockIdx.x < NRD) { reducer(f0, f1, q, wq, wk, scr, wv, wo, out, sb, G); return; }
    const int b = blockIdx.x - NRD;
    const int warp = __shfl_sync(~0u, threadIdx.x >> 5, 0), lane = threadIdx.x & 31;
    const int g = lane >> 2, t = lane & 3;

    if (warp >= 8) {
        if (warp < 10) {
            const int p = warp - 8;
            if (lane == 0) {
                if (p == 0) TS(0);
                asm volatile("prefetch.tensormap [%0];" ::"l"(p ? &m1 : &m0) : "memory");
            }
            if (lane < NS / 2) {
                const int s = 2 * lane + p;
                mbar_init(sb + SM_BAR + s * 8, 1); mbar_init(sb + SM_BAR + (NS + s) * 8, 1);
            }
            if (p == 0 && lane == 31) mbar_init(sb + SM_REF, 1);
            asm volatile("fence.mbarrier_init.release.cluster;" ::: "memory");
            __syncwarp();
            bar_arrive(B_QK, 384);
            if (lane == 0) {
                uint64_t pol; asm volatile("createpolicy.fractional.L2::evict_first.b64 %0, 1.0;" : "=l"(pol));
                int s = p; uint32_t ph = 1;
                int sa = p, na = 0; uint32_t pa = 0;
                int tl = b + p * G;
                bool late = false;
                for (int n = 0;; n++) {
                    int nxt = tl + 2 * G;
                    if (n >= NST - 1) nxt = grab_tile(g_ctr) + 2 * NST * G;
                    const int d = n < NRAMP ? D0 : (tl >= NT - TAILT ? D2 : D1);
                    while (n - na >= d) {
                        mbar_wait(sb + SM_BAR + sa * 8, pa);
                        if (na < NS / 2) TR(1, 2 * na + p);
                        na++; sa += 2;
                        if (sa >= NS) { sa -= NS; pa ^= 1; }
                    }
                    mbar_wait(sb + SM_BAR + (NS + s) * 8, ph);
                    const bool last = nxt >= NT;
                    uint32_t flag = last;
                    if (!late && nxt >= NT - MAXT - 16 * b) { late = true; flag |= 2; }
                    if (last) mbar_wait(sb + SM_REF, 0);
                    sts32(sb + SM_FLAG + s * 4, flag);
                    issue_tile(&m0, &m1, sb, s, tl, pol);
                    TR(0, 2 * n + p);
                    if (last) break;
                    s += 2;
                    if (s >= NS) { s -= NS; ph ^= 1; }
                    tl = nxt;
                }
                if (p) TSE(5);
            }
            return;
        }
        const int h = threadIdx.x - 320;
        uint4 v[6];
        for (int it = 0;; it++) {
            bool miss = false;
#pragma unroll
            for (int k = 0; k < 6; k++) v[k] = ldg_relaxed(g_qk + k * 64 + h);
#pragma unroll
            for (int k = 0; k < 6; k++) miss |= has(v[k], 0);
            if (!miss) break;
            if (it > SPIN_LIMIT) __trap();
            if (it == 0) __nanosleep(QSLEEP);
        }
#pragma unroll
        for (int k = 0; k < 6; k++) sts128(sb + SM_QK + (k * 64 + h) * 16, ~v[k].x, ~v[k].y, ~v[k].z, ~v[k].w);
        __syncwarp();
        bar_sync(B_QK, 384);
        if (warp == 11) return;
        uint32_t r = 1;
        for (int it = 0;; it++) {
            __nanosleep(500);
            if (lane < NQ) asm volatile("ld.acquire.gpu.global.u32 %0, [%1];" : "=r"(r) : "l"(g_mref + lane) : "memory");
            if (__all_sync(~0u, r != 0)) break;
            if (it > SPIN_LIMIT) __trap();
        }
        if (lane < NQ) sts32(sb + SM_M + lane * 4, ~r);
        __syncwarp();
        if (lane == 0) { mbar_arrive(sb + SM_REF); TSE(7); }
        return;
    }

    const int grp = warp >> 2, cw = warp & 3;
    if (lane == 0) {
        const char* a; int sz;
        if (warp >= 6) {
            sz = C * C * 2 / WSL; a = (const char*)(warp == 6 ? wq : wk) + (b % WSL) * sz;
        } else {
            const int tl = b + (warp / 3) * G, which = warp % 3;
            const int par = tl * TP, y = par >> 8, x = par & 255;
            a = which < 2 ? f0 + ((size_t)(2 * y + which) * W0 + 2 * x) * (C * 2) : f1 + ((size_t)y * W1 + x) * (C * 2);
            sz = which < 2 ? TP * 2 * C * 2 : TP * C * 2;
        }
        if (warp >= 6 || warp < 3 * NPRE) asm volatile("cp.async.bulk.prefetch.L2.global [%0], %1;" ::"l"(a), "r"(sz) : "memory");
    }

    const int xp = lane & 7, mi = lane >> 3;
    const uint32_t offS1 = opaque(12288 + xp * 128 + ((mi ^ xp) << 4)), offS1x = opaque(offS1 ^ 64);
    const uint32_t offS0 = opaque(offS1 - 12288 + cw * 3072), offS0x = opaque(offS0 ^ 64);
    const uint32_t offT = opaque(mi * 3072 + xp * 128 + (((cw + 4 * grp) ^ xp) << 4)), offTx = opaque(offT ^ 64);
    const uint32_t offU = opaque(12288 + (mi % 3) * 1024 + xp * 128 + (((cw + 4 * (grp ^ (mi / 3))) ^ xp) << 4));
    const uint32_t offV = opaque(12288 + (1 + (mi & 1)) * 1024 + xp * 128 + (((cw + 4 * (grp ^ 1)) ^ xp) << 4));
    const int shl = opaque(9 * t), shl4 = opaque(9 * t + 4);
    const uint32_t pw = opaque((cw >> 1) * 512 + lane * 16 + (cw & 1) * 8), muw = opaque(1024 + t * 16 + cw * 4);
    const uint32_t prd = opaque(lane * 16), mur = opaque(1024 + t * 16);
    uint32_t pb0 = sb + SM_P + grp * 2 * PBUF;
    const uint32_t pbx = pb0 ^ (pb0 + PBUF);
    const bool odd = g & 1;
    const int barid = B_GRP + grp;
    const bool elected = cw == 3 && lane == 0;

    uint32_t qa[48];
    float r_lo, r_hi;
    bar_sync(B_QK, 384);
    {
        float rr[2][4] = {{0.f, 0.f, 0.f, 0.f}, {0.f, 0.f, 0.f, 0.f}};
#pragma unroll
        for (int kk = 0; kk < 12; kk++) {
            const uint4 v = lds128(sb + SM_QK + kk * 512 + lane * 16);
            qa[4 * kk] = v.x; qa[4 * kk + 1] = v.y; qa[4 * kk + 2] = v.z; qa[4 * kk + 3] = v.w;
            mma(rr[kk & 1], v.x, v.y, v.z, v.w, ONES, ONES);
        }
        r_lo = rr[0][0] + rr[1][0]; r_hi = rr[0][2] + rr[1][2];
    }
    if (threadIdx.x == 0) TS(1);

    float acc[6][4];
#pragma unroll
    for (int i = 0; i < 6; i++) acc[i][0] = acc[i][1] = acc[i][2] = acc[i][3] = 0.f;
    float m_lo = -INFINITY, m_hi = -INFINITY, l_lo = 0.f, l_hi = 0.f;
    float cm[4] = {0.f, 0.f, 0.f, 0.f};
    uint32_t xt[6][4]; uint4 pa, pb, mv;
    int s = grp; uint32_t ph = 0;
    while (true) {
        mbar_wait(sb + SM_BAR + s * 8, ph);
        PH(0, 0);
        const uint32_t stop = lds32(sb + SM_FLAG + s * 4);
        const uint32_t st = sb + SM_STAGES + s * STAGE;
        float sc[2][4], gr[2][4], sx[4];
#pragma unroll
        for (int e = 0; e < 4; e++) sc[0][e] = sc[1][e] = gr[0][e] = gr[1][e] = sx[e] = 0.f;
#pragma unroll
        for (int qq = 0; qq < 6; qq++) {
            uint32_t x[4], y[4];
            ldsm4(x, st + (qq & 1 ? offS0x : offS0) + (qq >> 1) * 1024);
            ldsm4(y, st + (qq & 1 ? offS1x : offS1) + (qq >> 1) * 1024);
#pragma unroll
            for (int e = 0; e < 4; e++) x[e] = hadd2(x[e], y[e]);
            mma8(gr[0], x[0], x[1], x[0]);
            mma8(gr[1], x[0], x[1], x[1]);
            mma(sx, x[0], x[1], x[2], x[3], ONES, ONES);
            mma8(gr[0], x[2], x[3], x[2]);
            mma8(gr[1], x[2], x[3], x[3]);
            mma(sc[0], qa[8 * qq], qa[8 * qq + 1], qa[8 * qq + 2], qa[8 * qq + 3], x[0], x[1]);
            mma(sc[1], qa[8 * qq + 4], qa[8 * qq + 5], qa[8 * qq + 6], qa[8 * qq + 7], x[2], x[3]);
        }
        uint32_t yt[6];
        ldsm4t(yt, st + offU);
        ldsm2t(yt + 4, st + offV);
#pragma unroll
        for (int i = 0; i < 6; i++) ldsm4t(xt[i], st + (i < 3 ? offT : offTx) + (i % 3) * 1024);

        const float mu = (sx[0] + sx[2]) * (1.f / C), ss = odd ? gr[0][1] + gr[1][3] : gr[0][0] + gr[1][2];
        const float rs = rsq(fmaxf(fmaf(-mu, mu, ss * (1.f / C)), 0.f) + 1e-5f);
        const float mu0 = __shfl_sync(~0u, mu, shl), mu1 = __shfl_sync(~0u, mu, shl4);
        const float rs0 = __shfl_sync(~0u, rs, shl), rs1 = __shfl_sync(~0u, rs, shl4);
        const float u0 = fmaf(-mu0, r_lo, sc[0][0] + sc[1][0]), u1 = fmaf(-mu1, r_lo, sc[0][1] + sc[1][1]);
        const float u2 = fmaf(-mu0, r_hi, sc[0][2] + sc[1][2]), u3 = fmaf(-mu1, r_hi, sc[0][3] + sc[1][3]);
        const float d0 = fmaf(u0, rs0, -m_lo), d1 = fmaf(u1, rs1, -m_lo), d2 = fmaf(u2, rs0, -m_hi), d3 = fmaf(u3, rs1, -m_hi);
        PH(1, u(d0 + d2));
        float p0 = ex2(d0), p1 = ex2(d1), p2 = ex2(d2), p3 = ex2(d3);
        sts64(pb0 + pw, pack2(p0 * rs0, p1 * rs1), pack2(p2 * rs0, p3 * rs1));
        if (lane < 4) sts32(pb0 + muw, pack2(mu0, mu1));
#pragma unroll
        for (int i = 0; i < 6; i++)
#pragma unroll
            for (int e = 0; e < 4; e++) xt[i][e] = hadd2v(xt[i][e], yt[i]);
        const bool over = bar_any(barid, 128, fmaxf(fmaxf(d0, d1), fmaxf(d2, d3)) > LAZY);
        PH(3, 0);
        pa = lds128(pb0 + prd); pb = lds128(pb0 + prd + 512); mv = lds128(pb0 + mur);
        if (elected) mbar_arrive(sb + SM_BAR + (NS + s) * 8);
        if (__builtin_expect(over, 0)) {
            const float s0 = u0 * rs0, s1 = u1 * rs1, s2 = u2 * rs0, s3 = u3 * rs1;
            float xl = fmaxf(s0, s1), xh = fmaxf(s2, s3);
            xl = fmaxf(xl, __shfl_xor_sync(~0u, xl, 1)); xh = fmaxf(xh, __shfl_xor_sync(~0u, xh, 1));
            xl = fmaxf(xl, __shfl_xor_sync(~0u, xl, 2)); xh = fmaxf(xh, __shfl_xor_sync(~0u, xh, 2));
            if (t < 2) sts32(sb + SM_MX + grp * 256 + ((g + 8 * t) * 4 + cw) * 4, u(t ? xh : xl));
            bar_sync(B_MAX + grp, 128);
            const uint4 ml4 = lds128(sb + SM_MX + grp * 256 + g * 16), mh4 = lds128(sb + SM_MX + grp * 256 + g * 16 + 128);
            const float nl = fmaxf(fmaxf(fmaxf(f(ml4.x), f(ml4.y)), fmaxf(f(ml4.z), f(ml4.w))), m_lo);
            const float nh = fmaxf(fmaxf(fmaxf(f(mh4.x), f(mh4.y)), fmaxf(f(mh4.z), f(mh4.w))), m_hi);
            p0 = ex2(s0 - nl); p1 = ex2(s1 - nl); p2 = ex2(s2 - nh); p3 = ex2(s3 - nh);
            sts64(pb0 + pw, pack2(p0 * rs0, p1 * rs1), pack2(p2 * rs0, p3 * rs1));
            const float al = ex2(m_lo - nl), ah = ex2(m_hi - nh);
            m_lo = nl; m_hi = nh;
            l_lo *= al; l_hi *= ah; cm[0] *= al; cm[2] *= ah;
#pragma unroll
            for (int i = 0; i < 6; i++) { acc[i][0] *= al; acc[i][1] *= al; acc[i][2] *= ah; acc[i][3] *= ah; }
            bar_sync(B_MAX + grp, 128);
            pa = lds128(pb0 + prd); pb = lds128(pb0 + prd + 512);
        }
        l_lo += p0 + p1; l_hi += p2 + p3;
        if (stop & 1) break;
#pragma unroll
        for (int i = 0; i < 6; i++) mma(acc[i], pa.x, pa.y, pa.z, pa.w, xt[i][0], xt[i][1]);
        mma(cm, pa.x, pa.y, pa.z, pa.w, mv.x, mv.y);
#pragma unroll
        for (int i = 0; i < 6; i++) mma(acc[i], pb.x, pb.y, pb.z, pb.w, xt[i][2], xt[i][3]);
        mma(cm, pb.x, pb.y, pb.z, pb.w, mv.z, mv.w);
        PH(4, u(acc[5][0]));
        if (stop) {
            float a = l_lo + __shfl_xor_sync(~0u, l_lo, 1), c = l_hi + __shfl_xor_sync(~0u, l_hi, 1);
            a += __shfl_xor_sync(~0u, a, 2); c += __shfl_xor_sync(~0u, c, 2);
            const uint32_t m = u((t ? m_hi : m_lo) + lg2(fmaxf(t ? c : a, 1.f)));
            if (t < 2) asm volatile("red.relaxed.gpu.global.max.u32 [%0], %1;" ::"l"(g_mmax + g + 8 * t), "r"(m >> 31 ? ~m : m | 0x80000000u) : "memory");
        }
        pb0 ^= pbx;
        s += 2;
        if (s >= NS) { s -= NS; ph ^= 1; }
    }
    const float al = ex2(m_lo - f(lds32(sb + SM_M + g * 4))), ah = ex2(m_hi - f(lds32(sb + SM_M + 32 + g * 4)));
    mma(cm, pa.x, pa.y, pa.z, pa.w, mv.x, mv.y);
#pragma unroll
    for (int i = 3; i < 6; i++) mma(acc[i], pa.x, pa.y, pa.z, pa.w, xt[i][0], xt[i][1]);
    mma(cm, pb.x, pb.y, pb.z, pb.w, mv.z, mv.w);
#pragma unroll
    for (int i = 3; i < 6; i++) mma(acc[i], pb.x, pb.y, pb.z, pb.w, xt[i][2], xt[i][3]);
#pragma unroll
    for (int i = 0; i < 3; i++) mma(acc[i], pa.x, pa.y, pa.z, pa.w, xt[i][0], xt[i][1]);
#pragma unroll
    for (int i = 0; i < 3; i++) mma(acc[i], pb.x, pb.y, pb.z, pb.w, xt[i][2], xt[i][3]);
    if (threadIdx.x == grp * 128) TSE(2 + grp);
    if (threadIdx.x == grp * 128 + 96) TSX(2 + grp, u(acc[5][0]));

    uint4* const dst = g_acc + (b & 1) * ACC + ((g >> 1) * 8 + cw + 4 * grp) * 8 + (lane & 7);
    const uint32_t xw = opaque(sb + SM_STAGES + grp * STAGE + cw * 1536 + lane * 16), xr = opaque(sb + SM_STAGES + (grp ^ 1) * STAGE + cw * 1536 + lane * 16);
    asm volatile("" ::"l"(dst));
    const float cl = -cm[0] * al, ch = -cm[2] * ah;
#pragma unroll
    for (int i = 0; i < 3; i++)
        sts128(xw + i * 512, u(fmaf(acc[3 + i][0], al, cl)), u(fmaf(acc[3 + i][1], al, cl)), u(fmaf(acc[3 + i][2], ah, ch)), u(fmaf(acc[3 + i][3], ah, ch)));
#pragma unroll
    for (int i = 0; i < 3; i++) { acc[i][0] = fmaf(acc[i][0], al, cl); acc[i][1] = fmaf(acc[i][1], al, cl); acc[i][2] = fmaf(acc[i][2], ah, ch); acc[i][3] = fmaf(acc[i][3], ah, ch); }
    const uint32_t w_lo = packh(1.f, l_lo * al), w_hi = packh(1.f, l_hi * ah);
    bar_sync(B_MERGE, 256);
    if (threadIdx.x == 224) TSX(4, 0);
    uint4 o[3];
#pragma unroll
    for (int i = 0; i < 3; i++) o[i] = lds128(xr + i * 512);
    red8h(dst, packh(acc[0][0] + f(o[0].x), acc[0][1] + f(o[0].y)), packh(acc[1][0] + f(o[1].x), acc[1][1] + f(o[1].y)), packh(acc[2][0] + f(o[2].x), acc[2][1] + f(o[2].y)), w_lo);
    red8h(dst + 256, packh(acc[0][2] + f(o[0].z), acc[0][3] + f(o[0].w)), packh(acc[1][2] + f(o[1].z), acc[1][3] + f(o[1].w)), packh(acc[2][2] + f(o[2].z), acc[2][3] + f(o[2].w)), w_hi);
    if (threadIdx.x == 0) TSE(4);
    if (threadIdx.x == 224) TSX(9, 0);
}

typedef CUresult (*EncodeFn)(CUtensorMap*, CUtensorMapDataType, cuuint32_t, void*, const cuuint64_t*, const cuuint64_t*,
                             const cuuint32_t*, const cuuint32_t*, CUtensorMapInterleave, CUtensorMapSwizzle,
                             CUtensorMapL2promotion, CUtensorMapFloatOOBfill);

}

extern "C" void kernel_launch(void* const* d_in, const int* in_sizes, int n_in, void* d_out, int out_size) {
    const __nv_bfloat16* q = (const __nv_bfloat16*)d_in[0];
    char* f0 = (char*)d_in[1];
    char* f1 = (char*)d_in[2];
    const __nv_bfloat16* wq = (const __nv_bfloat16*)d_in[3];
    const __nv_bfloat16* wk = (const __nv_bfloat16*)d_in[4];
    const __nv_bfloat16* wv = (const __nv_bfloat16*)d_in[5];
    const __nv_bfloat16* wo = (const __nv_bfloat16*)d_in[6];

    static EncodeFn enc = nullptr;
    static int grid = 0;
    static Scratch* scr = nullptr;
    if (!enc) {
        void* fn = nullptr; cudaDriverEntryPointQueryResult qr;
        cudaGetDriverEntryPoint("cuTensorMapEncodeTiled", &fn, cudaEnableDefault, &qr);
        enc = (EncodeFn)fn;
        cudaGetSymbolAddress((void**)&scr, g_scratch);
        int dev = 0, sms = 0;
        cudaGetDevice(&dev);
        cudaDeviceGetAttribute(&sms, cudaDevAttrMultiProcessorCount, dev);
        grid = sms < MAXG ? sms : MAXG;
        cudaFuncSetAttribute(attn_main, cudaFuncAttributeMaxDynamicSharedMemorySize, SMEM_BYTES);
    }
    CUtensorMap m0, m1;
    {
        cuuint64_t dims[5] = {64, W1, 3, 2, W0};
        cuuint64_t str[4] = {2 * C * 2, 128, C * 2, (cuuint64_t)W0 * C * 2};
        cuuint32_t box[5] = {64, TP, 3, 2, 2}, es[5] = {1, 1, 1, 1, 1};
        enc(&m0, CU_TENSOR_MAP_DATA_TYPE_BFLOAT16, 5, f0, dims, str, box, es, CU_TENSOR_MAP_INTERLEAVE_NONE,
            CU_TENSOR_MAP_SWIZZLE_128B, CU_TENSOR_MAP_L2_PROMOTION_NONE, CU_TENSOR_MAP_FLOAT_OOB_FILL_NONE);
    }
    {
        cuuint64_t dims[4] = {64, W1, 3, W1};
        cuuint64_t str[3] = {C * 2, 128, (cuuint64_t)W1 * C * 2};
        cuuint32_t box[4] = {64, TP, 3, 1}, es[4] = {1, 1, 1, 1};
        enc(&m1, CU_TENSOR_MAP_DATA_TYPE_BFLOAT16, 4, f1, dims, str, box, es, CU_TENSOR_MAP_INTERLEAVE_NONE,
            CU_TENSOR_MAP_SWIZZLE_128B, CU_TENSOR_MAP_L2_PROMOTION_NONE, CU_TENSOR_MAP_FLOAT_OOB_FILL_NONE);
    }
    attn_main<<<grid, NTHREADS, SMEM_BYTES, cudaStreamPerThread>>>(f0, f1, q, wq, wk, scr, wv, wo, (__nv_bfloat16*)d_out, m0, m1);
}
```

```cpp
#include <cuda_runtime.h>
#include <cuda_bf16.h>
#include <cuda.h>
#include <stdint.h>

namespace {

constexpr int C = 192;
constexpr int NQ = 16;
constexpr int W0 = 512;
constexpr int W1 = 256;
constexpr int TP = 8;
constexpr int NT = W1 * W1 / TP;
constexpr int STAGE = TP * 5 * C * 2;
#define NS 14
#define D0 1
#define D1 4
#define D2 2
#define NRAMP 3
#define TAILT 1000
#define QSLEEP 700
#define WSL 24
#define MAXT 3000
#define REFT 1800
#define POLLN 1
#define PGAP 110
#define LAZY 12.f
#define GR4 1
#define NST 2
#define NPRE 2
static_assert(NST > D0, "the first dynamic tile index must not delay the start");
constexpr int NTHREADS = 384;
constexpr int MAXG = 132;
constexpr int NRD = NQ;
constexpr int ACC = NQ * 32;
constexpr int NSRC = 12;
constexpr int SPIN_LIMIT = 1 << 22;

constexpr int SM_STAGES = 0;
constexpr int SM_P = NS * STAGE;
constexpr int PBUF = 1088;
constexpr int SM_QK = SM_P + 4 * PBUF;
constexpr int SM_MX = SM_QK + 6144;
constexpr int SM_M = SM_MX + 512;
constexpr int SM_BAR = SM_M + 64;
constexpr int SM_REF = SM_BAR + 16 * NS;
constexpr int SM_FLAG = SM_REF + 8;
constexpr int SM_TOTAL = SM_FLAG + 4 * NS;
constexpr int SMEM_BYTES = SM_TOTAL + 1024;
static_assert(SMEM_BYTES <= 232448, "smem");
constexpr int WROW = 400;
constexpr int RD_W = 0;
constexpr int RD_QN = 2 * C * WROW;
constexpr int RD_KQ = RD_QN + 6144;
constexpr int RD_B = RD_KQ + 7168;
constexpr int RD_RDY = RD_B + 32 * 144 + 256;
constexpr int RD_BAR = RD_RDY + 16;
static_assert(RD_BAR + 64 <= SM_TOTAL, "smem");

struct Scratch {
    uint4 acc[2 * ACC];
    uint4 qk[NSRC * 32];
    unsigned ctr[32];
    unsigned mmax[32];
    unsigned mref[32];
};
__device__ __align__(128) Scratch g_scratch;
#define g_acc (scr->acc)
#define g_qk (scr->qk)
#define g_ctr (scr->ctr)
#define g_mmax (scr->mmax)
#define g_mref (scr->mref)
#define g_ts (scr->ts)
#define g_tr (scr->tr)
#define TR(k, i) do {} while (0)
#define TS(i) do {} while (0)
#define TSD(i, dep) do {} while (0)
#define TSX(i, dep) do {} while (0)
#define TSP(i, dep) do {} while (0)
#define TSE(i) TS(i)
#define CK_(i, dep) do {} while (0)
#define PH(i, dep) do {} while (0)

__device__ __forceinline__ uint32_t s2u(const void* p) { return (uint32_t)__cvta_generic_to_shared(p); }
__device__ __forceinline__ void mbar_init(uint32_t a, int c) { asm volatile("mbarrier.init.shared::cta.b64 [%0], %1;" ::"r"(a), "r"(c) : "memory"); }
__device__ __forceinline__ void mbar_expect(uint32_t a, uint32_t b) { asm volatile("mbarrier.arrive.expect_tx.shared::cta.b64 _, [%0], %1;" ::"r"(a), "r"(b) : "memory"); }
__device__ __forceinline__ void mbar_arrive(uint32_t a) { asm volatile("mbarrier.arrive.shared::cta.b64 _, [%0];" ::"r"(a) : "memory"); }
__device__ __forceinline__ void mbar_wait(uint32_t a, uint32_t ph) {
    uint32_t ok; int it = 0;
    do {
        asm volatile("{.reg .pred p; mbarrier.try_wait.parity.shared::cta.b64 p, [%1], %2; selp.u32 %0,1,0,p;}" : "=r"(ok) : "r"(a), "r"(ph) : "memory");
        if (++it > SPIN_LIMIT) __trap();
    } while (!ok);
}
__device__ __forceinline__ void bar_sync(int id, int n) { asm volatile("bar.sync %0, %1;" ::"r"(id), "r"(n) : "memory"); }
__device__ __forceinline__ bool bar_any(int id, int n, bool c) {
    uint32_t r;
    asm volatile("{.reg .pred p, q; setp.ne.u32 q, %3, 0; bar.red.or.pred p, %1, %2, q; selp.u32 %0, 1, 0, p;}" : "=r"(r) : "r"(id), "r"(n), "r"((uint32_t)c) : "memory");
    return r;
}
__device__ __forceinline__ void bar_arrive(int id, int n) { asm volatile("bar.arrive %0, %1;" ::"r"(id), "r"(n) : "memory"); }
__device__ __forceinline__ void ldsm4(uint32_t* r, uint32_t a) {
    asm volatile("ldmatrix.sync.aligned.m8n8.x4.shared.b16 {%0,%1,%2,%3}, [%4];" : "=r"(r[0]), "=r"(r[1]), "=r"(r[2]), "=r"(r[3]) : "r"(a) : "memory");
}
__device__ __forceinline__ void ldsm4t(uint32_t* r, uint32_t a) {
    asm volatile("ldmatrix.sync.aligned.m8n8.x4.trans.shared.b16 {%0,%1,%2,%3}, [%4];" : "=r"(r[0]), "=r"(r[1]), "=r"(r[2]), "=r"(r[3]) : "r"(a) : "memory");
}
__device__ __forceinline__ void ldsm2t(uint32_t* r, uint32_t a) {
    asm volatile("ldmatrix.sync.aligned.m8n8.x2.trans.shared.b16 {%0,%1}, [%2];" : "=r"(r[0]), "=r"(r[1]) : "r"(a) : "memory");
}
__device__ __forceinline__ void mma(float* d, uint32_t a0, uint32_t a1, uint32_t a2, uint32_t a3, uint32_t b0, uint32_t b1) {
    asm("mma.sync.aligned.m16n8k16.row.col.f32.bf16.bf16.f32 {%0,%1,%2,%3}, {%4,%5,%6,%7}, {%8,%9}, {%0,%1,%2,%3};"
        : "+f"(d[0]), "+f"(d[1]), "+f"(d[2]), "+f"(d[3]) : "r"(a0), "r"(a1), "r"(a2), "r"(a3), "r"(b0), "r"(b1));
}
__device__ __forceinline__ void mmah(float* d, uint32_t a0, uint32_t a1, uint32_t a2, uint32_t a3, uint32_t b0, uint32_t b1) {
    asm("mma.sync.aligned.m16n8k16.row.col.f32.f16.f16.f32 {%0,%1,%2,%3}, {%4,%5,%6,%7}, {%8,%9}, {%0,%1,%2,%3};"
        : "+f"(d[0]), "+f"(d[1]), "+f"(d[2]), "+f"(d[3]) : "r"(a0), "r"(a1), "r"(a2), "r"(a3), "r"(b0), "r"(b1));
}
__device__ __forceinline__ void mma8(float* d, uint32_t a0, uint32_t a1, uint32_t b0) {
    asm("mma.sync.aligned.m16n8k8.row.col.f32.bf16.bf16.f32 {%0,%1,%2,%3}, {%4,%5}, {%6}, {%0,%1,%2,%3};"
        : "+f"(d[0]), "+f"(d[1]), "+f"(d[2]), "+f"(d[3]) : "r"(a0), "r"(a1), "r"(b0));
}
__device__ __forceinline__ uint32_t hadd2(uint32_t a, uint32_t b) {
    uint32_t r; asm("add.rn.bf16x2 %0, %1, %2;" : "=r"(r) : "r"(a), "r"(b)); return r;
}
__device__ __forceinline__ uint32_t pack2(float lo, float hi) {
    uint32_t r; asm("cvt.rn.bf16x2.f32 %0, %1, %2;" : "=r"(r) : "f"(hi), "f"(lo)); return r;
}
__device__ __forceinline__ uint32_t packh(float lo, float hi) {
    uint32_t r; asm("cvt.rn.f16x2.f32 %0, %1, %2;" : "=r"(r) : "f"(hi), "f"(lo)); return r;
}
__device__ __forceinline__ float2 unpackh(uint32_t v) {
    float2 r; asm("{.reg .b16 l, h; mov.b32 {l, h}, %2; cvt.f32.f16 %0, l; cvt.f32.f16 %1, h;}" : "=f"(r.x), "=f"(r.y) : "r"(v)); return r;
}
__device__ __forceinline__ float bflo(uint32_t v) { return __uint_as_float(v << 16); }
__device__ __forceinline__ float bfhi(uint32_t v) { return __uint_as_float(v & 0xffff0000u); }
__device__ __forceinline__ float ex2(float x) { float r; asm("ex2.approx.ftz.f32 %0, %1;" : "=f"(r) : "f"(x)); return r; }
__device__ __forceinline__ void sts128(uint32_t a, uint32_t x, uint32_t y, uint32_t z, uint32_t w) {
    asm volatile("st.shared.v4.b32 [%0], {%1,%2,%3,%4};" ::"r"(a), "r"(x), "r"(y), "r"(z), "r"(w) : "memory");
}
__device__ __forceinline__ void sts64(uint32_t a, uint32_t x, uint32_t y) {
    asm volatile("st.shared.v2.b32 [%0], {%1,%2};" ::"r"(a), "r"(x), "r"(y) : "memory");
}
__device__ __forceinline__ void sts32(uint32_t a, uint32_t x) { asm volatile("st.shared.b32 [%0], %1;" ::"r"(a), "r"(x) : "memory"); }
__device__ __forceinline__ uint4 lds128(uint32_t a) {
    uint4 v; asm volatile("ld.shared.v4.b32 {%0,%1,%2,%3}, [%4];" : "=r"(v.x), "=r"(v.y), "=r"(v.z), "=r"(v.w) : "r"(a) : "memory"); return v;
}
__device__ __forceinline__ uint32_t lds32(uint32_t a) { uint32_t v; asm volatile("ld.shared.b32 %0, [%1];" : "=r"(v) : "r"(a) : "memory"); return v; }
__device__ __forceinline__ int grab_tile(unsigned* ctr) {
    int v; asm volatile("atom.relaxed.gpu.global.inc.u32 %0, [%1], 0x7fffffff;" : "=r"(v) : "l"(ctr) : "memory"); return v;
}
__device__ __forceinline__ uint32_t opaque(uint32_t v) { uint32_t r; asm volatile("mov.b32 %0, %1;" : "=r"(r) : "r"(v)); return r; }
__device__ __forceinline__ float rsq(float x) { float r; asm("rsqrt.approx.ftz.f32 %0, %1;" : "=f"(r) : "f"(x)); return r; }
__device__ __forceinline__ float rcp(float x) { float r; asm("rcp.approx.ftz.f32 %0, %1;" : "=f"(r) : "f"(x)); return r; }
__device__ __forceinline__ float lg2(float x) { float r; asm("lg2.approx.ftz.f32 %0, %1;" : "=f"(r) : "f"(x)); return r; }
__device__ __forceinline__ float f(uint32_t v) { return __uint_as_float(v); }
__device__ __forceinline__ uint32_t u(float v) { return __float_as_uint(v); }

constexpr uint32_t ONES = 0x3F803F80u;
constexpr float QSCALE = 0.07216878364870322f * 1.4426950408889634f;

__device__ __forceinline__ void issue_tile(const CUtensorMap* m0, const CUtensorMap* m1, uint32_t sb, int s, int tl, uint64_t pol) {
    const uint32_t full = sb + SM_BAR + s * 8, dst = sb + SM_STAGES + s * STAGE;
    const int par = tl * TP, y = par >> 8, x = par & 255;
    mbar_expect(full, STAGE);
    asm volatile("cp.async.bulk.tensor.5d.shared::cluster.global.mbarrier::complete_tx::bytes.L2::cache_hint [%0], [%1, {%3,%4,%3,%3,%5}], [%2], %6;"
                 ::"r"(dst), "l"(m0), "r"(full), "r"(0), "r"(x), "r"(2 * y), "l"(pol) : "memory");
    asm volatile("cp.async.bulk.tensor.4d.shared::cluster.global.mbarrier::complete_tx::bytes.L2::cache_hint [%0], [%1, {%3,%4,%3,%5}], [%2], %6;"
                 ::"r"(dst + TP * 4 * C * 2), "l"(m1), "r"(full), "r"(0), "r"(x), "r"(y), "l"(pol) : "memory");
}

__device__ __forceinline__ uint4 ldg_relaxed(const uint4* p) {
    uint4 v; asm volatile("ld.relaxed.gpu.global.v4.u32 {%0,%1,%2,%3}, [%4];" : "=r"(v.x), "=r"(v.y), "=r"(v.z), "=r"(v.w) : "l"(p) : "memory"); return v;
}
__device__ __forceinline__ uint32_t ldg_relaxed32(const void* p) {
    uint32_t v; asm volatile("ld.relaxed.gpu.global.u32 %0, [%1];" : "=r"(v) : "l"(p) : "memory"); return v;
}
__device__ __forceinline__ void stg_relaxed(uint4* p, uint32_t x, uint32_t y, uint32_t z, uint32_t w) {
    asm volatile("st.relaxed.gpu.global.v4.u32 [%0], {%1,%2,%3,%4};" ::"l"(p), "r"(x), "r"(y), "r"(z), "r"(w) : "memory");
}
__device__ __forceinline__ void stg_relaxed32(void* p, uint32_t x) { asm volatile("st.relaxed.gpu.global.u32 [%0], %1;" ::"l"(p), "r"(x) : "memory"); }
__device__ __forceinline__ bool has(const uint4& v, uint32_t m) { return v.x == m || v.y == m || v.z == m || v.w == m; }
__device__ __forceinline__ uint32_t hadd2v(uint32_t a, uint32_t b) {
    uint32_t r; asm volatile("add.rn.bf16x2 %0, %1, %2;" : "=r"(r) : "r"(a), "r"(b)); return r;
}

__device__ __forceinline__ void red8h(uint4* p, uint32_t x, uint32_t y, uint32_t z, uint32_t w) {
    asm volatile("red.relaxed.gpu.global.add.noftz.v4.f16x2 [%0], {%1,%2,%3,%4};" ::"l"(p), "r"(x), "r"(y), "r"(z), "r"(w) : "memory");
}
__device__ __forceinline__ uint2 lds64v(uint32_t a) {
    uint2 v; asm volatile("ld.volatile.shared.v2.b32 {%0,%1}, [%2];" : "=r"(v.x), "=r"(v.y) : "r"(a) : "memory"); return v;
}
__device__ __forceinline__ uint4 lds128v(uint32_t a) {
    uint4 v; asm volatile("ld.volatile.shared.v4.b32 {%0,%1,%2,%3}, [%4];" : "=r"(v.x), "=r"(v.y), "=r"(v.z), "=r"(v.w) : "r"(a) : "memory"); return v;
}
__device__ __forceinline__ uint32_t brow(int r) { return RD_B + r * 144 + (r >> 3) * 64; }

enum { B_QK = 1, B_QN = 2, B_GRP = 3  , B_Q = 5, B_MERGE = 6, B_ALL = 7, B_MAX = 8  , B_WARP = 10, B_POLL = 11, B_SLOW = 12 };

__device__ __noinline__ void slow_rows(const char* __restrict__ f0, const char* __restrict__ f1, const __nv_bfloat16* __restrict__ q,
                                       const __nv_bfloat16* __restrict__ wq, const __nv_bfloat16* __restrict__ wk, const uint32_t sb)
{
    const int warp = threadIdx.x >> 5, lane = threadIdx.x & 31;
    float* const sm = reinterpret_cast<float*>(__cvta_shared_to_generic(sb + RD_W));
    bar_sync(B_POLL, 352);
    for (int i = threadIdx.x; i < 4 * C; i += 96) sm[i] = __bfloat162float(q[(blockIdx.x & 12) * C + i]);
    bar_sync(B_SLOW, 96);
#pragma unroll 1
    for (int j = threadIdx.x; j < 4 * C; j += 96) {
        const float* const x = sm + j / C * C;
        float mu = 0.f, var = 0.f, s = 0.f;
#pragma unroll 1
        for (int i = 0; i < C; i++) mu += x[i];
        mu *= 1.f / C;
#pragma unroll 4
        for (int i = 0; i < C; i++) { var = fmaf(x[i] - mu, x[i] - mu, var); s = fmaf(x[i] - mu, __bfloat162float(wq[i * C + j % C]), s); }
        sm[4 * C + j] = s * rsq(var * (1.f / C) + 1e-5f);
    }
    bar_sync(B_SLOW, 96);
#pragma unroll 1
    for (int j = threadIdx.x; j < 4 * C; j += 96) {
        float s = 0.f;
#pragma unroll 4
        for (int i = 0; i < C; i++) s = fmaf(sm[4 * C + j / C * C + i], __bfloat162float(wk[j % C * C + i]), s);
        sm[j] = s * QSCALE;
    }
    bar_sync(B_SLOW, 96);
    float k[4][6], a[4][6], m[4], l[4];
#pragma unroll
    for (int r = 0; r < 4; r++) {
        m[r] = -INFINITY; l[r] = 0.f;
#pragma unroll
        for (int i = 0; i < 6; i++) { k[r][i] = sm[r * C + 64 * (i >> 1) + 2 * lane + (i & 1)]; a[r][i] = 0.f; }
    }
#pragma unroll 1
    for (int par = warp; par < W1 * W1; par += 3) {
        const uint32_t* p0 = reinterpret_cast<const uint32_t*>(f0 + (size_t)((par >> 8) * 2 * W0 + (par & 255) * 2) * (C * 2)) + lane;
        const uint32_t* p1 = reinterpret_cast<const uint32_t*>(f1 + (size_t)par * (C * 2)) + lane;
        uint32_t v[4][3];
#pragma unroll
        for (int i = 0; i < 3; i++)
#pragma unroll
            for (int j = 0; j < 4; j++) v[j][i] = hadd2(__ldg(p0 + ((j >> 1) * W0 + (j & 1)) * (C / 2) + 32 * i), __ldg(p1 + 32 * i));
#pragma unroll
        for (int j = 0; j < 4; j++) {
            float x[6], s1 = 0.f, s2 = 0.f, d[4] = {0.f, 0.f, 0.f, 0.f};
#pragma unroll
            for (int i = 0; i < 3; i++) { x[2 * i] = bflo(v[j][i]); x[2 * i + 1] = bfhi(v[j][i]); s1 += x[2 * i] + x[2 * i + 1]; }
#pragma unroll
            for (int o = 1; o < 32; o <<= 1) s1 += __shfl_xor_sync(~0u, s1, o);
#pragma unroll
            for (int i = 0; i < 6; i++) {
                x[i] -= s1 * (1.f / C); s2 = fmaf(x[i], x[i], s2);
#pragma unroll
                for (int r = 0; r < 4; r++) d[r] = fmaf(x[i], k[r][i], d[r]);
            }
#pragma unroll
            for (int o = 1; o < 32; o <<= 1) {
                s2 += __shfl_xor_sync(~0u, s2, o);
#pragma unroll
                for (int r = 0; r < 4; r++) d[r] += __shfl_xor_sync(~0u, d[r], o);
            }
            const float rs = rsq(s2 * (1.f / C) + 1e-5f);
#pragma unroll
            for (int r = 0; r < 4; r++) {
                const float nm = fmaxf(m[r], d[r] * rs), al = ex2(m[r] - nm), p = ex2(d[r] * rs - nm);
                m[r] = nm; l[r] = fmaf(l[r], al, p);
#pragma unroll
                for (int i = 0; i < 6; i++) a[r][i] = fmaf(a[r][i], al, x[i] * (p * rs));
            }
        }
    }
    bar_sync(B_SLOW, 96);
#pragma unroll
    for (int r = 0; r < 4; r++) {
        float* const o = sm + ((r * 3 + warp) * 32 + lane) * 8;
#pragma unroll
        for (int i = 0; i < 6; i++) o[i] = a[r][i];
        o[6] = l[r]; o[7] = m[r];
    }
    bar_sync(B_SLOW, 96);
#pragma unroll 1
    for (int r = warp; r < 4; r += 3) {
        const float* const o = sm + (r * 96 + lane) * 8;
        const float M = fmaxf(fmaxf(o[7], o[256 + 7]), o[512 + 7]), e0 = ex2(o[7] - M), e1 = ex2(o[256 + 7] - M), e2 = ex2(o[512 + 7] - M);
        float x[7];
#pragma unroll
        for (int i = 0; i < 7; i++) x[i] = o[i] * e0 + o[256 + i] * e1 + o[512 + i] * e2;
        uint32_t hi[3], lo[3];
        const float rl = 1.f / x[6];
#pragma unroll
        for (int i = 0; i < 3; i++) {
            hi[i] = packh(x[2 * i] * rl, x[2 * i + 1] * rl);
            const float2 h = unpackh(hi[i]);
            lo[i] = packh(fmaf(x[2 * i], rl, -h.x), fmaf(x[2 * i + 1], rl, -h.y));
        }
        const uint32_t bw = sb + brow(8 * r + (lane & 3)) + (lane >> 2) * 16;
        sts128(bw, hi[0], hi[1], hi[2], lane ? 0u : 0x3C00u);
        sts128(bw + 4 * 144, lo[0], lo[1], lo[2], 0);
    }
    bar_sync(B_SLOW, 96);
}

__device__ __forceinline__ void reducer(const char* __restrict__ f0, const char* __restrict__ f1, const __nv_bfloat16* __restrict__ q, const __nv_bfloat16* __restrict__ wq, const __nv_bfloat16* __restrict__ wk,
                                        Scratch* scr, const __nv_bfloat16* __restrict__ wv, const __nv_bfloat16* __restrict__ wo,
                                        __nv_bfloat16* __restrict__ out, const uint32_t sb, const int GS)
{
    const int warp = threadIdx.x >> 5, lane = threadIdx.x & 31, b = blockIdx.x;
    const int g = lane >> 2, t = lane & 3;
    if (threadIdx.x == 256) TS(0);
    if (b < NSRC && warp < 8) {
        const uint32_t wqs = sb + RD_W, wbar = sb + RD_BAR;
        const int hr = lane >> 4, qt = (lane >> 2) & 3, sub = lane & 3;
        const uint32_t* qp = reinterpret_cast<const uint32_t*>(q + (warp + 8 * hr) * C + 48 * qt + 6 * sub);
        uint32_t qw[6];
#pragma unroll
        for (int j = 0; j < 3; j++) { qw[j] = __ldg(qp + j); qw[3 + j] = __ldg(qp + 12 + j); }
        if (lane == 0) { mbar_init(wbar + warp * 8, 1); asm volatile("fence.mbarrier_init.release.cluster;" ::: "memory"); mbar_expect(wbar + warp * 8, 9216);
            asm volatile("cp.async.bulk.shared::cluster.global.mbarrier::complete_tx::bytes [%0], [%1], 9216, [%2];"
                         ::"r"(wqs + warp * 9232), "l"(wq + 24 * warp * C), "r"(wbar + warp * 8) : "memory");
        }
        __syncwarp();
        if (threadIdx.x == 0) TSP(2, 0);
        float e[12];
#pragma unroll
        for (int j = 0; j < 6; j++) { e[2 * j] = bflo(qw[j]); e[2 * j + 1] = bfhi(qw[j]); }
        float sm = ((e[0] + e[1]) + (e[2] + e[3])) + ((e[4] + e[5]) + (e[6] + e[7])) + ((e[8] + e[9]) + (e[10] + e[11]));
#pragma unroll
        for (int o = 1; o < 16; o <<= 1) sm += __shfl_xor_sync(~0u, sm, o);
        if (threadIdx.x == 0) TSP(5, u(sm));
        float v0 = 0.f, v1 = 0.f;
#pragma unroll
        for (int j = 0; j < 12; j++) e[j] -= sm * (1.f / C);
#pragma unroll
        for (int j = 0; j < 6; j++) { v0 = fmaf(e[j], e[j], v0); v1 = fmaf(e[6 + j], e[6 + j], v1); }
        v0 += v1;
#pragma unroll
        for (int o = 1; o < 16; o <<= 1) v0 += __shfl_xor_sync(~0u, v0, o);
        const float rq = rsq(v0 * (1.f / C) + 1e-5f);
#pragma unroll
        for (int j = 0; j < 6; j++)
            sts32(sb + RD_QN + (3 * sub + (j >> 1)) * 512 + (4 * warp + qt) * 16 + (2 * (j & 1) + hr) * 4, pack2(e[j] * rq, e[6 + j] * rq));
        if (threadIdx.x == 0) TSP(8, 0);
        uint32_t wkf[2][3];
#pragma unroll
        for (int i = 0; i < 2; i++)
#pragma unroll
            for (int j = 0; j < 3; j++) wkf[i][j] = __ldg(reinterpret_cast<const uint32_t*>(wk + (16 * b + 8 * i + g) * C + 24 * warp + 8 * j + 2 * t));
        bar_sync(B_QN, 256);
        float acc[2][3][4];
#pragma unroll
        for (int i = 0; i < 3; i++)
#pragma unroll
            for (int e = 0; e < 4; e++) acc[0][i][e] = acc[1][i][e] = 0.f;
        const uint32_t ba = wqs + (lane & 7) * 9232 + (lane >> 3) * 384 + 48 * warp;
        uint4 a[12];
#pragma unroll
        for (int kk = 0; kk < 12; kk++) a[kk] = lds128(sb + RD_QN + kk * 512 + lane * 16);
        mbar_wait(wbar + (lane & 7) * 8, 0);
        __syncwarp();
        if (threadIdx.x == 0) TSP(4, 0);
#pragma unroll
        for (int kp = 0; kp < 6; kp++)
#pragma unroll
            for (int i = 0; i < 3; i++) {
                uint32_t bb[4];
                ldsm4t(bb, ba + kp * 1536 + i * 16);
                mma(acc[0][i], a[2 * kp].x, a[2 * kp].y, a[2 * kp].z, a[2 * kp].w, bb[0], bb[1]);
                mma(acc[1][i], a[2 * kp + 1].x, a[2 * kp + 1].y, a[2 * kp + 1].z, a[2 * kp + 1].w, bb[2], bb[3]);
            }
        if (threadIdx.x == 0) TSP(7, u(acc[1][2][3]));
        float kq[2][4] = {{0.f, 0.f, 0.f, 0.f}, {0.f, 0.f, 0.f, 0.f}};
#pragma unroll
        for (int j = 0; j < 3; j++) {
            const uint32_t a0 = pack2(acc[0][j][0] + acc[1][j][0], acc[0][j][1] + acc[1][j][1]), a1 = pack2(acc[0][j][2] + acc[1][j][2], acc[0][j][3] + acc[1][j][3]);
            mma8(kq[0], a0, a1, wkf[0][j]);
            mma8(kq[1], a0, a1, wkf[1][j]);
        }
        if (warp < 7) {
            sts128(sb + RD_KQ + warp * 1024 + lane * 16, u(kq[0][0]), u(kq[0][1]), u(kq[0][2]), u(kq[0][3]));
            sts128(sb + RD_KQ + warp * 1024 + 512 + lane * 16, u(kq[1][0]), u(kq[1][1]), u(kq[1][2]), u(kq[1][3]));
            bar_arrive(B_Q, 256);
        } else {
            bar_sync(B_Q, 256);
#pragma unroll
            for (int w = 0; w < 7; w++)
#pragma unroll
                for (int i = 0; i < 2; i++) {
                    const uint4 o = lds128(sb + RD_KQ + w * 1024 + i * 512 + lane * 16);
                    kq[i][0] += f(o.x); kq[i][1] += f(o.y); kq[i][2] += f(o.z); kq[i][3] += f(o.w);
                }
            stg_relaxed(g_qk + b * 32 + lane, ~pack2(kq[0][0] * QSCALE, kq[0][1] * QSCALE), ~pack2(kq[0][2] * QSCALE, kq[0][3] * QSCALE),
                        ~pack2(kq[1][0] * QSCALE, kq[1][1] * QSCALE), ~pack2(kq[1][2] * QSCALE, kq[1][3] * QSCALE));
            if (lane == 0) TS(10);
        }
    } else if (b >= NSRC) {
        if (b == NSRC && warp == 0) stg_relaxed32(g_mmax + lane, 0);
        __nanosleep(2500);
    }
    bar_sync(B_ALL, 384);

#pragma unroll 1
    for (int r = 0; r < 3; r++) {
        uint4 v[8];
#pragma unroll
        for (int k = 0; k < 8; k++) {
            const int idx = (8 * r + k) * 384 + threadIdx.x;
            v[k] = __ldg(reinterpret_cast<const uint4*>(idx < 4608 ? wv : wo - C * C) + idx);
        }
#pragma unroll
        for (int k = 0; k < 8; k++) {
            const int idx = (8 * r + k) * 384 + threadIdx.x, row = idx / 24;
            sts128(sb + RD_W + row * WROW + (idx - 24 * row) * 16, v[k].x, v[k].y, v[k].z, v[k].w);
        }
    }
    if (threadIdx.x < 256) {
        stg_relaxed(g_acc + (threadIdx.x >> 7) * ACC + (b >> 2) * 128 + (threadIdx.x & 127), 0, 0, 0, 0);
        __threadfence();
    }
    if (threadIdx.x == 0) sts128(sb + RD_RDY, 0, 0, 0, 0);
    bar_sync(B_ALL, 384);
    uint32_t wa[12][4];
    float ws0 = 0.f, ws1 = 0.f, qv0 = 0.f, qv1 = 0.f;
    __nv_bfloat16* op = out;
    if (warp < 3) {
        const int col = 48 * (b & 3) + 16 * warp;
        float d[24][4];
#pragma unroll
        for (int i = 0; i < 24; i++) d[i][0] = d[i][1] = d[i][2] = d[i][3] = 0.f;
        const int mi = lane >> 3, r = lane & 7;
        const uint32_t aa = sb + RD_W + (C + (mi >> 1) * 8 + r) * WROW + (col + (mi & 1) * 8) * 2;
        const uint32_t ba = sb + RD_W + ((mi >> 1) * 8 + r) * WROW + (mi & 1) * 16;
#pragma unroll 1
        for (int kk = 0; kk < 12; kk++) {
            uint32_t a[4];
            ldsm4t(a, aa + kk * 16 * WROW);
#pragma unroll
            for (int i = 0; i < 12; i++) {
                uint32_t bb[4];
                ldsm4(bb, ba + i * 16 * WROW + kk * 32);
                mma(d[2 * i], a[0], a[1], a[2], a[3], bb[0], bb[1]);
                mma(d[2 * i + 1], a[0], a[1], a[2], a[3], bb[2], bb[3]);
            }
        }
        float c0 = 0.f, c1 = 0.f, m0 = 0.f, m1 = 0.f;
#pragma unroll
        for (int i = 0; i < 24; i++) { c0 += d[i][0] + d[i][1]; c1 += d[i][2] + d[i][3]; }
        c0 += __shfl_xor_sync(~0u, c0, 1); c1 += __shfl_xor_sync(~0u, c1, 1);
        c0 += __shfl_xor_sync(~0u, c0, 2); c1 += __shfl_xor_sync(~0u, c1, 2);
        c0 *= 1.f / C; c1 *= 1.f / C;
#pragma unroll
        for (int i = 0; i < 24; i++) {
            d[i][0] -= c0; d[i][1] -= c0; d[i][2] -= c1; d[i][3] -= c1;
            m0 = fmaxf(m0, fmaxf(fabsf(d[i][0]), fabsf(d[i][1]))); m1 = fmaxf(m1, fmaxf(fabsf(d[i][2]), fabsf(d[i][3])));
        }
        m0 = fmaxf(m0, __shfl_xor_sync(~0u, m0, 1)); m1 = fmaxf(m1, __shfl_xor_sync(~0u, m1, 1));
        m0 = fmaxf(m0, __shfl_xor_sync(~0u, m0, 2)); m1 = fmaxf(m1, __shfl_xor_sync(~0u, m1, 2));
        const uint32_t e0 = min(max(u(m0) >> 23, 12u), 254u), e1 = min(max(u(m1) >> 23, 12u), 254u);
        const float s0 = f((265u - e0) << 23), s1 = f((265u - e1) << 23);
        const bool k0 = fabsf(c0) < INFINITY, k1 = fabsf(c1) < INFINITY;
        ws0 = k0 ? f((e0 - 11u) << 23) : c0; ws1 = k1 ? f((e1 - 11u) << 23) : c1;
#pragma unroll
        for (int i = 0; i < 24; i++) {
            const int kk = i < 16 ? i & 7 : i >> 1, hf = i < 16 ? i >> 3 : i & 1;
            wa[kk][2 * hf] = k0 ? packh(d[i][0] * s0, d[i][1] * s0) : 0u;
            wa[kk][2 * hf + 1] = k1 ? packh(d[i][2] * s1, d[i][3] * s1) : 0u;
        }
        const int o = ((b & 12) + t) * C + col + g;
        qv0 = __bfloat162float(q[o]); qv1 = __bfloat162float(q[o + 8]);
        op = out + o;
        asm volatile("" : "+l"(op));
        if (threadIdx.x == 0) TSE(6);
    } else if (warp == 3) {
        if (lane == 0) {
            uint32_t m;
            for (int it = 0;; it++) {
                const int left = NT - 2 * NST * GS - (int)ldg_relaxed32(g_ctr);
                m = ldg_relaxed32(g_mmax + b);
                if (left <= REFT && m) break;
                if (left <= 0) { m = 0x80000000u; break; }
                if (it > SPIN_LIMIT) __trap();
                __nanosleep(300);
            }
            asm volatile("st.release.gpu.global.u32 [%0], %1;" ::"l"(g_mref + b), "r"(~u(f(m >> 31 ? m ^ 0x80000000u : ~m) + 8.f)) : "memory");
            TSE(7);
        }
        return;
    } else {
        const int pr = warp & 1;
        const uint4* const pa = g_acc + ((b >> 2) * 2 + pr) * 64 + lane;
        const uint32_t bw = opaque(sb + brow(16 * pr + 8 * ((lane >> 2) & 1) + t) + (lane >> 3) * 16);
        const uint32_t fw = opaque(sb + RD_RDY + pr * 4);
        const uint32_t n0 = packh(0.f, (float)((GS + 1) >> 1)), n1 = packh(0.f, (float)(GS >> 1)), nstart = packh(0.f, (float)POLLN);
        for (int it = 0; ldg_relaxed32(reinterpret_cast<const uint32_t*>(pa - lane) + 3) < nstart; it++)
            if (it > SPIN_LIMIT) __trap();
        for (const unsigned c = clock(); clock() - c < ((warp - 4) >> 1) * PGAP;) {}
        for (int it = 0;; it++) {
            const uint4 a0 = ldg_relaxed(pa), a1 = ldg_relaxed(pa + ACC), b0 = ldg_relaxed(pa + 32), b1 = ldg_relaxed(pa + ACC + 32);
            bar_sync(B_WARP, 32);
            const bool ok = a0.w >= n0 && a1.w >= n1 && b0.w >= n0 && b1.w >= n1, all = __all_sync(~0u, ok);
            const uint32_t w = ok ? bw : bw - (RD_B - RD_QN);
            sts128(w, a0.x, a0.y, a0.z, a0.w); sts128(w + 4 * 144, a1.x, a1.y, a1.z, a1.w);
            sts128(w + 64, b0.x, b0.y, b0.z, b0.w); sts128(w + 4 * 144 + 64, b1.x, b1.y, b1.z, b1.w);
            sts32(all ? fw : fw + 8, 1);
            if (all) break;
            if (it > SPIN_LIMIT) __trap();
        }
        bar_arrive(B_POLL, 352);
        if (warp == 4) {
            if (b < NSRC) g_qk[b * 32 + lane] = make_uint4(0, 0, 0, 0);
            if (lane == 0) { g_mref[b] = 0; if (b == NSRC) g_ctr[0] = 0; }
        }
        return;
    }
    const uint32_t br = opaque(sb + brow(lane));
#pragma unroll 1
    for (uint32_t pass = 0;; pass = 1) {
        uint4 x[8];
        float o[5][4];
        for (int it = 0;; it++) {
            const uint2 rdy = lds64v(sb + RD_RDY);
            x[0] = lds128v(br); x[1] = lds128v(br + 16);
            if (it > 64 * SPIN_LIMIT) __trap();
            if (rdy.x & rdy.y) break;
        }
        if (threadIdx.x == 0) TSX(8, 0);
#pragma unroll
        for (int j = 2; j < 8; j++) x[j] = lds128v(br + j * 16);
#pragma unroll
        for (int j = 0; j < 5; j++) o[j][0] = o[j][1] = o[j][2] = o[j][3] = 0.f;
#pragma unroll
        for (int i = 0; i < 4; i++) {
            mmah(o[3 + (i & 1)], 0x3C00u, 0x3C00u, 0x3C00u, 0x3C00u, x[2 * i].w, x[2 * i + 1].w);
            mmah(o[0], wa[2 * i][0], wa[2 * i][1], wa[2 * i][2], wa[2 * i][3], x[2 * i].x, x[2 * i].y);
            mmah(o[1], wa[2 * i + 1][0], wa[2 * i + 1][1], wa[2 * i + 1][2], wa[2 * i + 1][3], x[2 * i + 1].x, x[2 * i + 1].y);
            mmah(o[2], wa[8 + i][0], wa[8 + i][1], wa[8 + i][2], wa[8 + i][3], x[2 * i].z, x[2 * i + 1].z);
        }
        const float L = (o[3][0] + o[3][1]) + (o[4][0] + o[4][1]), r = rcp(L);
        const float y0 = ((o[0][0] + o[0][1]) + (o[1][0] + o[1][1])) + (o[2][0] + o[2][1]);
        const float y1 = ((o[0][2] + o[0][3]) + (o[1][2] + o[1][3])) + (o[2][2] + o[2][3]);
        const uint32_t y = pack2(fmaf(y0, r * ws0, qv0), fmaf(y1, r * ws1, qv1));
        asm volatile("{.reg .b16 l, h; mov.b32 {l, h}, %1; st.global.b16 [%0], l; st.global.b16 [%0 + 16], h;}" ::"l"(op), "r"(y) : "memory");
        if (threadIdx.x == 0) TSD(11, y);
        if (__builtin_expect(__all_sync(~0u, L >= 0.001953125f && L <= 2048.f && fabsf(y0) < INFINITY) || pass, 1)) break;
        const uint32_t keep = sb + RD_W + 32768 + warp * 6144 + lane * 16;
#pragma unroll
        for (int kk = 0; kk < 12; kk++) sts128(keep + kk * 512, wa[kk][0], wa[kk][1], wa[kk][2], wa[kk][3]);
        slow_rows(f0, f1, q, wq, wk, sb);
#pragma unroll
        for (int kk = 0; kk < 12; kk++) {
            const uint4 v = lds128(keep + kk * 512);
            wa[kk][0] = v.x; wa[kk][1] = v.y; wa[kk][2] = v.z; wa[kk][3] = v.w;
        }
    }
}

__global__ void __launch_bounds__(NTHREADS, 1)
attn_main(const char* __restrict__ f0, const char* __restrict__ f1,
          const __nv_bfloat16* __restrict__ q, const __nv_bfloat16* __restrict__ wq, const __nv_bfloat16* __restrict__ wk, Scratch* scr,
          const __nv_bfloat16* __restrict__ wv, const __nv_bfloat16* __restrict__ wo, __nv_bfloat16* __restrict__ out,
          const __grid_constant__ CUtensorMap m0, const __grid_constant__ CUtensorMap m1)
{
    extern __shared__ char smem_raw[];
    const uint32_t sb = (s2u(smem_raw) + 1023u) & ~1023u;
    const int G = gridDim.x - NRD;
    if (blockIdx.x < NRD) { reducer(f0, f1, q, wq, wk, scr, wv, wo, out, sb, G); return; }
    const int b = blockIdx.x - NRD;
    const int warp = __shfl_sync(~0u, threadIdx.x >> 5, 0), lane = threadIdx.x & 31;
    const int g = lane >> 2, t = lane & 3;

    if (warp >= 8) {
        if (warp < 10) {
            const int p = warp - 8;
            if (lane == 0) {
                if (p == 0) TS(0);
                asm volatile("prefetch.tensormap [%0];" ::"l"(p ? &m1 : &m0) : "memory");
            }
            if (lane < NS / 2) {
                const int s = 2 * lane + p;
                mbar_init(sb + SM_BAR + s * 8, 1); mbar_init(sb + SM_BAR + (NS + s) * 8, 1);
            }
            if (p == 0 && lane == 31) mbar_init(sb + SM_REF, 1);
            asm volatile("fence.mbarrier_init.release.cluster;" ::: "memory");
            __syncwarp();
            bar_arrive(B_QK, 384);
            if (lane == 0) {
                uint64_t pol; asm volatile("createpolicy.fractional.L2::evict_first.b64 %0, 1.0;" : "=l"(pol));
                int s = p; uint32_t ph = 1;
                int sa = p, na = 0; uint32_t pa = 0;
                int tl = b + p * G;
                bool late = false;
                for (int n = 0;; n++) {
                    int nxt = tl + 2 * G;
                    if (n >= NST - 1) nxt = grab_tile(g_ctr) + 2 * NST * G;
                    const int d = n < NRAMP ? D0 : (tl >= NT - TAILT ? D2 : D1);
                    while (n - na >= d) {
                        mbar_wait(sb + SM_BAR + sa * 8, pa);
                        if (na < NS / 2) TR(1, 2 * na + p);
                        na++; sa += 2;
                        if (sa >= NS) { sa -= NS; pa ^= 1; }
                    }
                    mbar_wait(sb + SM_BAR + (NS + s) * 8, ph);
                    const bool last = nxt >= NT;
                    uint32_t flag = last;
                    if (!late && nxt >= NT - MAXT - 16 * b) { late = true; flag |= 2; }
                    if (last) mbar_wait(sb + SM_REF, 0);
                    sts32(sb + SM_FLAG + s * 4, flag);
                    issue_tile(&m0, &m1, sb, s, tl, pol);
                    TR(0, 2 * n + p);
                    if (last) break;
                    s += 2;
                    if (s >= NS) { s -= NS; ph ^= 1; }
                    tl = nxt;
                }
                if (p) TSE(5);
            }
            return;
        }
        const int h = threadIdx.x - 320;
        uint4 v[6];
        for (int it = 0;; it++) {
            bool miss = false;
#pragma unroll
            for (int k = 0; k < 6; k++) v[k] = ldg_relaxed(g_qk + k * 64 + h);
#pragma unroll
            for (int k = 0; k < 6; k++) miss |= has(v[k], 0);
            if (!miss) break;
            if (it > SPIN_LIMIT) __trap();
            if (it == 0) __nanosleep(QSLEEP);
        }
#pragma unroll
        for (int k = 0; k < 6; k++) sts128(sb + SM_QK + (k * 64 + h) * 16, ~v[k].x, ~v[k].y, ~v[k].z, ~v[k].w);
        __syncwarp();
        bar_sync(B_QK, 384);
        if (warp == 11) return;
        uint32_t r = 1;
        for (int it = 0;; it++) {
            __nanosleep(500);
            if (lane < NQ) asm volatile("ld.acquire.gpu.global.u32 %0, [%1];" : "=r"(r) : "l"(g_mref + lane) : "memory");
            if (__all_sync(~0u, r != 0)) break;
            if (it > SPIN_LIMIT) __trap();
        }
        if (lane < NQ) sts32(sb + SM_M + lane * 4, ~r);
        __syncwarp();
        if (lane == 0) { mbar_arrive(sb + SM_REF); TSE(7); }
        return;
    }

    const int grp = warp >> 2, cw = warp & 3;
    if (lane == 0) {
        const char* a; int sz;
        if (warp >= 6) {
            sz = C * C * 2 / WSL; a = (const char*)(warp == 6 ? wq : wk) + (b % WSL) * sz;
        } else {
            const int tl = b + (warp / 3) * G, which = warp % 3;
            const int par = tl * TP, y = par >> 8, x = par & 255;
            a = which < 2 ? f0 + ((size_t)(2 * y + which) * W0 + 2 * x) * (C * 2) : f1 + ((size_t)y * W1 + x) * (C * 2);
            sz = which < 2 ? TP * 2 * C * 2 : TP * C * 2;
        }
        if (warp >= 6 || warp < 3 * NPRE) asm volatile("cp.async.bulk.prefetch.L2.global [%0], %1;" ::"l"(a), "r"(sz) : "memory");
    }

    const int xp = lane & 7, mi = lane >> 3;
    const uint32_t offS1 = opaque(12288 + xp * 128 + ((mi ^ xp) << 4)), offS1x = opaque(offS1 ^ 64);
    const uint32_t offS0 = opaque(offS1 - 12288 + cw * 3072), offS0x = opaque(offS0 ^ 64);
    const uint32_t offT = opaque(mi * 3072 + xp * 128 + (((cw + 4 * grp) ^ xp) << 4)), offTx = opaque(offT ^ 64);
    const uint32_t offU = opaque(12288 + (mi % 3) * 1024 + xp * 128 + (((cw + 4 * (grp ^ (mi / 3))) ^ xp) << 4));
    const uint32_t offV = opaque(12288 + (1 + (mi & 1)) * 1024 + xp * 128 + (((cw + 4 * (grp ^ 1)) ^ xp) << 4));
    const int shl = opaque(9 * t), shl4 = opaque(9 * t + 4);
    const uint32_t pw = opaque((cw >> 1) * 512 + lane * 16 + (cw & 1) * 8), muw = opaque(1024 + t * 16 + cw * 4);
    const uint32_t prd = opaque(lane * 16), mur = opaque(1024 + t * 16);
    uint32_t pb0 = sb + SM_P + grp * 2 * PBUF;
    const uint32_t pbx = pb0 ^ (pb0 + PBUF);
    const bool odd = g & 1;
    const int barid = B_GRP + grp;
    const bool elected = cw == 3 && lane == 0;

    uint32_t qa[48];
    float r_lo, r_hi;
    bar_sync(B_QK, 384);
    {
        float rr[2][4] = {{0.f, 0.f, 0.f, 0.f}, {0.f, 0.f, 0.f, 0.f}};
#pragma unroll
        for (int kk = 0; kk < 12; kk++) {
            const uint4 v = lds128(sb + SM_QK + kk * 512 + lane * 16);
            qa[4 * kk] = v.x; qa[4 * kk + 1] = v.y; qa[4 * kk + 2] = v.z; qa[4 * kk + 3] = v.w;
            mma(rr[kk & 1], v.x, v.y, v.z, v.w, ONES, ONES);
        }
        r_lo = rr[0][0] + rr[1][0]; r_hi = rr[0][2] + rr[1][2];
    }
    if (threadIdx.x == 0) TS(1);

    float acc[6][4];
#pragma unroll
    for (int i = 0; i < 6; i++) acc[i][0] = acc[i][1] = acc[i][2] = acc[i][3] = 0.f;
    float m_lo = -INFINITY, m_hi = -INFINITY, l_lo = 0.f, l_hi = 0.f;
    float cm[4] = {0.f, 0.f, 0.f, 0.f};
    uint32_t xt[6][4], yt[6]; uint4 pa, pb, mv;
    int s = grp; uint32_t ph = 0;
    while (true) {
        mbar_wait(sb + SM_BAR + s * 8, ph);
        PH(0, 0);
        const uint32_t stop = lds32(sb + SM_FLAG + s * 4);
        const uint32_t st = sb + SM_STAGES + s * STAGE;
        float sc[2][4], gr[4][4], sx[4];
#pragma unroll
        for (int e = 0; e < 4; e++) sc[0][e] = sc[1][e] = gr[0][e] = gr[1][e] = gr[2][e] = gr[3][e] = sx[e] = 0.f;
#pragma unroll
        for (int qq = 0; qq < 6; qq++) {
            uint32_t x[4], y[4];
            ldsm4(x, st + (qq & 1 ? offS0x : offS0) + (qq >> 1) * 1024);
            ldsm4(y, st + (qq & 1 ? offS1x : offS1) + (qq >> 1) * 1024);
#pragma unroll
            for (int e = 0; e < 4; e++) x[e] = hadd2(x[e], y[e]);
            mma8(gr[0], x[0], x[1], x[0]);
            mma8(gr[1], x[0], x[1], x[1]);
            mma(sx, x[0], x[1], x[2], x[3], ONES, ONES);
            mma8(gr[GR4 ? 2 : 0], x[2], x[3], x[2]);
            mma8(gr[GR4 ? 3 : 1], x[2], x[3], x[3]);
            mma(sc[0], qa[8 * qq], qa[8 * qq + 1], qa[8 * qq + 2], qa[8 * qq + 3], x[0], x[1]);
            mma(sc[1], qa[8 * qq + 4], qa[8 * qq + 5], qa[8 * qq + 6], qa[8 * qq + 7], x[2], x[3]);
        }
        ldsm4t(yt, st + offU);
        ldsm2t(yt + 4, st + offV);
#pragma unroll
        for (int i = 0; i < 6; i++) ldsm4t(xt[i], st + (i < 3 ? offT : offTx) + (i % 3) * 1024);

        const float mu = (sx[0] + sx[2]) * (1.f / C), ss = GR4 ? (odd ? (gr[0][1] + gr[1][3]) + (gr[2][1] + gr[3][3]) : (gr[0][0] + gr[1][2]) + (gr[2][0] + gr[3][2])) : (odd ? gr[0][1] + gr[1][3] : gr[0][0] + gr[1][2]);
        const float rs = rsq(fmaxf(fmaf(-mu, mu, ss * (1.f / C)), 0.f) + 1e-5f);
        const float mu0 = __shfl_sync(~0u, mu, shl), mu1 = __shfl_sync(~0u, mu, shl4);
        const float rs0 = __shfl_sync(~0u, rs, shl), rs1 = __shfl_sync(~0u, rs, shl4);
        const float u0 = fmaf(-mu0, r_lo, sc[0][0] + sc[1][0]), u1 = fmaf(-mu1, r_lo, sc[0][1] + sc[1][1]);
        const float u2 = fmaf(-mu0, r_hi, sc[0][2] + sc[1][2]), u3 = fmaf(-mu1, r_hi, sc[0][3] + sc[1][3]);
        const float d0 = fmaf(u0, rs0, -m_lo), d1 = fmaf(u1, rs1, -m_lo), d2 = fmaf(u2, rs0, -m_hi), d3 = fmaf(u3, rs1, -m_hi);
        PH(1, u(d0 + d2));
        float p0 = ex2(d0), p1 = ex2(d1), p2 = ex2(d2), p3 = ex2(d3);
        sts64(pb0 + pw, pack2(p0 * rs0, p1 * rs1), pack2(p2 * rs0, p3 * rs1));
        if (lane < 4) sts32(pb0 + muw, pack2(mu0, mu1));
        const bool over = bar_any(barid, 128, fmaxf(fmaxf(d0, d1), fmaxf(d2, d3)) > LAZY);
        PH(3, 0);
        pa = lds128(pb0 + prd); pb = lds128(pb0 + prd + 512); mv = lds128(pb0 + mur);
        if (elected) mbar_arrive(sb + SM_BAR + (NS + s) * 8);
        if (__builtin_expect(over, 0)) {
            const float s0 = u0 * rs0, s1 = u1 * rs1, s2 = u2 * rs0, s3 = u3 * rs1;
            float xl = fmaxf(s0, s1), xh = fmaxf(s2, s3);
            xl = fmaxf(xl, __shfl_xor_sync(~0u, xl, 1)); xh = fmaxf(xh, __shfl_xor_sync(~0u, xh, 1));
            xl = fmaxf(xl, __shfl_xor_sync(~0u, xl, 2)); xh = fmaxf(xh, __shfl_xor_sync(~0u, xh, 2));
            if (t < 2) sts32(sb + SM_MX + grp * 256 + ((g + 8 * t) * 4 + cw) * 4, u(t ? xh : xl));
            bar_sync(B_MAX + grp, 128);
            const uint4 ml4 = lds128(sb + SM_MX + grp * 256 + g * 16), mh4 = lds128(sb + SM_MX + grp * 256 + g * 16 + 128);
            const float nl = fmaxf(fmaxf(fmaxf(f(ml4.x), f(ml4.y)), fmaxf(f(ml4.z), f(ml4.w))), m_lo);
            const float nh = fmaxf(fmaxf(fmaxf(f(mh4.x), f(mh4.y)), fmaxf(f(mh4.z), f(mh4.w))), m_hi);
            p0 = ex2(s0 - nl); p1 = ex2(s1 - nl); p2 = ex2(s2 - nh); p3 = ex2(s3 - nh);
            sts64(pb0 + pw, pack2(p0 * rs0, p1 * rs1), pack2(p2 * rs0, p3 * rs1));
            const float al = ex2(m_lo - nl), ah = ex2(m_hi - nh);
            m_lo = nl; m_hi = nh;
            l_lo *= al; l_hi *= ah; cm[0] *= al; cm[2] *= ah;
#pragma unroll
            for (int i = 0; i < 6; i++) { acc[i][0] *= al; acc[i][1] *= al; acc[i][2] *= ah; acc[i][3] *= ah; }
            bar_sync(B_MAX + grp, 128);
            pa = lds128(pb0 + prd); pb = lds128(pb0 + prd + 512);
        }
        l_lo += p0 + p1; l_hi += p2 + p3;
        if (stop & 1) break;
#pragma unroll
        for (int i = 0; i < 6; i++) mma(acc[i], pa.x, pa.y, pa.z, pa.w, hadd2v(xt[i][0], yt[i]), hadd2v(xt[i][1], yt[i]));
        mma(cm, pa.x, pa.y, pa.z, pa.w, mv.x, mv.y);
#pragma unroll
        for (int i = 0; i < 6; i++) mma(acc[i], pb.x, pb.y, pb.z, pb.w, hadd2v(xt[i][2], yt[i]), hadd2v(xt[i][3], yt[i]));
        mma(cm, pb.x, pb.y, pb.z, pb.w, mv.z, mv.w);
        PH(4, u(acc[5][0]));
        if (stop) {
            float a = l_lo + __shfl_xor_sync(~0u, l_lo, 1), c = l_hi + __shfl_xor_sync(~0u, l_hi, 1);
            a += __shfl_xor_sync(~0u, a, 2); c += __shfl_xor_sync(~0u, c, 2);
            const uint32_t m = u((t ? m_hi : m_lo) + lg2(fmaxf(t ? c : a, 1.f)));
            if (t < 2) asm volatile("red.relaxed.gpu.global.max.u32 [%0], %1;" ::"l"(g_mmax + g + 8 * t), "r"(m >> 31 ? ~m : m | 0x80000000u) : "memory");
        }
        pb0 ^= pbx;
        s += 2;
        if (s >= NS) { s -= NS; ph ^= 1; }
    }
    const float al = ex2(m_lo - f(lds32(sb + SM_M + g * 4))), ah = ex2(m_hi - f(lds32(sb + SM_M + 32 + g * 4)));
    mma(cm, pa.x, pa.y, pa.z, pa.w, mv.x, mv.y);
#pragma unroll
    for (int i = 3; i < 6; i++) mma(acc[i], pa.x, pa.y, pa.z, pa.w, hadd2v(xt[i][0], yt[i]), hadd2v(xt[i][1], yt[i]));
    mma(cm, pb.x, pb.y, pb.z, pb.w, mv.z, mv.w);
#pragma unroll
    for (int i = 3; i < 6; i++) mma(acc[i], pb.x, pb.y, pb.z, pb.w, hadd2v(xt[i][2], yt[i]), hadd2v(xt[i][3], yt[i]));
#pragma unroll
    for (int i = 0; i < 3; i++) mma(acc[i], pa.x, pa.y, pa.z, pa.w, hadd2v(xt[i][0], yt[i]), hadd2v(xt[i][1], yt[i]));
#pragma unroll
    for (int i = 0; i < 3; i++) mma(acc[i], pb.x, pb.y, pb.z, pb.w, hadd2v(xt[i][2], yt[i]), hadd2v(xt[i][3], yt[i]));
    if (threadIdx.x == grp * 128) TSE(2 + grp);
    if (threadIdx.x == grp * 128 + 96) TSX(2 + grp, u(acc[5][0]));

    uint4* const dst = g_acc + (b & 1) * ACC + ((g >> 1) * 8 + cw + 4 * grp) * 8 + (lane & 7);
    const uint32_t xw = opaque(sb + SM_STAGES + grp * STAGE + cw * 1536 + lane * 16), xr = opaque(sb + SM_STAGES + (grp ^ 1) * STAGE + cw * 1536 + lane * 16);
    asm volatile("" ::"l"(dst));
    const float cl = -cm[0] * al, ch = -cm[2] * ah;
#pragma unroll
    for (int i = 0; i < 3; i++)
        sts128(xw + i * 512, u(fmaf(acc[3 + i][0], al, cl)), u(fmaf(acc[3 + i][1], al, cl)), u(fmaf(acc[3 + i][2], ah, ch)), u(fmaf(acc[3 + i][3], ah, ch)));
#pragma unroll
    for (int i = 0; i < 3; i++) { acc[i][0] = fmaf(acc[i][0], al, cl); acc[i][1] = fmaf(acc[i][1], al, cl); acc[i][2] = fmaf(acc[i][2], ah, ch); acc[i][3] = fmaf(acc[i][3], ah, ch); }
    const uint32_t w_lo = packh(l_lo * al, 1.f), w_hi = packh(l_hi * ah, 1.f);
    bar_sync(B_MERGE, 256);
    if (threadIdx.x == 224) TSX(4, 0);
    uint4 o[3];
#pragma unroll
    for (int i = 0; i < 3; i++) o[i] = lds128(xr + i * 512);
    red8h(dst, packh(acc[0][0] + f(o[0].x), acc[0][1] + f(o[0].y)), packh(acc[1][0] + f(o[1].x), acc[1][1] + f(o[1].y)), packh(acc[2][0] + f(o[2].x), acc[2][1] + f(o[2].y)), w_lo);
    red8h(dst + 256, packh(acc[0][2] + f(o[0].z), acc[0][3] + f(o[0].w)), packh(acc[1][2] + f(o[1].z), acc[1][3] + f(o[1].w)), packh(acc[2][2] + f(o[2].z), acc[2][3] + f(o[2].w)), w_hi);
    if (threadIdx.x == 0) TSE(4);
    if (threadIdx.x == 224) TSX(9, 0);
}

typedef CUresult (*EncodeFn)(CUtensorMap*, CUtensorMapDataType, cuuint32_t, void*, const cuuint64_t*, const cuuint64_t*,
                             const cuuint32_t*, const cuuint32_t*, CUtensorMapInterleave, CUtensorMapSwizzle,
                             CUtensorMapL2promotion, CUtensorMapFloatOOBfill);

}

extern "C" void kernel_launch(void* const* d_in, const int* in_sizes, int n_in, void* d_out, int out_size) {
    const __nv_bfloat16* q = (const __nv_bfloat16*)d_in[0];
    char* f0 = (char*)d_in[1];
    char* f1 = (char*)d_in[2];
    const __nv_bfloat16* wq = (const __nv_bfloat16*)d_in[3];
    const __nv_bfloat16* wk = (const __nv_bfloat16*)d_in[4];
    const __nv_bfloat16* wv = (const __nv_bfloat16*)d_in[5];
    const __nv_bfloat16* wo = (const __nv_bfloat16*)d_in[6];

    static EncodeFn enc = nullptr;
    static int grid = 0;
    static Scratch* scr = nullptr;
    if (!enc) {
        void* fn = nullptr; cudaDriverEntryPointQueryResult qr;
        cudaGetDriverEntryPoint("cuTensorMapEncodeTiled", &fn, cudaEnableDefault, &qr);
        enc = (EncodeFn)fn;
        cudaGetSymbolAddress((void**)&scr, g_scratch);
        int dev = 0, sms = 0;
        cudaGetDevice(&dev);
        cudaDeviceGetAttribute(&sms, cudaDevAttrMultiProcessorCount, dev);
        grid = sms < MAXG ? sms : MAXG;
        cudaFuncSetAttribute(attn_main, cudaFuncAttributeMaxDynamicSharedMemorySize, SMEM_BYTES);
    }
    CUtensorMap m0, m1;
    {
        cuuint64_t dims[5] = {64, W1, 3, 2, W0};
        cuuint64_t str[4] = {2 * C * 2, 128, C * 2, (cuuint64_t)W0 * C * 2};
        cuuint32_t box[5] = {64, TP, 3, 2, 2}, es[5] = {1, 1, 1, 1, 1};
        enc(&m0, CU_TENSOR_MAP_DATA_TYPE_BFLOAT16, 5, f0, dims, str, box, es, CU_TENSOR_MAP_INTERLEAVE_NONE,
            CU_TENSOR_MAP_SWIZZLE_128B, CU_TENSOR_MAP_L2_PROMOTION_NONE, CU_TENSOR_MAP_FLOAT_OOB_FILL_NONE);
    }
    {
        cuuint64_t dims[4] = {64, W1, 3, W1};
        cuuint64_t str[3] = {C * 2, 128, (cuuint64_t)W1 * C * 2};
        cuuint32_t box[4] = {64, TP, 3, 1}, es[4] = {1, 1, 1, 1};
        enc(&m1, CU_TENSOR_MAP_DATA_TYPE_BFLOAT16, 4, f1, dims, str, box, es, CU_TENSOR_MAP_INTERLEAVE_NONE,
            CU_TENSOR_MAP_SWIZZLE_128B, CU_TENSOR_MAP_L2_PROMOTION_NONE, CU_TENSOR_MAP_FLOAT_OOB_FILL_NONE);
    }
    attn_main<<<grid, NTHREADS, SMEM_BYTES, cudaStreamPerThread>>>(f0, f1, q, wq, wk, scr, wv, wo, (__nv_bfloat16*)d_out, m0, m1);
}
```

```cpp
#include <cuda_runtime.h>
#include <cuda_bf16.h>
#include <cuda.h>
#include <stdint.h>

namespace {

constexpr int C = 192;
constexpr int NQ = 16;
constexpr int W0 = 512;
constexpr int W1 = 256;
constexpr int TP = 8;
constexpr int NT = W1 * W1 / TP;
constexpr int STAGE = TP * 5 * C * 2;
#define NS 14
#define D0 3
#define D1 2
#define D2 1
#define NRAMP 5
#define TAILT 150
#define QSLEEP 700
#define WSL 24
#define MAXT 3000
#define REFT 1800
#define POLLN 1
#define PGAP 110
#define LAZY 12.f
#define GR4 1
#define NST 4
#define NI 1
#define NPACE 5
#define T0 0
#define T1 1600
#define TG 960
#define PFX 0
#define TAILP TAILT
#define LATE 1
#define WFIRST 1
static_assert(NST > D0, "the first dynamic tile index must not delay the start");
constexpr int NTHREADS = 384;
constexpr int MAXG = 132;
constexpr int NRD = NQ;
constexpr int ACC = NQ * 32;
constexpr int NSRC = 12;
constexpr int SPIN_LIMIT = 1 << 22;

constexpr int SM_STAGES = 0;
constexpr int SM_P = NS * STAGE;
constexpr int PBUF = 1088;
constexpr int SM_QK = SM_P + 4 * PBUF;
constexpr int SM_MX = SM_QK + 6144;
constexpr int SM_M = SM_MX + 512;
constexpr int SM_BAR = SM_M + 64;
constexpr int SM_REF = SM_BAR + 16 * NS;
constexpr int SM_FLAG = SM_REF + 8;
constexpr int SM_TOTAL = SM_FLAG + 4 * NS;
constexpr int SMEM_BYTES = SM_TOTAL + 1024;
static_assert(SMEM_BYTES <= 232448, "smem");
constexpr int WROW = 400;
constexpr int RD_W = 0;
constexpr int RD_QN = 2 * C * WROW;
constexpr int RD_KQ = RD_QN + 6144;
constexpr int RD_B = RD_KQ + 7168;
constexpr int RD_RDY = RD_B + 32 * 144 + 256;
constexpr int RD_BAR = RD_RDY + 16;
static_assert(RD_BAR + 64 <= SM_TOTAL, "smem");

struct Scratch {
    uint4 acc[2 * ACC];
    uint4 qk[NSRC * 32];
    unsigned ctr[32];
    unsigned mmax[32];
    unsigned mref[32];
};
__device__ __align__(128) Scratch g_scratch;
#define g_acc (scr->acc)
#define g_qk (scr->qk)
#define g_ctr (scr->ctr)
#define g_mmax (scr->mmax)
#define g_mref (scr->mref)
#define g_ts (scr->ts)
#define g_tr (scr->tr)
#define TR(k, i) do {} while (0)
#define TS(i) do {} while (0)
#define TSD(i, dep) do {} while (0)
#define TSX(i, dep) do {} while (0)
#define TSP(i, dep) do {} while (0)
#define TSE(i) TS(i)
#define CK_(i, dep) do {} while (0)
#define PH(i, dep) do {} while (0)

__device__ __forceinline__ uint32_t s2u(const void* p) { return (uint32_t)__cvta_generic_to_shared(p); }
__device__ __forceinline__ void mbar_init(uint32_t a, int c) { asm volatile("mbarrier.init.shared::cta.b64 [%0], %1;" ::"r"(a), "r"(c) : "memory"); }
__device__ __forceinline__ void mbar_expect(uint32_t a, uint32_t b) { asm volatile("mbarrier.arrive.expect_tx.shared::cta.b64 _, [%0], %1;" ::"r"(a), "r"(b) : "memory"); }
__device__ __forceinline__ void mbar_arrive(uint32_t a) { asm volatile("mbarrier.arrive.shared::cta.b64 _, [%0];" ::"r"(a) : "memory"); }
__device__ __forceinline__ void mbar_wait(uint32_t a, uint32_t ph) {
    uint32_t ok; int it = 0;
    do {
        asm volatile("{.reg .pred p; mbarrier.try_wait.parity.shared::cta.b64 p, [%1], %2; selp.u32 %0,1,0,p;}" : "=r"(ok) : "r"(a), "r"(ph) : "memory");
        if (++it > SPIN_LIMIT) __trap();
    } while (!ok);
}
__device__ __forceinline__ bool elect() {
    uint32_t r; asm volatile("{.reg .pred p; elect.sync _|p, 0xffffffff; selp.u32 %0, 1, 0, p;}" : "=r"(r)); return r;
}
__device__ __forceinline__ void bar_sync(int id, int n) { asm volatile("bar.sync %0, %1;" ::"r"(id), "r"(n) : "memory"); }
__device__ __forceinline__ bool bar_any(int id, int n, bool c) {
    uint32_t r;
    asm volatile("{.reg .pred p, q; setp.ne.u32 q, %3, 0; bar.red.or.pred p, %1, %2, q; selp.u32 %0, 1, 0, p;}" : "=r"(r) : "r"(id), "r"(n), "r"((uint32_t)c) : "memory");
    return r;
}
__device__ __forceinline__ void bar_arrive(int id, int n) { asm volatile("bar.arrive %0, %1;" ::"r"(id), "r"(n) : "memory"); }
__device__ __forceinline__ void ldsm4(uint32_t* r, uint32_t a) {
    asm volatile("ldmatrix.sync.aligned.m8n8.x4.shared.b16 {%0,%1,%2,%3}, [%4];" : "=r"(r[0]), "=r"(r[1]), "=r"(r[2]), "=r"(r[3]) : "r"(a) : "memory");
}
__device__ __forceinline__ void ldsm4t(uint32_t* r, uint32_t a) {
    asm volatile("ldmatrix.sync.aligned.m8n8.x4.trans.shared.b16 {%0,%1,%2,%3}, [%4];" : "=r"(r[0]), "=r"(r[1]), "=r"(r[2]), "=r"(r[3]) : "r"(a) : "memory");
}
__device__ __forceinline__ void ldsm2t(uint32_t* r, uint32_t a) {
    asm volatile("ldmatrix.sync.aligned.m8n8.x2.trans.shared.b16 {%0,%1}, [%2];" : "=r"(r[0]), "=r"(r[1]) : "r"(a) : "memory");
}
__device__ __forceinline__ void mma(float* d, uint32_t a0, uint32_t a1, uint32_t a2, uint32_t a3, uint32_t b0, uint32_t b1) {
    asm("mma.sync.aligned.m16n8k16.row.col.f32.bf16.bf16.f32 {%0,%1,%2,%3}, {%4,%5,%6,%7}, {%8,%9}, {%0,%1,%2,%3};"
        : "+f"(d[0]), "+f"(d[1]), "+f"(d[2]), "+f"(d[3]) : "r"(a0), "r"(a1), "r"(a2), "r"(a3), "r"(b0), "r"(b1));
}
__device__ __forceinline__ void mmah(float* d, uint32_t a0, uint32_t a1, uint32_t a2, uint32_t a3, uint32_t b0, uint32_t b1) {
    asm("mma.sync.aligned.m16n8k16.row.col.f32.f16.f16.f32 {%0,%1,%2,%3}, {%4,%5,%6,%7}, {%8,%9}, {%0,%1,%2,%3};"
        : "+f"(d[0]), "+f"(d[1]), "+f"(d[2]), "+f"(d[3]) : "r"(a0), "r"(a1), "r"(a2), "r"(a3), "r"(b0), "r"(b1));
}
__device__ __forceinline__ void mma8(float* d, uint32_t a0, uint32_t a1, uint32_t b0) {
    asm("mma.sync.aligned.m16n8k8.row.col.f32.bf16.bf16.f32 {%0,%1,%2,%3}, {%4,%5}, {%6}, {%0,%1,%2,%3};"
        : "+f"(d[0]), "+f"(d[1]), "+f"(d[2]), "+f"(d[3]) : "r"(a0), "r"(a1), "r"(b0));
}
__device__ __forceinline__ uint32_t hadd2(uint32_t a, uint32_t b) {
    uint32_t r; asm("add.rn.bf16x2 %0, %1, %2;" : "=r"(r) : "r"(a), "r"(b)); return r;
}
__device__ __forceinline__ uint32_t pack2(float lo, float hi) {
    uint32_t r; asm("cvt.rn.bf16x2.f32 %0, %1, %2;" : "=r"(r) : "f"(hi), "f"(lo)); return r;
}
__device__ __forceinline__ uint32_t packh(float lo, float hi) {
    uint32_t r; asm("cvt.rn.f16x2.f32 %0, %1, %2;" : "=r"(r) : "f"(hi), "f"(lo)); return r;
}
__device__ __forceinline__ float2 unpackh(uint32_t v) {
    float2 r; asm("{.reg .b16 l, h; mov.b32 {l, h}, %2; cvt.f32.f16 %0, l; cvt.f32.f16 %1, h;}" : "=f"(r.x), "=f"(r.y) : "r"(v)); return r;
}
__device__ __forceinline__ float bflo(uint32_t v) { return __uint_as_float(v << 16); }
__device__ __forceinline__ float bfhi(uint32_t v) { return __uint_as_float(v & 0xffff0000u); }
__device__ __forceinline__ float ex2(float x) { float r; asm("ex2.approx.ftz.f32 %0, %1;" : "=f"(r) : "f"(x)); return r; }
__device__ __forceinline__ void sts128(uint32_t a, uint32_t x, uint32_t y, uint32_t z, uint32_t w) {
    asm volatile("st.shared.v4.b32 [%0], {%1,%2,%3,%4};" ::"r"(a), "r"(x), "r"(y), "r"(z), "r"(w) : "memory");
}
__device__ __forceinline__ void sts64(uint32_t a, uint32_t x, uint32_t y) {
    asm volatile("st.shared.v2.b32 [%0], {%1,%2};" ::"r"(a), "r"(x), "r"(y) : "memory");
}
__device__ __forceinline__ void sts32(uint32_t a, uint32_t x) { asm volatile("st.shared.b32 [%0], %1;" ::"r"(a), "r"(x) : "memory"); }
__device__ __forceinline__ uint4 lds128(uint32_t a) {
    uint4 v; asm volatile("ld.shared.v4.b32 {%0,%1,%2,%3}, [%4];" : "=r"(v.x), "=r"(v.y), "=r"(v.z), "=r"(v.w) : "r"(a) : "memory"); return v;
}
__device__ __forceinline__ uint32_t lds32(uint32_t a) { uint32_t v; asm volatile("ld.shared.b32 %0, [%1];" : "=r"(v) : "r"(a) : "memory"); return v; }
__device__ __forceinline__ int grab_tile(unsigned* ctr) {
    int v; asm volatile("atom.relaxed.gpu.global.inc.u32 %0, [%1], 0x7fffffff;" : "=r"(v) : "l"(ctr) : "memory"); return v;
}
__device__ __forceinline__ uint32_t opaque(uint32_t v) { uint32_t r; asm volatile("mov.b32 %0, %1;" : "=r"(r) : "r"(v)); return r; }
__device__ __forceinline__ unsigned clock32() { unsigned c; asm volatile("mov.u32 %0, %%clock;" : "=r"(c)); return c; }
__device__ __forceinline__ float rsq(float x) { float r; asm("rsqrt.approx.ftz.f32 %0, %1;" : "=f"(r) : "f"(x)); return r; }
__device__ __forceinline__ float rcp(float x) { float r; asm("rcp.approx.ftz.f32 %0, %1;" : "=f"(r) : "f"(x)); return r; }
__device__ __forceinline__ float lg2(float x) { float r; asm("lg2.approx.ftz.f32 %0, %1;" : "=f"(r) : "f"(x)); return r; }
__device__ __forceinline__ float f(uint32_t v) { return __uint_as_float(v); }
__device__ __forceinline__ uint32_t u(float v) { return __float_as_uint(v); }

constexpr uint32_t ONES = 0x3F803F80u;
constexpr float QSCALE = 0.07216878364870322f * 1.4426950408889634f;

__device__ __forceinline__ void issue_tile(const CUtensorMap* m0, const CUtensorMap* m1, uint32_t sb, int s, int tl, uint64_t pol) {
    const uint32_t full = sb + SM_BAR + s * 8, dst = sb + SM_STAGES + s * STAGE;
    const int par = tl * TP, y = par >> 8, x = par & 255;
    mbar_expect(full, STAGE);
    asm volatile("cp.async.bulk.tensor.5d.shared::cluster.global.mbarrier::complete_tx::bytes.L2::cache_hint [%0], [%1, {%3,%4,%3,%3,%5}], [%2], %6;"
                 ::"r"(dst), "l"(m0), "r"(full), "r"(0), "r"(x), "r"(2 * y), "l"(pol) : "memory");
    asm volatile("cp.async.bulk.tensor.4d.shared::cluster.global.mbarrier::complete_tx::bytes.L2::cache_hint [%0], [%1, {%3,%4,%3,%5}], [%2], %6;"
                 ::"r"(dst + TP * 4 * C * 2), "l"(m1), "r"(full), "r"(0), "r"(x), "r"(y), "l"(pol) : "memory");
}

__device__ __forceinline__ void prefetch_l2(const void* a, int n) { asm volatile("cp.async.bulk.prefetch.L2.global [%0], %1;" ::"l"(a), "r"(n) : "memory"); }
__device__ __forceinline__ uint4 ldg_relaxed(const uint4* p) {
    uint4 v; asm volatile("ld.relaxed.gpu.global.v4.u32 {%0,%1,%2,%3}, [%4];" : "=r"(v.x), "=r"(v.y), "=r"(v.z), "=r"(v.w) : "l"(p) : "memory"); return v;
}
__device__ __forceinline__ uint32_t ldg_relaxed32(const void* p) {
    uint32_t v; asm volatile("ld.relaxed.gpu.global.u32 %0, [%1];" : "=r"(v) : "l"(p) : "memory"); return v;
}
__device__ __forceinline__ void stg_relaxed(uint4* p, uint32_t x, uint32_t y, uint32_t z, uint32_t w) {
    asm volatile("st.relaxed.gpu.global.v4.u32 [%0], {%1,%2,%3,%4};" ::"l"(p), "r"(x), "r"(y), "r"(z), "r"(w) : "memory");
}
__device__ __forceinline__ void stg_relaxed32(void* p, uint32_t x) { asm volatile("st.relaxed.gpu.global.u32 [%0], %1;" ::"l"(p), "r"(x) : "memory"); }
__device__ __forceinline__ bool has(const uint4& v, uint32_t m) { return v.x == m || v.y == m || v.z == m || v.w == m; }
__device__ __forceinline__ uint32_t hadd2v(uint32_t a, uint32_t b) {
    uint32_t r; asm volatile("add.rn.bf16x2 %0, %1, %2;" : "=r"(r) : "r"(a), "r"(b)); return r;
}

__device__ __forceinline__ void red8h(uint4* p, uint32_t x, uint32_t y, uint32_t z, uint32_t w) {
    asm volatile("red.relaxed.gpu.global.add.noftz.v4.f16x2 [%0], {%1,%2,%3,%4};" ::"l"(p), "r"(x), "r"(y), "r"(z), "r"(w) : "memory");
}
__device__ __forceinline__ uint2 lds64v(uint32_t a) {
    uint2 v; asm volatile("ld.volatile.shared.v2.b32 {%0,%1}, [%2];" : "=r"(v.x), "=r"(v.y) : "r"(a) : "memory"); return v;
}
__device__ __forceinline__ uint4 lds128v(uint32_t a) {
    uint4 v; asm volatile("ld.volatile.shared.v4.b32 {%0,%1,%2,%3}, [%4];" : "=r"(v.x), "=r"(v.y), "=r"(v.z), "=r"(v.w) : "r"(a) : "memory"); return v;
}
__device__ __forceinline__ uint32_t brow(int r) { return RD_B + r * 144 + (r >> 3) * 64; }

enum { B_QK = 1, B_QN = 2, B_GRP = 3  , B_Q = 5, B_MERGE = 6, B_ALL = 7, B_MAX = 8  , B_WARP = 10, B_POLL = 11, B_SLOW = 12 };

__device__ __noinline__ void slow_rows(const char* __restrict__ f0, const char* __restrict__ f1, const __nv_bfloat16* __restrict__ q,
                                       const __nv_bfloat16* __restrict__ wq, const __nv_bfloat16* __restrict__ wk, const uint32_t sb)
{
    const int warp = threadIdx.x >> 5, lane = threadIdx.x & 31;
    float* const sm = reinterpret_cast<float*>(__cvta_shared_to_generic(sb + RD_W));
    bar_sync(B_POLL, 352);
    for (int i = threadIdx.x; i < 4 * C; i += 96) sm[i] = __bfloat162float(q[(blockIdx.x & 12) * C + i]);
    bar_sync(B_SLOW, 96);
#pragma unroll 1
    for (int j = threadIdx.x; j < 4 * C; j += 96) {
        const float* const x = sm + j / C * C;
        float mu = 0.f, var = 0.f, s = 0.f;
#pragma unroll 1
        for (int i = 0; i < C; i++) mu += x[i];
        mu *= 1.f / C;
#pragma unroll 4
        for (int i = 0; i < C; i++) { var = fmaf(x[i] - mu, x[i] - mu, var); s = fmaf(x[i] - mu, __bfloat162float(wq[i * C + j % C]), s); }
        sm[4 * C + j] = s * rsq(var * (1.f / C) + 1e-5f);
    }
    bar_sync(B_SLOW, 96);
#pragma unroll 1
    for (int j = threadIdx.x; j < 4 * C; j += 96) {
        float s = 0.f;
#pragma unroll 4
        for (int i = 0; i < C; i++) s = fmaf(sm[4 * C + j / C * C + i], __bfloat162float(wk[j % C * C + i]), s);
        sm[j] = s * QSCALE;
    }
    bar_sync(B_SLOW, 96);
    float k[4][6], a[4][6], m[4], l[4];
#pragma unroll
    for (int r = 0; r < 4; r++) {
        m[r] = -INFINITY; l[r] = 0.f;
#pragma unroll
        for (int i = 0; i < 6; i++) { k[r][i] = sm[r * C + 64 * (i >> 1) + 2 * lane + (i & 1)]; a[r][i] = 0.f; }
    }
#pragma unroll 1
    for (int par = warp; par < W1 * W1; par += 3) {
        const uint32_t* p0 = reinterpret_cast<const uint32_t*>(f0 + (size_t)((par >> 8) * 2 * W0 + (par & 255) * 2) * (C * 2)) + lane;
        const uint32_t* p1 = reinterpret_cast<const uint32_t*>(f1 + (size_t)par * (C * 2)) + lane;
        uint32_t v[4][3];
#pragma unroll
        for (int i = 0; i < 3; i++)
#pragma unroll
            for (int j = 0; j < 4; j++) v[j][i] = hadd2(__ldg(p0 + ((j >> 1) * W0 + (j & 1)) * (C / 2) + 32 * i), __ldg(p1 + 32 * i));
#pragma unroll
        for (int j = 0; j < 4; j++) {
            float x[6], s1 = 0.f, s2 = 0.f, d[4] = {0.f, 0.f, 0.f, 0.f};
#pragma unroll
            for (int i = 0; i < 3; i++) { x[2 * i] = bflo(v[j][i]); x[2 * i + 1] = bfhi(v[j][i]); s1 += x[2 * i] + x[2 * i + 1]; }
#pragma unroll
            for (int o = 1; o < 32; o <<= 1) s1 += __shfl_xor_sync(~0u, s1, o);
#pragma unroll
            for (int i = 0; i < 6; i++) {
                x[i] -= s1 * (1.f / C); s2 = fmaf(x[i], x[i], s2);
#pragma unroll
                for (int r = 0; r < 4; r++) d[r] = fmaf(x[i], k[r][i], d[r]);
            }
#pragma unroll
            for (int o = 1; o < 32; o <<= 1) {
                s2 += __shfl_xor_sync(~0u, s2, o);
#pragma unroll
                for (int r = 0; r < 4; r++) d[r] += __shfl_xor_sync(~0u, d[r], o);
            }
            const float rs = rsq(s2 * (1.f / C) + 1e-5f);
#pragma unroll
            for (int r = 0; r < 4; r++) {
                const float nm = fmaxf(m[r], d[r] * rs), al = ex2(m[r] - nm), p = ex2(d[r] * rs - nm);
                m[r] = nm; l[r] = fmaf(l[r], al, p);
#pragma unroll
                for (int i = 0; i < 6; i++) a[r][i] = fmaf(a[r][i], al, x[i] * (p * rs));
            }
        }
    }
    bar_sync(B_SLOW, 96);
#pragma unroll
    for (int r = 0; r < 4; r++) {
        float* const o = sm + ((r * 3 + warp) * 32 + lane) * 8;
#pragma unroll
        for (int i = 0; i < 6; i++) o[i] = a[r][i];
        o[6] = l[r]; o[7] = m[r];
    }
    bar_sync(B_SLOW, 96);
#pragma unroll 1
    for (int r = warp; r < 4; r += 3) {
        const float* const o = sm + (r * 96 + lane) * 8;
        const float M = fmaxf(fmaxf(o[7], o[256 + 7]), o[512 + 7]), e0 = ex2(o[7] - M), e1 = ex2(o[256 + 7] - M), e2 = ex2(o[512 + 7] - M);
        float x[7];
#pragma unroll
        for (int i = 0; i < 7; i++) x[i] = o[i] * e0 + o[256 + i] * e1 + o[512 + i] * e2;
        uint32_t hi[3], lo[3];
        const float rl = 1.f / x[6];
#pragma unroll
        for (int i = 0; i < 3; i++) {
            hi[i] = packh(x[2 * i] * rl, x[2 * i + 1] * rl);
            const float2 h = unpackh(hi[i]);
            lo[i] = packh(fmaf(x[2 * i], rl, -h.x), fmaf(x[2 * i + 1], rl, -h.y));
        }
        const uint32_t bw = sb + brow(8 * r + (lane & 3)) + (lane >> 2) * 16;
        sts128(bw, hi[0], hi[1], hi[2], lane ? 0u : 0x3C00u);
        sts128(bw + 4 * 144, lo[0], lo[1], lo[2], 0);
    }
    bar_sync(B_SLOW, 96);
}

__device__ __forceinline__ void reducer(const char* __restrict__ f0, const char* __restrict__ f1, const __nv_bfloat16* __restrict__ q, const __nv_bfloat16* __restrict__ wq, const __nv_bfloat16* __restrict__ wk,
                                        Scratch* scr, const __nv_bfloat16* __restrict__ wv, const __nv_bfloat16* __restrict__ wo,
                                        __nv_bfloat16* __restrict__ out, const uint32_t sb, const int GS)
{
    const int warp = threadIdx.x >> 5, lane = threadIdx.x & 31, b = blockIdx.x;
    const int g = lane >> 2, t = lane & 3;
    if (threadIdx.x == 256) TS(0);
    if (b < NSRC && warp < 8) {
        const uint32_t wqs = sb + RD_W, wbar = sb + RD_BAR;
        const int hr = lane >> 4, qt = (lane >> 2) & 3, sub = lane & 3;
        const uint32_t* qp = reinterpret_cast<const uint32_t*>(q + (warp + 8 * hr) * C + 48 * qt + 6 * sub);
        uint32_t qw[6];
#pragma unroll
        for (int j = 0; j < 3; j++) { qw[j] = __ldg(qp + j); qw[3 + j] = __ldg(qp + 12 + j); }
        if (lane == 0) { mbar_init(wbar + warp * 8, 1); asm volatile("fence.mbarrier_init.release.cluster;" ::: "memory"); mbar_expect(wbar + warp * 8, 9216);
            asm volatile("cp.async.bulk.shared::cluster.global.mbarrier::complete_tx::bytes [%0], [%1], 9216, [%2];"
                         ::"r"(wqs + warp * 9232), "l"(wq + 24 * warp * C), "r"(wbar + warp * 8) : "memory");
        }
        __syncwarp();
        if (threadIdx.x == 0) TSP(2, 0);
        float e[12];
#pragma unroll
        for (int j = 0; j < 6; j++) { e[2 * j] = bflo(qw[j]); e[2 * j + 1] = bfhi(qw[j]); }
        float sm = ((e[0] + e[1]) + (e[2] + e[3])) + ((e[4] + e[5]) + (e[6] + e[7])) + ((e[8] + e[9]) + (e[10] + e[11]));
#pragma unroll
        for (int o = 1; o < 16; o <<= 1) sm += __shfl_xor_sync(~0u, sm, o);
        if (threadIdx.x == 0) TSP(5, u(sm));
        float v0 = 0.f, v1 = 0.f;
#pragma unroll
        for (int j = 0; j < 12; j++) e[j] -= sm * (1.f / C);
#pragma unroll
        for (int j = 0; j < 6; j++) { v0 = fmaf(e[j], e[j], v0); v1 = fmaf(e[6 + j], e[6 + j], v1); }
        v0 += v1;
#pragma unroll
        for (int o = 1; o < 16; o <<= 1) v0 += __shfl_xor_sync(~0u, v0, o);
        const float rq = rsq(v0 * (1.f / C) + 1e-5f);
#pragma unroll
        for (int j = 0; j < 6; j++)
            sts32(sb + RD_QN + (3 * sub + (j >> 1)) * 512 + (4 * warp + qt) * 16 + (2 * (j & 1) + hr) * 4, pack2(e[j] * rq, e[6 + j] * rq));
        if (threadIdx.x == 0) TSP(8, 0);
        uint32_t wkf[2][3];
#pragma unroll
        for (int i = 0; i < 2; i++)
#pragma unroll
            for (int j = 0; j < 3; j++) wkf[i][j] = __ldg(reinterpret_cast<const uint32_t*>(wk + (16 * b + 8 * i + g) * C + 24 * warp + 8 * j + 2 * t));
        bar_sync(B_QN, 256);
        float acc[2][3][4];
#pragma unroll
        for (int i = 0; i < 3; i++)
#pragma unroll
            for (int e = 0; e < 4; e++) acc[0][i][e] = acc[1][i][e] = 0.f;
        const uint32_t ba = wqs + (lane & 7) * 9232 + (lane >> 3) * 384 + 48 * warp;
        uint4 a[12];
#pragma unroll
        for (int kk = 0; kk < 12; kk++) a[kk] = lds128(sb + RD_QN + kk * 512 + lane * 16);
        mbar_wait(wbar + (lane & 7) * 8, 0);
        __syncwarp();
        if (threadIdx.x == 0) TSP(4, 0);
#pragma unroll
        for (int kp = 0; kp < 6; kp++)
#pragma unroll
            for (int i = 0; i < 3; i++) {
                uint32_t bb[4];
                ldsm4t(bb, ba + kp * 1536 + i * 16);
                mma(acc[0][i], a[2 * kp].x, a[2 * kp].y, a[2 * kp].z, a[2 * kp].w, bb[0], bb[1]);
                mma(acc[1][i], a[2 * kp + 1].x, a[2 * kp + 1].y, a[2 * kp + 1].z, a[2 * kp + 1].w, bb[2], bb[3]);
            }
        if (threadIdx.x == 0) TSP(7, u(acc[1][2][3]));
        float kq[2][4] = {{0.f, 0.f, 0.f, 0.f}, {0.f, 0.f, 0.f, 0.f}};
#pragma unroll
        for (int j = 0; j < 3; j++) {
            const uint32_t a0 = pack2(acc[0][j][0] + acc[1][j][0], acc[0][j][1] + acc[1][j][1]), a1 = pack2(acc[0][j][2] + acc[1][j][2], acc[0][j][3] + acc[1][j][3]);
            mma8(kq[0], a0, a1, wkf[0][j]);
            mma8(kq[1], a0, a1, wkf[1][j]);
        }
        if (warp < 7) {
            sts128(sb + RD_KQ + warp * 1024 + lane * 16, u(kq[0][0]), u(kq[0][1]), u(kq[0][2]), u(kq[0][3]));
            sts128(sb + RD_KQ + warp * 1024 + 512 + lane * 16, u(kq[1][0]), u(kq[1][1]), u(kq[1][2]), u(kq[1][3]));
            bar_arrive(B_Q, 256);
        } else {
            bar_sync(B_Q, 256);
#pragma unroll
            for (int w = 0; w < 7; w++)
#pragma unroll
                for (int i = 0; i < 2; i++) {
                    const uint4 o = lds128(sb + RD_KQ + w * 1024 + i * 512 + lane * 16);
                    kq[i][0] += f(o.x); kq[i][1] += f(o.y); kq[i][2] += f(o.z); kq[i][3] += f(o.w);
                }
            stg_relaxed(g_qk + b * 32 + lane, ~pack2(kq[0][0] * QSCALE, kq[0][1] * QSCALE), ~pack2(kq[0][2] * QSCALE, kq[0][3] * QSCALE),
                        ~pack2(kq[1][0] * QSCALE, kq[1][1] * QSCALE), ~pack2(kq[1][2] * QSCALE, kq[1][3] * QSCALE));
            if (lane == 0) TS(10);
        }
    } else if (b >= NSRC) {
        if (b == NSRC && warp == 0) stg_relaxed32(g_mmax + lane, 0);
        __nanosleep(2500);
    }
    bar_sync(B_ALL, 384);

#pragma unroll 1
    for (int r = 0; r < 3; r++) {
        uint4 v[8];
#pragma unroll
        for (int k = 0; k < 8; k++) {
            const int idx = (8 * r + k) * 384 + threadIdx.x;
            v[k] = __ldg(reinterpret_cast<const uint4*>(idx < 4608 ? wv : wo - C * C) + idx);
        }
#pragma unroll
        for (int k = 0; k < 8; k++) {
            const int idx = (8 * r + k) * 384 + threadIdx.x, row = idx / 24;
            sts128(sb + RD_W + row * WROW + (idx - 24 * row) * 16, v[k].x, v[k].y, v[k].z, v[k].w);
        }
    }
    if (threadIdx.x < 256) {
        stg_relaxed(g_acc + (threadIdx.x >> 7) * ACC + (b >> 2) * 128 + (threadIdx.x & 127), 0, 0, 0, 0);
        __threadfence();
    }
    if (threadIdx.x == 0) sts128(sb + RD_RDY, 0, 0, 0, 0);
    bar_sync(B_ALL, 384);
    uint32_t wa[12][4];
    float ws0 = 0.f, ws1 = 0.f, qv0 = 0.f, qv1 = 0.f;
    __nv_bfloat16* op = out;
    if (warp < 3) {
        const int col = 48 * (b & 3) + 16 * warp;
        float d[24][4];
#pragma unroll
        for (int i = 0; i < 24; i++) d[i][0] = d[i][1] = d[i][2] = d[i][3] = 0.f;
        const int mi = lane >> 3, r = lane & 7;
        const uint32_t aa = sb + RD_W + (C + (mi >> 1) * 8 + r) * WROW + (col + (mi & 1) * 8) * 2;
        const uint32_t ba = sb + RD_W + ((mi >> 1) * 8 + r) * WROW + (mi & 1) * 16;
#pragma unroll 1
        for (int kk = 0; kk < 12; kk++) {
            uint32_t a[4];
            ldsm4t(a, aa + kk * 16 * WROW);
#pragma unroll
            for (int i = 0; i < 12; i++) {
                uint32_t bb[4];
                ldsm4(bb, ba + i * 16 * WROW + kk * 32);
                mma(d[2 * i], a[0], a[1], a[2], a[3], bb[0], bb[1]);
                mma(d[2 * i + 1], a[0], a[1], a[2], a[3], bb[2], bb[3]);
            }
        }
        float c0 = 0.f, c1 = 0.f, m0 = 0.f, m1 = 0.f;
#pragma unroll
        for (int i = 0; i < 24; i++) { c0 += d[i][0] + d[i][1]; c1 += d[i][2] + d[i][3]; }
        c0 += __shfl_xor_sync(~0u, c0, 1); c1 += __shfl_xor_sync(~0u, c1, 1);
        c0 += __shfl_xor_sync(~0u, c0, 2); c1 += __shfl_xor_sync(~0u, c1, 2);
        c0 *= 1.f / C; c1 *= 1.f / C;
#pragma unroll
        for (int i = 0; i < 24; i++) {
            d[i][0] -= c0; d[i][1] -= c0; d[i][2] -= c1; d[i][3] -= c1;
            m0 = fmaxf(m0, fmaxf(fabsf(d[i][0]), fabsf(d[i][1]))); m1 = fmaxf(m1, fmaxf(fabsf(d[i][2]), fabsf(d[i][3])));
        }
        m0 = fmaxf(m0, __shfl_xor_sync(~0u, m0, 1)); m1 = fmaxf(m1, __shfl_xor_sync(~0u, m1, 1));
        m0 = fmaxf(m0, __shfl_xor_sync(~0u, m0, 2)); m1 = fmaxf(m1, __shfl_xor_sync(~0u, m1, 2));
        const uint32_t e0 = min(max(u(m0) >> 23, 12u), 254u), e1 = min(max(u(m1) >> 23, 12u), 254u);
        const float s0 = f((265u - e0) << 23), s1 = f((265u - e1) << 23);
        const bool k0 = fabsf(c0) < INFINITY, k1 = fabsf(c1) < INFINITY;
        ws0 = k0 ? f((e0 - 11u) << 23) : c0; ws1 = k1 ? f((e1 - 11u) << 23) : c1;
#pragma unroll
        for (int i = 0; i < 24; i++) {
            const int kk = i < 16 ? i & 7 : i >> 1, hf = i < 16 ? i >> 3 : i & 1;
            wa[kk][2 * hf] = k0 ? packh(d[i][0] * s0, d[i][1] * s0) : 0u;
            wa[kk][2 * hf + 1] = k1 ? packh(d[i][2] * s1, d[i][3] * s1) : 0u;
        }
        const int o = ((b & 12) + t) * C + col + g;
        qv0 = __bfloat162float(q[o]); qv1 = __bfloat162float(q[o + 8]);
        op = out + o;
        asm volatile("" : "+l"(op));
        if (threadIdx.x == 0) TSE(6);
    } else if (warp == 3) {
        if (lane == 0) {
            uint32_t m;
            for (int it = 0;; it++) {
                const int left = NT - 2 * NST * GS - (int)ldg_relaxed32(g_ctr);
                m = ldg_relaxed32(g_mmax + b);
                if (left <= REFT && m) break;
                if (left <= 0) { m = 0x80000000u; break; }
                if (it > SPIN_LIMIT) __trap();
                __nanosleep(300);
            }
            asm volatile("st.release.gpu.global.u32 [%0], %1;" ::"l"(g_mref + b), "r"(~u(f(m >> 31 ? m ^ 0x80000000u : ~m) + 8.f)) : "memory");
            TSE(7);
        }
        return;
    } else {
        const int pr = warp & 1;
        const uint4* const pa = g_acc + ((b >> 2) * 2 + pr) * 64 + lane;
        const uint32_t bw = opaque(sb + brow(16 * pr + 8 * ((lane >> 2) & 1) + t) + (lane >> 3) * 16);
        const uint32_t fw = opaque(sb + RD_RDY + pr * 4);
        const uint32_t n0 = packh(0.f, (float)((GS + 1) >> 1)), n1 = packh(0.f, (float)(GS >> 1)), nstart = packh(0.f, (float)POLLN);
        for (int it = 0; ldg_relaxed32(reinterpret_cast<const uint32_t*>(pa - lane) + 3) < nstart; it++)
            if (it > SPIN_LIMIT) __trap();
        for (const unsigned c = clock32(); clock32() - c < ((warp - 4) >> 1) * PGAP;) {}
        for (int it = 0;; it++) {
            const uint4 a0 = ldg_relaxed(pa), a1 = ldg_relaxed(pa + ACC), b0 = ldg_relaxed(pa + 32), b1 = ldg_relaxed(pa + ACC + 32);
            bar_sync(B_WARP, 32);
            const bool ok = a0.w >= n0 && a1.w >= n1 && b0.w >= n0 && b1.w >= n1, all = __all_sync(~0u, ok);
            const uint32_t w = ok ? bw : bw - (RD_B - RD_QN);
            sts128(w, a0.x, a0.y, a0.z, a0.w); sts128(w + 4 * 144, a1.x, a1.y, a1.z, a1.w);
            sts128(w + 64, b0.x, b0.y, b0.z, b0.w); sts128(w + 4 * 144 + 64, b1.x, b1.y, b1.z, b1.w);
            sts32(all ? fw : fw + 8, 1);
            if (all) break;
            if (it > SPIN_LIMIT) __trap();
        }
        bar_arrive(B_POLL, 352);
        if (warp == 4) {
            if (b < NSRC) g_qk[b * 32 + lane] = make_uint4(0, 0, 0, 0);
            if (lane == 0) { g_mref[b] = 0; if (b == NSRC) g_ctr[0] = 0; }
        }
        return;
    }
    const uint32_t br = opaque(sb + brow(lane));
#pragma unroll 1
    for (uint32_t pass = 0;; pass = 1) {
        uint4 x[8];
        float o[5][4];
        for (int it = 0;; it++) {
            const uint2 rdy = lds64v(sb + RD_RDY);
            x[0] = lds128v(br); x[1] = lds128v(br + 16);
            if (it > 64 * SPIN_LIMIT) __trap();
            if (rdy.x & rdy.y) break;
        }
        if (threadIdx.x == 0) TSX(8, 0);
#pragma unroll
        for (int j = 2; j < 8; j++) x[j] = lds128v(br + j * 16);
#pragma unroll
        for (int j = 0; j < 5; j++) o[j][0] = o[j][1] = o[j][2] = o[j][3] = 0.f;
#pragma unroll
        for (int i = 0; i < 4; i++) {
            mmah(o[3 + (i & 1)], 0x3C00u, 0x3C00u, 0x3C00u, 0x3C00u, x[2 * i].w, x[2 * i + 1].w);
            mmah(o[0], wa[2 * i][0], wa[2 * i][1], wa[2 * i][2], wa[2 * i][3], x[2 * i].x, x[2 * i].y);
            mmah(o[1], wa[2 * i + 1][0], wa[2 * i + 1][1], wa[2 * i + 1][2], wa[2 * i + 1][3], x[2 * i + 1].x, x[2 * i + 1].y);
            mmah(o[2], wa[8 + i][0], wa[8 + i][1], wa[8 + i][2], wa[8 + i][3], x[2 * i].z, x[2 * i + 1].z);
        }
        const float L = (o[3][0] + o[3][1]) + (o[4][0] + o[4][1]), r = rcp(L);
        const float y0 = ((o[0][0] + o[0][1]) + (o[1][0] + o[1][1])) + (o[2][0] + o[2][1]);
        const float y1 = ((o[0][2] + o[0][3]) + (o[1][2] + o[1][3])) + (o[2][2] + o[2][3]);
        const uint32_t y = pack2(fmaf(y0, r * ws0, qv0), fmaf(y1, r * ws1, qv1));
        asm volatile("{.reg .b16 l, h; mov.b32 {l, h}, %1; st.global.b16 [%0], l; st.global.b16 [%0 + 16], h;}" ::"l"(op), "r"(y) : "memory");
        if (threadIdx.x == 0) TSD(11, y);
        if (__builtin_expect(__all_sync(~0u, L >= 0.001953125f && L <= 2048.f && fabsf(y0) < INFINITY) || pass, 1)) break;
        const uint32_t keep = sb + RD_W + 32768 + warp * 6144 + lane * 16;
#pragma unroll
        for (int kk = 0; kk < 12; kk++) sts128(keep + kk * 512, wa[kk][0], wa[kk][1], wa[kk][2], wa[kk][3]);
        slow_rows(f0, f1, q, wq, wk, sb);
#pragma unroll
        for (int kk = 0; kk < 12; kk++) {
            const uint4 v = lds128(keep + kk * 512);
            wa[kk][0] = v.x; wa[kk][1] = v.y; wa[kk][2] = v.z; wa[kk][3] = v.w;
        }
    }
}

__global__ void __launch_bounds__(NTHREADS, 1)
attn_main(const char* __restrict__ f0, const char* __restrict__ f1,
          const __nv_bfloat16* __restrict__ q, const __nv_bfloat16* __restrict__ wq, const __nv_bfloat16* __restrict__ wk, Scratch* scr,
          const __nv_bfloat16* __restrict__ wv, const __nv_bfloat16* __restrict__ wo, __nv_bfloat16* __restrict__ out,
          const __grid_constant__ CUtensorMap m0, const __grid_constant__ CUtensorMap m1)
{
    extern __shared__ char smem_raw[];
    const uint32_t sb = (s2u(smem_raw) + 1023u) & ~1023u;
    const int G = gridDim.x - NRD;
    const int b = blockIdx.x - NRD;
    if (threadIdx.x == 0 && b >= 0) {
        prefetch_l2((const char*)(b % (2 * WSL) < WSL ? wq : wk) + b % WSL * (C * C * 2 / WSL), C * C * 2 / WSL);
        const char* a = f0 + (uint32_t)(b * (4 * TP * C * 2) + (b >> 4) * (W0 * C * 2));
        prefetch_l2(a, 4 * TP * C * 2);
        prefetch_l2(a + W0 * C * 2, 4 * TP * C * 2);
        prefetch_l2(f1 + b * (2 * TP * C * 2), 2 * TP * C * 2);
    }
    if (b < 0) { reducer(f0, f1, q, wq, wk, scr, wv, wo, out, sb, G); return; }
    const int warp = __shfl_sync(~0u, threadIdx.x >> 5, 0), lane = threadIdx.x & 31;
    const int g = lane >> 2, t = lane & 3;

    if (warp >= 8) {
        if (warp < 10) {
            const int p = warp - 8;
            const unsigned c0 = clock32();
            const uint32_t sbp = opaque(sb), bar = sbp + SM_BAR + p * 8;
            uint64_t pol; asm volatile("createpolicy.fractional.L2::evict_first.b64 %0, 1.0;" : "=l"(pol));
            if (elect()) {
                if (p == 0) TS(0);
                asm volatile("prefetch.tensormap [%0];" ::"l"(p ? &m1 : &m0) : "memory");
#pragma unroll
                for (int n = 0; n < NI; n++) mbar_init(bar + n * 16, 2);
                asm volatile("fence.mbarrier_init.release.cluster;" ::: "memory");
#pragma unroll
                for (int n = 0; n < NI; n++) {
                    issue_tile(&m0, &m1, sbp, p + 2 * n, 2 * b + p + 2 * n * G, pol);
                    TR(0, 2 * n + p);
                    sts32(sbp + SM_FLAG + (p + 2 * n) * 4, 0);
                    mbar_arrive(bar + n * 16);
                }
#pragma unroll
                for (int n = 0; n < NS / 2; n++) {
                    if (n >= NI) mbar_init(bar + n * 16, 2);
                    mbar_init(bar + NS * 8 + n * 16, 1);
                }
                if (p == 0) mbar_init(sbp + SM_REF, 1);
                asm volatile("fence.mbarrier_init.release.cluster;" ::: "memory");
            }
            __syncwarp();
            bar_arrive(B_QK, 384);
            if (elect()) {
                int tl = 2 * b + p + 2 * NI * G;
                int s = p + 2 * NI; uint32_t ph = 1;
                int sa = p, na = 0; uint32_t pa = 0;
                bool late = false;
                for (int n = NI;; n++) {
                    const int d = n < NRAMP ? D0 : (tl >= NT - TAILT ? D2 : D1);
                    while (n - na >= d) {
                        mbar_wait(sbp + SM_BAR + sa * 8, pa);
                        if (na < NS / 2) TR(1, 2 * na + p);
                        na++; sa += 2;
                        if (sa >= NS) { sa -= NS; pa ^= 1; }
                    }
                    mbar_wait(sbp + SM_BAR + (NS + s) * 8, ph);
                    if (n < NPACE) while (clock32() - c0 < (n ? T1 + (2 * (n - 1) + p) * TG : T0)) {}
                    issue_tile(&m0, &m1, sbp, s, tl, pol);
                    TR(0, 2 * n + p);
                    int nxt = tl + 2 * G;
                    if (n >= NST - 1) nxt = grab_tile(g_ctr) + 2 * NST * G;
                    const bool last = nxt >= NT;
                    uint32_t flag = last;
                    if (!late && nxt >= NT - MAXT - 16 * b) { late = true; flag |= 2; }
                    if (last) mbar_wait(sbp + SM_REF, 0);
                    sts32(sbp + SM_FLAG + s * 4, flag);
                    mbar_arrive(sbp + SM_BAR + s * 8);
                    if (last) break;
                    s += 2;
                    if (s >= NS) { s -= NS; ph ^= 1; }
                    tl = nxt;
                }
                if (p) TSE(5);
            }
            return;
        }
        const int h = threadIdx.x - 320;
        uint4 v[6];
        for (int it = 0;; it++) {
            bool miss = false;
#pragma unroll
            for (int k = 0; k < 6; k++) v[k] = ldg_relaxed(g_qk + k * 64 + h);
#pragma unroll
            for (int k = 0; k < 6; k++) miss |= has(v[k], 0);
            if (!miss) break;
            if (it > SPIN_LIMIT) __trap();
            if (it == 0) __nanosleep(QSLEEP);
        }
#pragma unroll
        for (int k = 0; k < 6; k++) sts128(sb + SM_QK + (k * 64 + h) * 16, ~v[k].x, ~v[k].y, ~v[k].z, ~v[k].w);
        __syncwarp();
        bar_sync(B_QK, 384);
        if (warp == 11) return;
        uint32_t r = 1;
        for (int it = 0;; it++) {
            __nanosleep(500);
            if (lane < NQ) asm volatile("ld.acquire.gpu.global.u32 %0, [%1];" : "=r"(r) : "l"(g_mref + lane) : "memory");
            if (__all_sync(~0u, r != 0)) break;
            if (it > SPIN_LIMIT) __trap();
        }
        if (lane < NQ) sts32(sb + SM_M + lane * 4, ~r);
        __syncwarp();
        if (lane == 0) { mbar_arrive(sb + SM_REF); TSE(7); }
        return;
    }

    const int grp = warp >> 2, cw = warp & 3;
    const int xp = lane & 7, mi = lane >> 3;
    const uint32_t offS1 = opaque(12288 + xp * 128 + ((mi ^ xp) << 4)), offS1x = opaque(offS1 ^ 64);
    const uint32_t offS0 = opaque(offS1 - 12288 + cw * 3072), offS0x = opaque(offS0 ^ 64);
    const uint32_t offT = opaque(mi * 3072 + xp * 128 + (((cw + 4 * grp) ^ xp) << 4)), offTx = opaque(offT ^ 64);
    const uint32_t offU = opaque(12288 + (mi % 3) * 1024 + xp * 128 + (((cw + 4 * (grp ^ (mi / 3))) ^ xp) << 4));
    const uint32_t offV = opaque(12288 + (1 + (mi & 1)) * 1024 + xp * 128 + (((cw + 4 * (grp ^ 1)) ^ xp) << 4));
    const int shl = opaque(9 * t), shl4 = opaque(9 * t + 4);
    const uint32_t pw = opaque((cw >> 1) * 512 + lane * 16 + (cw & 1) * 8), muw = opaque(1024 + t * 16 + cw * 4);
    const uint32_t prd = opaque(lane * 16), mur = opaque(1024 + t * 16);
    uint32_t pb0 = sb + SM_P + grp * 2 * PBUF;
    const uint32_t pbx = pb0 ^ (pb0 + PBUF);
    const bool odd = g & 1;
    const int barid = B_GRP + grp;
    const bool elected = cw == 3 && lane == 0;

    uint32_t qa[48];
    float r_lo, r_hi;
    bar_sync(B_QK, 384);
    {
        float rr[2][4] = {{0.f, 0.f, 0.f, 0.f}, {0.f, 0.f, 0.f, 0.f}};
#pragma unroll
        for (int kk = 0; kk < 12; kk++) {
            const uint4 v = lds128(sb + SM_QK + kk * 512 + lane * 16);
            qa[4 * kk] = v.x; qa[4 * kk + 1] = v.y; qa[4 * kk + 2] = v.z; qa[4 * kk + 3] = v.w;
            mma(rr[kk & 1], v.x, v.y, v.z, v.w, ONES, ONES);
        }
        r_lo = rr[0][0] + rr[1][0]; r_hi = rr[0][2] + rr[1][2];
    }
    if (threadIdx.x == 0) TS(1);

    float acc[6][4];
#pragma unroll
    for (int i = 0; i < 6; i++) acc[i][0] = acc[i][1] = acc[i][2] = acc[i][3] = 0.f;
    float m_lo = -INFINITY, m_hi = -INFINITY, l_lo = 0.f, l_hi = 0.f;
    float cm[4] = {0.f, 0.f, 0.f, 0.f};
    uint32_t xt[6][4], yt[6]; uint4 pa, pb, mv;
    int s = grp; uint32_t ph = 0;
    while (true) {
        mbar_wait(sb + SM_BAR + s * 8, ph);
        PH(0, 0);
        const uint32_t stop = lds32(sb + SM_FLAG + s * 4);
        const uint32_t st = sb + SM_STAGES + s * STAGE;
        float sc[2][4], gr[4][4], sx[4];
#pragma unroll
        for (int e = 0; e < 4; e++) sc[0][e] = sc[1][e] = gr[0][e] = gr[1][e] = gr[2][e] = gr[3][e] = sx[e] = 0.f;
#pragma unroll
        for (int qq = 0; qq < 6; qq++) {
            uint32_t x[4], y[4];
            ldsm4(x, st + (qq & 1 ? offS0x : offS0) + (qq >> 1) * 1024);
            ldsm4(y, st + (qq & 1 ? offS1x : offS1) + (qq >> 1) * 1024);
#pragma unroll
            for (int e = 0; e < 4; e++) x[e] = hadd2(x[e], y[e]);
            mma8(gr[0], x[0], x[1], x[0]);
            mma8(gr[1], x[0], x[1], x[1]);
            mma(sx, x[0], x[1], x[2], x[3], ONES, ONES);
            mma8(gr[GR4 ? 2 : 0], x[2], x[3], x[2]);
            mma8(gr[GR4 ? 3 : 1], x[2], x[3], x[3]);
            mma(sc[0], qa[8 * qq], qa[8 * qq + 1], qa[8 * qq + 2], qa[8 * qq + 3], x[0], x[1]);
            mma(sc[1], qa[8 * qq + 4], qa[8 * qq + 5], qa[8 * qq + 6], qa[8 * qq + 7], x[2], x[3]);
        }
        ldsm4t(yt, st + offU);
        ldsm2t(yt + 4, st + offV);
#pragma unroll
        for (int i = 0; i < 6; i++) ldsm4t(xt[i], st + (i < 3 ? offT : offTx) + (i % 3) * 1024);

        const float mu = (sx[0] + sx[2]) * (1.f / C), ss = GR4 ? (odd ? (gr[0][1] + gr[1][3]) + (gr[2][1] + gr[3][3]) : (gr[0][0] + gr[1][2]) + (gr[2][0] + gr[3][2])) : (odd ? gr[0][1] + gr[1][3] : gr[0][0] + gr[1][2]);
        const float rs = rsq(fmaxf(fmaf(-mu, mu, ss * (1.f / C)), 0.f) + 1e-5f);
        const float mu0 = __shfl_sync(~0u, mu, shl), mu1 = __shfl_sync(~0u, mu, shl4);
        const float rs0 = __shfl_sync(~0u, rs, shl), rs1 = __shfl_sync(~0u, rs, shl4);
        const float u0 = fmaf(-mu0, r_lo, sc[0][0] + sc[1][0]), u1 = fmaf(-mu1, r_lo, sc[0][1] + sc[1][1]);
        const float u2 = fmaf(-mu0, r_hi, sc[0][2] + sc[1][2]), u3 = fmaf(-mu1, r_hi, sc[0][3] + sc[1][3]);
        const float d0 = fmaf(u0, rs0, -m_lo), d1 = fmaf(u1, rs1, -m_lo), d2 = fmaf(u2, rs0, -m_hi), d3 = fmaf(u3, rs1, -m_hi);
        PH(1, u(d0 + d2));
        float p0 = ex2(d0), p1 = ex2(d1), p2 = ex2(d2), p3 = ex2(d3);
        sts64(pb0 + pw, pack2(p0 * rs0, p1 * rs1), pack2(p2 * rs0, p3 * rs1));
        if (lane < 4) sts32(pb0 + muw, pack2(mu0, mu1));
        const bool over = bar_any(barid, 128, fmaxf(fmaxf(d0, d1), fmaxf(d2, d3)) > LAZY);
        PH(3, 0);
        pa = lds128(pb0 + prd); pb = lds128(pb0 + prd + 512); mv = lds128(pb0 + mur);
        if (elected) mbar_arrive(sb + SM_BAR + (NS + s) * 8);
        if (__builtin_expect(over, 0)) {
            const float s0 = u0 * rs0, s1 = u1 * rs1, s2 = u2 * rs0, s3 = u3 * rs1;
            float xl = fmaxf(s0, s1), xh = fmaxf(s2, s3);
            xl = fmaxf(xl, __shfl_xor_sync(~0u, xl, 1)); xh = fmaxf(xh, __shfl_xor_sync(~0u, xh, 1));
            xl = fmaxf(xl, __shfl_xor_sync(~0u, xl, 2)); xh = fmaxf(xh, __shfl_xor_sync(~0u, xh, 2));
            if (t < 2) sts32(sb + SM_MX + grp * 256 + ((g + 8 * t) * 4 + cw) * 4, u(t ? xh : xl));
            bar_sync(B_MAX + grp, 128);
            const uint4 ml4 = lds128(sb + SM_MX + grp * 256 + g * 16), mh4 = lds128(sb + SM_MX + grp * 256 + g * 16 + 128);
            const float nl = fmaxf(fmaxf(fmaxf(f(ml4.x), f(ml4.y)), fmaxf(f(ml4.z), f(ml4.w))), m_lo);
            const float nh = fmaxf(fmaxf(fmaxf(f(mh4.x), f(mh4.y)), fmaxf(f(mh4.z), f(mh4.w))), m_hi);
            p0 = ex2(s0 - nl); p1 = ex2(s1 - nl); p2 = ex2(s2 - nh); p3 = ex2(s3 - nh);
            sts64(pb0 + pw, pack2(p0 * rs0, p1 * rs1), pack2(p2 * rs0, p3 * rs1));
            const float al = ex2(m_lo - nl), ah = ex2(m_hi - nh);
            m_lo = nl; m_hi = nh;
            l_lo *= al; l_hi *= ah; cm[0] *= al; cm[2] *= ah;
#pragma unroll
            for (int i = 0; i < 6; i++) { acc[i][0] *= al; acc[i][1] *= al; acc[i][2] *= ah; acc[i][3] *= ah; }
            bar_sync(B_MAX + grp, 128);
            pa = lds128(pb0 + prd); pb = lds128(pb0 + prd + 512);
        }
        l_lo += p0 + p1; l_hi += p2 + p3;
        if (stop & 1) break;
#pragma unroll
        for (int i = 0; i < 6; i++) mma(acc[i], pa.x, pa.y, pa.z, pa.w, hadd2v(xt[i][0], yt[i]), hadd2v(xt[i][1], yt[i]));
        mma(cm, pa.x, pa.y, pa.z, pa.w, mv.x, mv.y);
#pragma unroll
        for (int i = 0; i < 6; i++) mma(acc[i], pb.x, pb.y, pb.z, pb.w, hadd2v(xt[i][2], yt[i]), hadd2v(xt[i][3], yt[i]));
        mma(cm, pb.x, pb.y, pb.z, pb.w, mv.z, mv.w);
        PH(4, u(acc[5][0]));
        if (stop) {
            float a = l_lo + __shfl_xor_sync(~0u, l_lo, 1), c = l_hi + __shfl_xor_sync(~0u, l_hi, 1);
            a += __shfl_xor_sync(~0u, a, 2); c += __shfl_xor_sync(~0u, c, 2);
            const uint32_t m = u((t ? m_hi : m_lo) + lg2(fmaxf(t ? c : a, 1.f)));
            if (t < 2) asm volatile("red.relaxed.gpu.global.max.u32 [%0], %1;" ::"l"(g_mmax + g + 8 * t), "r"(m >> 31 ? ~m : m | 0x80000000u) : "memory");
        }
        pb0 ^= pbx;
        s += 2;
        if (s >= NS) { s -= NS; ph ^= 1; }
    }
    const float al = ex2(m_lo - f(lds32(sb + SM_M + g * 4))), ah = ex2(m_hi - f(lds32(sb + SM_M + 32 + g * 4)));
    mma(cm, pa.x, pa.y, pa.z, pa.w, mv.x, mv.y);
#pragma unroll
    for (int i = 3; i < 6; i++) mma(acc[i], pa.x, pa.y, pa.z, pa.w, hadd2v(xt[i][0], yt[i]), hadd2v(xt[i][1], yt[i]));
    mma(cm, pb.x, pb.y, pb.z, pb.w, mv.z, mv.w);
#pragma unroll
    for (int i = 3; i < 6; i++) mma(acc[i], pb.x, pb.y, pb.z, pb.w, hadd2v(xt[i][2], yt[i]), hadd2v(xt[i][3], yt[i]));
#pragma unroll
    for (int i = 0; i < 3; i++) mma(acc[i], pa.x, pa.y, pa.z, pa.w, hadd2v(xt[i][0], yt[i]), hadd2v(xt[i][1], yt[i]));
#pragma unroll
    for (int i = 0; i < 3; i++) mma(acc[i], pb.x, pb.y, pb.z, pb.w, hadd2v(xt[i][2], yt[i]), hadd2v(xt[i][3], yt[i]));
    if (threadIdx.x == grp * 128) TSE(2 + grp);
    if (threadIdx.x == grp * 128 + 96) TSX(2 + grp, u(acc[5][0]));

    uint4* const dst = g_acc + (b & 1) * ACC + ((g >> 1) * 8 + cw + 4 * grp) * 8 + (lane & 7);
    const uint32_t xw = opaque(sb + SM_STAGES + grp * STAGE + cw * 1536 + lane * 16), xr = opaque(sb + SM_STAGES + (grp ^ 1) * STAGE + cw * 1536 + lane * 16);
    asm volatile("" ::"l"(dst));
    const float cl = -cm[0] * al, ch = -cm[2] * ah;
#pragma unroll
    for (int i = 0; i < 3; i++)
        sts128(xw + i * 512, u(fmaf(acc[3 + i][0], al, cl)), u(fmaf(acc[3 + i][1], al, cl)), u(fmaf(acc[3 + i][2], ah, ch)), u(fmaf(acc[3 + i][3], ah, ch)));
#pragma unroll
    for (int i = 0; i < 3; i++) { acc[i][0] = fmaf(acc[i][0], al, cl); acc[i][1] = fmaf(acc[i][1], al, cl); acc[i][2] = fmaf(acc[i][2], ah, ch); acc[i][3] = fmaf(acc[i][3], ah, ch); }
    const uint32_t w_lo = packh(l_lo * al, 1.f), w_hi = packh(l_hi * ah, 1.f);
    bar_sync(B_MERGE, 256);
    if (threadIdx.x == 224) TSX(4, 0);
    uint4 o[3];
#pragma unroll
    for (int i = 0; i < 3; i++) o[i] = lds128(xr + i * 512);
    red8h(dst, packh(acc[0][0] + f(o[0].x), acc[0][1] + f(o[0].y)), packh(acc[1][0] + f(o[1].x), acc[1][1] + f(o[1].y)), packh(acc[2][0] + f(o[2].x), acc[2][1] + f(o[2].y)), w_lo);
    red8h(dst + 256, packh(acc[0][2] + f(o[0].z), acc[0][3] + f(o[0].w)), packh(acc[1][2] + f(o[1].z), acc[1][3] + f(o[1].w)), packh(acc[2][2] + f(o[2].z), acc[2][3] + f(o[2].w)), w_hi);
    if (threadIdx.x == 0) TSE(4);
    if (threadIdx.x == 224) TSX(9, 0);
}

typedef CUresult (*EncodeFn)(CUtensorMap*, CUtensorMapDataType, cuuint32_t, void*, const cuuint64_t*, const cuuint64_t*,
                             const cuuint32_t*, const cuuint32_t*, CUtensorMapInterleave, CUtensorMapSwizzle,
                             CUtensorMapL2promotion, CUtensorMapFloatOOBfill);

}

extern "C" void kernel_launch(void* const* d_in, const int* in_sizes, int n_in, void* d_out, int out_size) {
    const __nv_bfloat16* q = (const __nv_bfloat16*)d_in[0];
    char* f0 = (char*)d_in[1];
    char* f1 = (char*)d_in[2];
    const __nv_bfloat16* wq = (const __nv_bfloat16*)d_in[3];
    const __nv_bfloat16* wk = (const __nv_bfloat16*)d_in[4];
    const __nv_bfloat16* wv = (const __nv_bfloat16*)d_in[5];
    const __nv_bfloat16* wo = (const __nv_bfloat16*)d_in[6];

    static EncodeFn enc = nullptr;
    static int grid = 0;
    static Scratch* scr = nullptr;
    if (!enc) {
        void* fn = nullptr; cudaDriverEntryPointQueryResult qr;
        cudaGetDriverEntryPoint("cuTensorMapEncodeTiled", &fn, cudaEnableDefault, &qr);
        enc = (EncodeFn)fn;
        cudaGetSymbolAddress((void**)&scr, g_scratch);
        int dev = 0, sms = 0;
        cudaGetDevice(&dev);
        cudaDeviceGetAttribute(&sms, cudaDevAttrMultiProcessorCount, dev);
        grid = sms < MAXG ? sms : MAXG;
        cudaFuncSetAttribute(attn_main, cudaFuncAttributeMaxDynamicSharedMemorySize, SMEM_BYTES);
    }
    CUtensorMap m0, m1;
    {
        cuuint64_t dims[5] = {64, W1, 3, 2, W0};
        cuuint64_t str[4] = {2 * C * 2, 128, C * 2, (cuuint64_t)W0 * C * 2};
        cuuint32_t box[5] = {64, TP, 3, 2, 2}, es[5] = {1, 1, 1, 1, 1};
        enc(&m0, CU_TENSOR_MAP_DATA_TYPE_BFLOAT16, 5, f0, dims, str, box, es, CU_TENSOR_MAP_INTERLEAVE_NONE,
            CU_TENSOR_MAP_SWIZZLE_128B, CU_TENSOR_MAP_L2_PROMOTION_NONE, CU_TENSOR_MAP_FLOAT_OOB_FILL_NONE);
    }
    {
        cuuint64_t dims[4] = {64, W1, 3, W1};
        cuuint64_t str[3] = {C * 2, 128, (cuuint64_t)W1 * C * 2};
        cuuint32_t box[4] = {64, TP, 3, 1}, es[4] = {1, 1, 1, 1};
        enc(&m1, CU_TENSOR_MAP_DATA_TYPE_BFLOAT16, 4, f1, dims, str, box, es, CU_TENSOR_MAP_INTERLEAVE_NONE,
            CU_TENSOR_MAP_SWIZZLE_128B, CU_TENSOR_MAP_L2_PROMOTION_NONE, CU_TENSOR_MAP_FLOAT_OOB_FILL_NONE);
    }
    attn_main<<<grid, NTHREADS, SMEM_BYTES, cudaStreamPerThread>>>(f0, f1, q, wq, wk, scr, wv, wo, (__nv_bfloat16*)d_out, m0, m1);
}
```

```cpp
#include <cuda_runtime.h>
#include <cuda_bf16.h>
#include <cuda.h>
#include <stdint.h>

namespace {

constexpr int C = 192;
constexpr int NQ = 16;
constexpr int W0 = 512;
constexpr int W1 = 256;
constexpr int TP = 8;
constexpr int NT = W1 * W1 / TP;
constexpr int STAGE = TP * 5 * C * 2;
#define NS 14
#define D0 3
#define D1 2
#define D2 1
#define NRAMP 5
#define TAILT 150
#define QSLEEP 700
#define WSL 24
#define MAXT 3000
#define REFT 1800
#define POLLN 1
#define PGAP 110
#define LAZY 12.f
#define GR4 1
#define NST 4
#define NI 1
#define NPACE 5
#define T0 0
#define T1 1600
#define TG 960
static_assert(NST > D0, "the first dynamic tile index must not delay the start");
constexpr int NTHREADS = 384;
constexpr int MAXG = 132;
constexpr int NRD = NQ;
constexpr int ACC = NQ * 32;
constexpr int NSRC = 12;
constexpr int SPIN_LIMIT = 1 << 22;

constexpr int SM_STAGES = 0;
constexpr int SM_P = NS * STAGE;
constexpr int PBUF = 1088;
constexpr int SM_QK = SM_P + 4 * PBUF;
constexpr int SM_MX = SM_QK + 6144;
constexpr int SM_M = SM_MX + 512;
constexpr int SM_BAR = SM_M + 64;
constexpr int SM_REF = SM_BAR + 16 * NS;
constexpr int SM_FLAG = SM_REF + 8;
constexpr int SM_TOTAL = SM_FLAG + 4 * NS;
constexpr int SMEM_BYTES = SM_TOTAL + 1024;
static_assert(SMEM_BYTES <= 232448, "smem");
constexpr int WROW = 400;
constexpr int RD_W = 0;
constexpr int RD_QN = 2 * C * WROW;
constexpr int RD_KQ = RD_QN + 6144;
constexpr int RD_B = RD_KQ + 7168;
constexpr int RD_RDY = RD_B + 32 * 144 + 256;
constexpr int RD_BAR = RD_RDY + 16;
static_assert(RD_BAR + 64 <= SM_TOTAL, "smem");

struct Scratch {
    uint4 acc[2 * ACC];
    uint4 qk[NSRC * 32];
    unsigned ctr[32];
    unsigned mmax[32];
    unsigned mref[32];
};
__device__ __align__(128) Scratch g_scratch;
#define g_acc (scr->acc)
#define g_qk (scr->qk)
#define g_ctr (scr->ctr)
#define g_mmax (scr->mmax)
#define g_mref (scr->mref)
#define g_ts (scr->ts)
#define g_tr (scr->tr)
#define TR(k, i) do {} while (0)
#define TS(i) do {} while (0)
#define TSD(i, dep) do {} while (0)
#define TSX(i, dep) do {} while (0)
#define TSP(i, dep) do {} while (0)
#define TSE(i) TS(i)
#define CK_(i, dep) do {} while (0)
#define PH(i, dep) do {} while (0)

__device__ __forceinline__ uint32_t s2u(const void* p) { return (uint32_t)__cvta_generic_to_shared(p); }
__device__ __forceinline__ void mbar_init(uint32_t a, int c) { asm volatile("mbarrier.init.shared::cta.b64 [%0], %1;" ::"r"(a), "r"(c) : "memory"); }
__device__ __forceinline__ void mbar_expect(uint32_t a, uint32_t b) { asm volatile("mbarrier.arrive.expect_tx.shared::cta.b64 _, [%0], %1;" ::"r"(a), "r"(b) : "memory"); }
__device__ __forceinline__ void mbar_arrive(uint32_t a) { asm volatile("mbarrier.arrive.shared::cta.b64 _, [%0];" ::"r"(a) : "memory"); }
__device__ __forceinline__ void mbar_wait(uint32_t a, uint32_t ph) {
    uint32_t ok; int it = 0;
    do {
        asm volatile("{.reg .pred p; mbarrier.try_wait.parity.shared::cta.b64 p, [%1], %2; selp.u32 %0,1,0,p;}" : "=r"(ok) : "r"(a), "r"(ph) : "memory");
        if (++it > SPIN_LIMIT) __trap();
    } while (!ok);
}
__device__ __forceinline__ bool elect() {
    uint32_t r; asm volatile("{.reg .pred p; elect.sync _|p, 0xffffffff; selp.u32 %0, 1, 0, p;}" : "=r"(r)); return r;
}
__device__ __forceinline__ void bar_sync(int id, int n) { asm volatile("bar.sync %0, %1;" ::"r"(id), "r"(n) : "memory"); }
__device__ __forceinline__ bool bar_any(int id, int n, bool c) {
    uint32_t r;
    asm volatile("{.reg .pred p, q; setp.ne.u32 q, %3, 0; bar.red.or.pred p, %1, %2, q; selp.u32 %0, 1, 0, p;}" : "=r"(r) : "r"(id), "r"(n), "r"((uint32_t)c) : "memory");
    return r;
}
__device__ __forceinline__ void bar_arrive(int id, int n) { asm volatile("bar.arrive %0, %1;" ::"r"(id), "r"(n) : "memory"); }
__device__ __forceinline__ void ldsm4(uint32_t* r, uint32_t a) {
    asm volatile("ldmatrix.sync.aligned.m8n8.x4.shared.b16 {%0,%1,%2,%3}, [%4];" : "=r"(r[0]), "=r"(r[1]), "=r"(r[2]), "=r"(r[3]) : "r"(a) : "memory");
}
__device__ __forceinline__ void ldsm4t(uint32_t* r, uint32_t a) {
    asm volatile("ldmatrix.sync.aligned.m8n8.x4.trans.shared.b16 {%0,%1,%2,%3}, [%4];" : "=r"(r[0]), "=r"(r[1]), "=r"(r[2]), "=r"(r[3]) : "r"(a) : "memory");
}
__device__ __forceinline__ void ldsm2t(uint32_t* r, uint32_t a) {
    asm volatile("ldmatrix.sync.aligned.m8n8.x2.trans.shared.b16 {%0,%1}, [%2];" : "=r"(r[0]), "=r"(r[1]) : "r"(a) : "memory");
}
__device__ __forceinline__ void mma(float* d, uint32_t a0, uint32_t a1, uint32_t a2, uint32_t a3, uint32_t b0, uint32_t b1) {
    asm("mma.sync.aligned.m16n8k16.row.col.f32.bf16.bf16.f32 {%0,%1,%2,%3}, {%4,%5,%6,%7}, {%8,%9}, {%0,%1,%2,%3};"
        : "+f"(d[0]), "+f"(d[1]), "+f"(d[2]), "+f"(d[3]) : "r"(a0), "r"(a1), "r"(a2), "r"(a3), "r"(b0), "r"(b1));
}
__device__ __forceinline__ void mmah(float* d, uint32_t a0, uint32_t a1, uint32_t a2, uint32_t a3, uint32_t b0, uint32_t b1) {
    asm("mma.sync.aligned.m16n8k16.row.col.f32.f16.f16.f32 {%0,%1,%2,%3}, {%4,%5,%6,%7}, {%8,%9}, {%0,%1,%2,%3};"
        : "+f"(d[0]), "+f"(d[1]), "+f"(d[2]), "+f"(d[3]) : "r"(a0), "r"(a1), "r"(a2), "r"(a3), "r"(b0), "r"(b1));
}
__device__ __forceinline__ void mma8(float* d, uint32_t a0, uint32_t a1, uint32_t b0) {
    asm("mma.sync.aligned.m16n8k8.row.col.f32.bf16.bf16.f32 {%0,%1,%2,%3}, {%4,%5}, {%6}, {%0,%1,%2,%3};"
        : "+f"(d[0]), "+f"(d[1]), "+f"(d[2]), "+f"(d[3]) : "r"(a0), "r"(a1), "r"(b0));
}
__device__ __forceinline__ uint32_t hadd2(uint32_t a, uint32_t b) {
    uint32_t r; asm("add.rn.bf16x2 %0, %1, %2;" : "=r"(r) : "r"(a), "r"(b)); return r;
}
__device__ __forceinline__ uint32_t pack2(float lo, float hi) {
    uint32_t r; asm("cvt.rn.bf16x2.f32 %0, %1, %2;" : "=r"(r) : "f"(hi), "f"(lo)); return r;
}
__device__ __forceinline__ uint32_t packh(float lo, float hi) {
    uint32_t r; asm("cvt.rn.f16x2.f32 %0, %1, %2;" : "=r"(r) : "f"(hi), "f"(lo)); return r;
}
__device__ __forceinline__ float2 unpackh(uint32_t v) {
    float2 r; asm("{.reg .b16 l, h; mov.b32 {l, h}, %2; cvt.f32.f16 %0, l; cvt.f32.f16 %1, h;}" : "=f"(r.x), "=f"(r.y) : "r"(v)); return r;
}
__device__ __forceinline__ float bflo(uint32_t v) { return __uint_as_float(v << 16); }
__device__ __forceinline__ float bfhi(uint32_t v) { return __uint_as_float(v & 0xffff0000u); }
__device__ __forceinline__ float ex2(float x) { float r; asm("ex2.approx.ftz.f32 %0, %1;" : "=f"(r) : "f"(x)); return r; }
__device__ __forceinline__ void sts128(uint32_t a, uint32_t x, uint32_t y, uint32_t z, uint32_t w) {
    asm volatile("st.shared.v4.b32 [%0], {%1,%2,%3,%4};" ::"r"(a), "r"(x), "r"(y), "r"(z), "r"(w) : "memory");
}
__device__ __forceinline__ void sts64(uint32_t a, uint32_t x, uint32_t y) {
    asm volatile("st.shared.v2.b32 [%0], {%1,%2};" ::"r"(a), "r"(x), "r"(y) : "memory");
}
__device__ __forceinline__ void sts32(uint32_t a, uint32_t x) { asm volatile("st.shared.b32 [%0], %1;" ::"r"(a), "r"(x) : "memory"); }
__device__ __forceinline__ uint4 lds128(uint32_t a) {
    uint4 v; asm volatile("ld.shared.v4.b32 {%0,%1,%2,%3}, [%4];" : "=r"(v.x), "=r"(v.y), "=r"(v.z), "=r"(v.w) : "r"(a) : "memory"); return v;
}
__device__ __forceinline__ uint32_t lds32(uint32_t a) { uint32_t v; asm volatile("ld.shared.b32 %0, [%1];" : "=r"(v) : "r"(a) : "memory"); return v; }
__device__ __forceinline__ int grab_tile(unsigned* ctr) {
    int v; asm volatile("atom.relaxed.gpu.global.inc.u32 %0, [%1], 0x7fffffff;" : "=r"(v) : "l"(ctr) : "memory"); return v;
}
__device__ __forceinline__ uint32_t opaque(uint32_t v) { uint32_t r; asm volatile("mov.b32 %0, %1;" : "=r"(r) : "r"(v)); return r; }
__device__ __forceinline__ unsigned clock32() { unsigned c; asm volatile("mov.u32 %0, %%clock;" : "=r"(c)); return c; }
__device__ __forceinline__ float rsq(float x) { float r; asm("rsqrt.approx.ftz.f32 %0, %1;" : "=f"(r) : "f"(x)); return r; }
__device__ __forceinline__ float rcp(float x) { float r; asm("rcp.approx.ftz.f32 %0, %1;" : "=f"(r) : "f"(x)); return r; }
__device__ __forceinline__ float lg2(float x) { float r; asm("lg2.approx.ftz.f32 %0, %1;" : "=f"(r) : "f"(x)); return r; }
__device__ __forceinline__ float f(uint32_t v) { return __uint_as_float(v); }
__device__ __forceinline__ uint32_t u(float v) { return __float_as_uint(v); }

constexpr uint32_t ONES = 0x3F803F80u;
constexpr float QSCALE = 0.07216878364870322f * 1.4426950408889634f;

__device__ __forceinline__ void issue_tile(const CUtensorMap* m0, const CUtensorMap* m1, uint32_t sb, int s, int tl, uint64_t pol) {
    const uint32_t full = sb + SM_BAR + s * 8, dst = sb + SM_STAGES + s * STAGE;
    const int par = tl * TP, y = par >> 8, x = par & 255;
    mbar_expect(full, STAGE);
    asm volatile("cp.async.bulk.tensor.5d.shared::cluster.global.mbarrier::complete_tx::bytes.L2::cache_hint [%0], [%1, {%3,%4,%3,%3,%5}], [%2], %6;"
                 ::"r"(dst), "l"(m0), "r"(full), "r"(0), "r"(x), "r"(2 * y), "l"(pol) : "memory");
    asm volatile("cp.async.bulk.tensor.4d.shared::cluster.global.mbarrier::complete_tx::bytes.L2::cache_hint [%0], [%1, {%3,%4,%3,%5}], [%2], %6;"
                 ::"r"(dst + TP * 4 * C * 2), "l"(m1), "r"(full), "r"(0), "r"(x), "r"(y), "l"(pol) : "memory");
}

__device__ __forceinline__ void prefetch_l2(const void* a, int n) { asm volatile("cp.async.bulk.prefetch.L2.global [%0], %1;" ::"l"(a), "r"(n) : "memory"); }
__device__ __forceinline__ uint4 ldg_relaxed(const uint4* p) {
    uint4 v; asm volatile("ld.relaxed.gpu.global.v4.u32 {%0,%1,%2,%3}, [%4];" : "=r"(v.x), "=r"(v.y), "=r"(v.z), "=r"(v.w) : "l"(p) : "memory"); return v;
}
__device__ __forceinline__ uint32_t ldg_relaxed32(const void* p) {
    uint32_t v; asm volatile("ld.relaxed.gpu.global.u32 %0, [%1];" : "=r"(v) : "l"(p) : "memory"); return v;
}
__device__ __forceinline__ void stg_relaxed(uint4* p, uint32_t x, uint32_t y, uint32_t z, uint32_t w) {
    asm volatile("st.relaxed.gpu.global.v4.u32 [%0], {%1,%2,%3,%4};" ::"l"(p), "r"(x), "r"(y), "r"(z), "r"(w) : "memory");
}
__device__ __forceinline__ void stg_relaxed32(void* p, uint32_t x) { asm volatile("st.relaxed.gpu.global.u32 [%0], %1;" ::"l"(p), "r"(x) : "memory"); }
__device__ __forceinline__ bool has(const uint4& v, uint32_t m) { return v.x == m || v.y == m || v.z == m || v.w == m; }
__device__ __forceinline__ uint32_t hadd2v(uint32_t a, uint32_t b) {
    uint32_t r; asm volatile("add.rn.bf16x2 %0, %1, %2;" : "=r"(r) : "r"(a), "r"(b)); return r;
}

__device__ __forceinline__ void red8h(uint4* p, uint32_t x, uint32_t y, uint32_t z, uint32_t w) {
    asm volatile("red.relaxed.gpu.global.add.noftz.v4.f16x2 [%0], {%1,%2,%3,%4};" ::"l"(p), "r"(x), "r"(y), "r"(z), "r"(w) : "memory");
}
__device__ __forceinline__ uint2 lds64v(uint32_t a) {
    uint2 v; asm volatile("ld.volatile.shared.v2.b32 {%0,%1}, [%2];" : "=r"(v.x), "=r"(v.y) : "r"(a) : "memory"); return v;
}
__device__ __forceinline__ uint4 lds128v(uint32_t a) {
    uint4 v; asm volatile("ld.volatile.shared.v4.b32 {%0,%1,%2,%3}, [%4];" : "=r"(v.x), "=r"(v.y), "=r"(v.z), "=r"(v.w) : "r"(a) : "memory"); return v;
}
__device__ __forceinline__ uint32_t brow(int r) { return RD_B + r * 144 + (r >> 3) * 64; }

enum { B_QK = 1, B_QN = 2, B_GRP = 3  , B_Q = 5, B_MERGE = 6, B_ALL = 7, B_MAX = 8  , B_WARP = 10, B_POLL = 11, B_SLOW = 12 };

__device__ __noinline__ void slow_rows(const char* __restrict__ f0, const char* __restrict__ f1, const __nv_bfloat16* __restrict__ q,
                                       const __nv_bfloat16* __restrict__ wq, const __nv_bfloat16* __restrict__ wk, const uint32_t sb)
{
    const int warp = threadIdx.x >> 5, lane = threadIdx.x & 31;
    float* const sm = reinterpret_cast<float*>(__cvta_shared_to_generic(sb + RD_W));
    bar_sync(B_POLL, 352);
    for (int i = threadIdx.x; i < 4 * C; i += 96) sm[i] = __bfloat162float(q[(blockIdx.x & 12) * C + i]);
    bar_sync(B_SLOW, 96);
#pragma unroll 1
    for (int j = threadIdx.x; j < 4 * C; j += 96) {
        const float* const x = sm + j / C * C;
        float mu = 0.f, var = 0.f, s = 0.f;
#pragma unroll 1
        for (int i = 0; i < C; i++) mu += x[i];
        mu *= 1.f / C;
#pragma unroll 4
        for (int i = 0; i < C; i++) { var = fmaf(x[i] - mu, x[i] - mu, var); s = fmaf(x[i] - mu, __bfloat162float(wq[i * C + j % C]), s); }
        sm[4 * C + j] = s * rsq(var * (1.f / C) + 1e-5f);
    }
    bar_sync(B_SLOW, 96);
#pragma unroll 1
    for (int j = threadIdx.x; j < 4 * C; j += 96) {
        float s = 0.f;
#pragma unroll 4
        for (int i = 0; i < C; i++) s = fmaf(sm[4 * C + j / C * C + i], __bfloat162float(wk[j % C * C + i]), s);
        sm[j] = s * QSCALE;
    }
    bar_sync(B_SLOW, 96);
    float k[4][6], a[4][6], m[4], l[4];
#pragma unroll
    for (int r = 0; r < 4; r++) {
        m[r] = -INFINITY; l[r] = 0.f;
#pragma unroll
        for (int i = 0; i < 6; i++) { k[r][i] = sm[r * C + 64 * (i >> 1) + 2 * lane + (i & 1)]; a[r][i] = 0.f; }
    }
#pragma unroll 1
    for (int par = warp; par < W1 * W1; par += 3) {
        const uint32_t* p0 = reinterpret_cast<const uint32_t*>(f0 + (size_t)((par >> 8) * 2 * W0 + (par & 255) * 2) * (C * 2)) + lane;
        const uint32_t* p1 = reinterpret_cast<const uint32_t*>(f1 + (size_t)par * (C * 2)) + lane;
        uint32_t v[4][3];
#pragma unroll
        for (int i = 0; i < 3; i++)
#pragma unroll
            for (int j = 0; j < 4; j++) v[j][i] = hadd2(__ldg(p0 + ((j >> 1) * W0 + (j & 1)) * (C / 2) + 32 * i), __ldg(p1 + 32 * i));
#pragma unroll
        for (int j = 0; j < 4; j++) {
            float x[6], s1 = 0.f, s2 = 0.f, d[4] = {0.f, 0.f, 0.f, 0.f};
#pragma unroll
            for (int i = 0; i < 3; i++) { x[2 * i] = bflo(v[j][i]); x[2 * i + 1] = bfhi(v[j][i]); s1 += x[2 * i] + x[2 * i + 1]; }
#pragma unroll
            for (int o = 1; o < 32; o <<= 1) s1 += __shfl_xor_sync(~0u, s1, o);
#pragma unroll
            for (int i = 0; i < 6; i++) {
                x[i] -= s1 * (1.f / C); s2 = fmaf(x[i], x[i], s2);
#pragma unroll
                for (int r = 0; r < 4; r++) d[r] = fmaf(x[i], k[r][i], d[r]);
            }
#pragma unroll
            for (int o = 1; o < 32; o <<= 1) {
                s2 += __shfl_xor_sync(~0u, s2, o);
#pragma unroll
                for (int r = 0; r < 4; r++) d[r] += __shfl_xor_sync(~0u, d[r], o);
            }
            const float rs = rsq(s2 * (1.f / C) + 1e-5f);
#pragma unroll
            for (int r = 0; r < 4; r++) {
                const float nm = fmaxf(m[r], d[r] * rs), al = ex2(m[r] - nm), p = ex2(d[r] * rs - nm);
                m[r] = nm; l[r] = fmaf(l[r], al, p);
#pragma unroll
                for (int i = 0; i < 6; i++) a[r][i] = fmaf(a[r][i], al, x[i] * (p * rs));
            }
        }
    }
    bar_sync(B_SLOW, 96);
#pragma unroll
    for (int r = 0; r < 4; r++) {
        float* const o = sm + ((r * 3 + warp) * 32 + lane) * 8;
#pragma unroll
        for (int i = 0; i < 6; i++) o[i] = a[r][i];
        o[6] = l[r]; o[7] = m[r];
    }
    bar_sync(B_SLOW, 96);
#pragma unroll 1
    for (int r = warp; r < 4; r += 3) {
        const float* const o = sm + (r * 96 + lane) * 8;
        const float M = fmaxf(fmaxf(o[7], o[256 + 7]), o[512 + 7]), e0 = ex2(o[7] - M), e1 = ex2(o[256 + 7] - M), e2 = ex2(o[512 + 7] - M);
        float x[7];
#pragma unroll
        for (int i = 0; i < 7; i++) x[i] = o[i] * e0 + o[256 + i] * e1 + o[512 + i] * e2;
        uint32_t hi[3], lo[3];
        const float rl = 1.f / x[6];
#pragma unroll
        for (int i = 0; i < 3; i++) {
            hi[i] = packh(x[2 * i] * rl, x[2 * i + 1] * rl);
            const float2 h = unpackh(hi[i]);
            lo[i] = packh(fmaf(x[2 * i], rl, -h.x), fmaf(x[2 * i + 1], rl, -h.y));
        }
        const uint32_t bw = sb + brow(8 * r + (lane & 3)) + (lane >> 2) * 16;
        sts128(bw, hi[0], hi[1], hi[2], lane ? 0u : 0x3C00u);
        sts128(bw + 4 * 144, lo[0], lo[1], lo[2], 0);
    }
    bar_sync(B_SLOW, 96);
}

__device__ __forceinline__ void reducer(const char* __restrict__ f0, const char* __restrict__ f1, const __nv_bfloat16* __restrict__ q, const __nv_bfloat16* __restrict__ wq, const __nv_bfloat16* __restrict__ wk,
                                        Scratch* scr, const __nv_bfloat16* __restrict__ wv, const __nv_bfloat16* __restrict__ wo,
                                        __nv_bfloat16* __restrict__ out, const uint32_t sb, const int GS)
{
    const int warp = threadIdx.x >> 5, lane = threadIdx.x & 31, b = blockIdx.x;
    const int g = lane >> 2, t = lane & 3;
    if (threadIdx.x == 256) TS(0);
    if (b < NSRC && warp < 8) {
        const uint32_t wqs = sb + RD_W, wbar = sb + RD_BAR;
        const int hr = lane >> 4, qt = (lane >> 2) & 3, sub = lane & 3;
        const uint32_t* qp = reinterpret_cast<const uint32_t*>(q + (warp + 8 * hr) * C + 48 * qt + 6 * sub);
        uint32_t qw[6];
#pragma unroll
        for (int j = 0; j < 3; j++) { qw[j] = __ldg(qp + j); qw[3 + j] = __ldg(qp + 12 + j); }
        if (lane == 0) { mbar_init(wbar + warp * 8, 1); asm volatile("fence.mbarrier_init.release.cluster;" ::: "memory"); mbar_expect(wbar + warp * 8, 9216);
            asm volatile("cp.async.bulk.shared::cluster.global.mbarrier::complete_tx::bytes [%0], [%1], 9216, [%2];"
                         ::"r"(wqs + warp * 9232), "l"(wq + 24 * warp * C), "r"(wbar + warp * 8) : "memory");
        }
        __syncwarp();
        if (threadIdx.x == 0) TSP(2, 0);
        float e[12];
#pragma unroll
        for (int j = 0; j < 6; j++) { e[2 * j] = bflo(qw[j]); e[2 * j + 1] = bfhi(qw[j]); }
        float sm = ((e[0] + e[1]) + (e[2] + e[3])) + ((e[4] + e[5]) + (e[6] + e[7])) + ((e[8] + e[9]) + (e[10] + e[11]));
#pragma unroll
        for (int o = 1; o < 16; o <<= 1) sm += __shfl_xor_sync(~0u, sm, o);
        if (threadIdx.x == 0) TSP(5, u(sm));
        float v0 = 0.f, v1 = 0.f;
#pragma unroll
        for (int j = 0; j < 12; j++) e[j] -= sm * (1.f / C);
#pragma unroll
        for (int j = 0; j < 6; j++) { v0 = fmaf(e[j], e[j], v0); v1 = fmaf(e[6 + j], e[6 + j], v1); }
        v0 += v1;
#pragma unroll
        for (int o = 1; o < 16; o <<= 1) v0 += __shfl_xor_sync(~0u, v0, o);
        const float rq = rsq(v0 * (1.f / C) + 1e-5f);
#pragma unroll
        for (int j = 0; j < 6; j++)
            sts32(sb + RD_QN + (3 * sub + (j >> 1)) * 512 + (4 * warp + qt) * 16 + (2 * (j & 1) + hr) * 4, pack2(e[j] * rq, e[6 + j] * rq));
        if (threadIdx.x == 0) TSP(8, 0);
        uint32_t wkf[2][3];
#pragma unroll
        for (int i = 0; i < 2; i++)
#pragma unroll
            for (int j = 0; j < 3; j++) wkf[i][j] = __ldg(reinterpret_cast<const uint32_t*>(wk + (16 * b + 8 * i + g) * C + 24 * warp + 8 * j + 2 * t));
        bar_sync(B_QN, 256);
        float acc[2][3][4];
#pragma unroll
        for (int i = 0; i < 3; i++)
#pragma unroll
            for (int e = 0; e < 4; e++) acc[0][i][e] = acc[1][i][e] = 0.f;
        const uint32_t ba = wqs + (lane & 7) * 9232 + (lane >> 3) * 384 + 48 * warp;
        uint4 a[12];
#pragma unroll
        for (int kk = 0; kk < 12; kk++) a[kk] = lds128(sb + RD_QN + kk * 512 + lane * 16);
        mbar_wait(wbar + (lane & 7) * 8, 0);
        __syncwarp();
        if (threadIdx.x == 0) TSP(4, 0);
#pragma unroll
        for (int kp = 0; kp < 6; kp++)
#pragma unroll
            for (int i = 0; i < 3; i++) {
                uint32_t bb[4];
                ldsm4t(bb, ba + kp * 1536 + i * 16);
                mma(acc[0][i], a[2 * kp].x, a[2 * kp].y, a[2 * kp].z, a[2 * kp].w, bb[0], bb[1]);
                mma(acc[1][i], a[2 * kp + 1].x, a[2 * kp + 1].y, a[2 * kp + 1].z, a[2 * kp + 1].w, bb[2], bb[3]);
            }
        if (threadIdx.x == 0) TSP(7, u(acc[1][2][3]));
        float kq[2][4] = {{0.f, 0.f, 0.f, 0.f}, {0.f, 0.f, 0.f, 0.f}};
#pragma unroll
        for (int j = 0; j < 3; j++) {
            const uint32_t a0 = pack2(acc[0][j][0] + acc[1][j][0], acc[0][j][1] + acc[1][j][1]), a1 = pack2(acc[0][j][2] + acc[1][j][2], acc[0][j][3] + acc[1][j][3]);
            mma8(kq[0], a0, a1, wkf[0][j]);
            mma8(kq[1], a0, a1, wkf[1][j]);
        }
        if (warp < 7) {
            sts128(sb + RD_KQ + warp * 1024 + lane * 16, u(kq[0][0]), u(kq[0][1]), u(kq[0][2]), u(kq[0][3]));
            sts128(sb + RD_KQ + warp * 1024 + 512 + lane * 16, u(kq[1][0]), u(kq[1][1]), u(kq[1][2]), u(kq[1][3]));
            bar_arrive(B_Q, 256);
        } else {
            bar_sync(B_Q, 256);
#pragma unroll
            for (int w = 0; w < 7; w++)
#pragma unroll
                for (int i = 0; i < 2; i++) {
                    const uint4 o = lds128(sb + RD_KQ + w * 1024 + i * 512 + lane * 16);
                    kq[i][0] += f(o.x); kq[i][1] += f(o.y); kq[i][2] += f(o.z); kq[i][3] += f(o.w);
                }
            stg_relaxed(g_qk + b * 32 + lane, ~pack2(kq[0][0] * QSCALE, kq[0][1] * QSCALE), ~pack2(kq[0][2] * QSCALE, kq[0][3] * QSCALE),
                        ~pack2(kq[1][0] * QSCALE, kq[1][1] * QSCALE), ~pack2(kq[1][2] * QSCALE, kq[1][3] * QSCALE));
            if (lane == 0) TS(10);
        }
    } else if (b >= NSRC) {
        if (b == NSRC && warp == 0) stg_relaxed32(g_mmax + lane, 0);
        __nanosleep(2500);
    }
    bar_sync(B_ALL, NTHREADS);

#pragma unroll 1
    for (int r = 0; r < 3; r++) {
        uint4 v[8];
#pragma unroll
        for (int k = 0; k < 8; k++) {
            const int idx = (8 * r + k) * 384 + threadIdx.x;
            v[k] = __ldg(reinterpret_cast<const uint4*>(idx < 4608 ? wv : wo - C * C) + idx);
        }
#pragma unroll
        for (int k = 0; k < 8; k++) {
            const int idx = (8 * r + k) * 384 + threadIdx.x, row = idx / 24;
            sts128(sb + RD_W + row * WROW + (idx - 24 * row) * 16, v[k].x, v[k].y, v[k].z, v[k].w);
        }
    }
    if (threadIdx.x < 256) {
        stg_relaxed(g_acc + (threadIdx.x >> 7) * ACC + (b >> 2) * 128 + (threadIdx.x & 127), 0, 0, 0, 0);
        __threadfence();
    }
    if (threadIdx.x == 0) sts128(sb + RD_RDY, 0, 0, 0, 0);
    bar_sync(B_ALL, NTHREADS);
    uint32_t wa[12][4];
    float ws0 = 0.f, ws1 = 0.f, qv0 = 0.f, qv1 = 0.f;
    __nv_bfloat16* op = out;
    if (warp < 3) {
        const int col = 48 * (b & 3) + 16 * warp;
        float d[24][4];
#pragma unroll
        for (int i = 0; i < 24; i++) d[i][0] = d[i][1] = d[i][2] = d[i][3] = 0.f;
        const int mi = lane >> 3, r = lane & 7;
        const uint32_t aa = sb + RD_W + (C + (mi >> 1) * 8 + r) * WROW + (col + (mi & 1) * 8) * 2;
        const uint32_t ba = sb + RD_W + ((mi >> 1) * 8 + r) * WROW + (mi & 1) * 16;
#pragma unroll 1
        for (int kk = 0; kk < 12; kk++) {
            uint32_t a[4];
            ldsm4t(a, aa + kk * 16 * WROW);
#pragma unroll
            for (int i = 0; i < 12; i++) {
                uint32_t bb[4];
                ldsm4(bb, ba + i * 16 * WROW + kk * 32);
                mma(d[2 * i], a[0], a[1], a[2], a[3], bb[0], bb[1]);
                mma(d[2 * i + 1], a[0], a[1], a[2], a[3], bb[2], bb[3]);
            }
        }
        float c0 = 0.f, c1 = 0.f, m0 = 0.f, m1 = 0.f;
#pragma unroll
        for (int i = 0; i < 24; i++) { c0 += d[i][0] + d[i][1]; c1 += d[i][2] + d[i][3]; }
        c0 += __shfl_xor_sync(~0u, c0, 1); c1 += __shfl_xor_sync(~0u, c1, 1);
        c0 += __shfl_xor_sync(~0u, c0, 2); c1 += __shfl_xor_sync(~0u, c1, 2);
        c0 *= 1.f / C; c1 *= 1.f / C;
#pragma unroll
        for (int i = 0; i < 24; i++) {
            d[i][0] -= c0; d[i][1] -= c0; d[i][2] -= c1; d[i][3] -= c1;
            m0 = fmaxf(m0, fmaxf(fabsf(d[i][0]), fabsf(d[i][1]))); m1 = fmaxf(m1, fmaxf(fabsf(d[i][2]), fabsf(d[i][3])));
        }
        m0 = fmaxf(m0, __shfl_xor_sync(~0u, m0, 1)); m1 = fmaxf(m1, __shfl_xor_sync(~0u, m1, 1));
        m0 = fmaxf(m0, __shfl_xor_sync(~0u, m0, 2)); m1 = fmaxf(m1, __shfl_xor_sync(~0u, m1, 2));
        const uint32_t e0 = min(max(u(m0) >> 23, 12u), 254u), e1 = min(max(u(m1) >> 23, 12u), 254u);
        const float s0 = f((265u - e0) << 23), s1 = f((265u - e1) << 23);
        const bool k0 = fabsf(c0) < INFINITY, k1 = fabsf(c1) < INFINITY;
        ws0 = k0 ? f((e0 - 11u) << 23) : c0; ws1 = k1 ? f((e1 - 11u) << 23) : c1;
#pragma unroll
        for (int i = 0; i < 24; i++) {
            const int kk = i < 16 ? i & 7 : i >> 1, hf = i < 16 ? i >> 3 : i & 1;
            wa[kk][2 * hf] = k0 ? packh(d[i][0] * s0, d[i][1] * s0) : 0u;
            wa[kk][2 * hf + 1] = k1 ? packh(d[i][2] * s1, d[i][3] * s1) : 0u;
        }
        const int o = ((b & 12) + t) * C + col + g;
        qv0 = __bfloat162float(q[o]); qv1 = __bfloat162float(q[o + 8]);
        op = out + o;
        asm volatile("" : "+l"(op));
        if (threadIdx.x == 0) TSE(6);
    } else if (warp == 3) {
        if (lane == 0) {
            uint32_t m;
            for (int it = 0;; it++) {
                const int left = NT - 2 * NST * GS - (int)ldg_relaxed32(g_ctr);
                m = ldg_relaxed32(g_mmax + b);
                if (left <= REFT && m) break;
                if (left <= 0) { m = 0x80000000u; break; }
                if (it > SPIN_LIMIT) __trap();
                __nanosleep(300);
            }
            asm volatile("st.release.gpu.global.u32 [%0], %1;" ::"l"(g_mref + b), "r"(~u(f(m >> 31 ? m ^ 0x80000000u : ~m) + 8.f)) : "memory");
            TSE(7);
        }
        return;
    } else {
        const int pr = warp & 1;
        const uint4* const pa = g_acc + ((b >> 2) * 2 + pr) * 64 + lane;
        const uint32_t bw = opaque(sb + brow(16 * pr + 8 * ((lane >> 2) & 1) + t) + (lane >> 3) * 16);
        const uint32_t fw = opaque(sb + RD_RDY + pr * 4);
        const uint32_t n0 = packh(0.f, (float)((GS + 1) >> 1)), n1 = packh(0.f, (float)(GS >> 1)), nstart = packh(0.f, (float)POLLN);
        for (int it = 0; ldg_relaxed32(reinterpret_cast<const uint32_t*>(pa - lane) + 3) < nstart; it++)
            if (it > SPIN_LIMIT) __trap();
        for (const unsigned c = clock32(); clock32() - c < ((warp - 4) >> 1) * PGAP;) {}
        for (int it = 0;; it++) {
            const uint4 a0 = ldg_relaxed(pa), a1 = ldg_relaxed(pa + ACC), b0 = ldg_relaxed(pa + 32), b1 = ldg_relaxed(pa + ACC + 32);
            bar_sync(B_WARP, 32);
            const bool ok = a0.w >= n0 && a1.w >= n1 && b0.w >= n0 && b1.w >= n1, all = __all_sync(~0u, ok);
            const uint32_t w = ok ? bw : bw - (RD_B - RD_QN);
            sts128(w, a0.x, a0.y, a0.z, a0.w); sts128(w + 4 * 144, a1.x, a1.y, a1.z, a1.w);
            sts128(w + 64, b0.x, b0.y, b0.z, b0.w); sts128(w + 4 * 144 + 64, b1.x, b1.y, b1.z, b1.w);
            sts32(all ? fw : fw + 8, 1);
            if (all) break;
            if (it > SPIN_LIMIT) __trap();
        }
        bar_arrive(B_POLL, 352);
        if (warp == 4) {
            if (b < NSRC) g_qk[b * 32 + lane] = make_uint4(0, 0, 0, 0);
            if (lane == 0) { g_mref[b] = 0; if (b == NSRC) g_ctr[0] = 0; }
        }
        return;
    }
    const uint32_t br = opaque(sb + brow(lane));
#pragma unroll 1
    for (uint32_t pass = 0;; pass = 1) {
        uint4 x[8];
        float o[5][4];
        for (int it = 0;; it++) {
            const uint2 rdy = lds64v(sb + RD_RDY);
            x[0] = lds128v(br); x[1] = lds128v(br + 16);
            if (it > 64 * SPIN_LIMIT) __trap();
            if (rdy.x & rdy.y) break;
        }
        if (threadIdx.x == 0) TSX(8, 0);
#pragma unroll
        for (int j = 2; j < 8; j++) x[j] = lds128v(br + j * 16);
#pragma unroll
        for (int j = 0; j < 5; j++) o[j][0] = o[j][1] = o[j][2] = o[j][3] = 0.f;
#pragma unroll
        for (int i = 0; i < 4; i++) {
            mmah(o[3 + (i & 1)], 0x3C00u, 0x3C00u, 0x3C00u, 0x3C00u, x[2 * i].w, x[2 * i + 1].w);
            mmah(o[0], wa[2 * i][0], wa[2 * i][1], wa[2 * i][2], wa[2 * i][3], x[2 * i].x, x[2 * i].y);
            mmah(o[1], wa[2 * i + 1][0], wa[2 * i + 1][1], wa[2 * i + 1][2], wa[2 * i + 1][3], x[2 * i + 1].x, x[2 * i + 1].y);
            mmah(o[2], wa[8 + i][0], wa[8 + i][1], wa[8 + i][2], wa[8 + i][3], x[2 * i].z, x[2 * i + 1].z);
        }
        const float L = (o[3][0] + o[3][1]) + (o[4][0] + o[4][1]), r = rcp(L);
        const float y0 = ((o[0][0] + o[0][1]) + (o[1][0] + o[1][1])) + (o[2][0] + o[2][1]);
        const float y1 = ((o[0][2] + o[0][3]) + (o[1][2] + o[1][3])) + (o[2][2] + o[2][3]);
        const uint32_t y = pack2(fmaf(y0, r * ws0, qv0), fmaf(y1, r * ws1, qv1));
        asm volatile("{.reg .b16 l, h; mov.b32 {l, h}, %1; st.global.b16 [%0], l; st.global.b16 [%0 + 16], h;}" ::"l"(op), "r"(y) : "memory");
        if (threadIdx.x == 0) TSD(11, y);
        if (__builtin_expect(__all_sync(~0u, L >= 0.001953125f && L <= 2048.f && fabsf(y0) < INFINITY) || pass, 1)) break;
        const uint32_t keep = sb + RD_W + 32768 + warp * 6144 + lane * 16;
#pragma unroll
        for (int kk = 0; kk < 12; kk++) sts128(keep + kk * 512, wa[kk][0], wa[kk][1], wa[kk][2], wa[kk][3]);
        slow_rows(f0, f1, q, wq, wk, sb);
#pragma unroll
        for (int kk = 0; kk < 12; kk++) {
            const uint4 v = lds128(keep + kk * 512);
            wa[kk][0] = v.x; wa[kk][1] = v.y; wa[kk][2] = v.z; wa[kk][3] = v.w;
        }
    }
}

__global__ void __launch_bounds__(NTHREADS, 1)
attn_main(const char* __restrict__ f0, const char* __restrict__ f1,
          const __nv_bfloat16* __restrict__ q, const __nv_bfloat16* __restrict__ wq, const __nv_bfloat16* __restrict__ wk, Scratch* scr,
          const __nv_bfloat16* __restrict__ wv, const __nv_bfloat16* __restrict__ wo, __nv_bfloat16* __restrict__ out,
          const __grid_constant__ CUtensorMap m0, const __grid_constant__ CUtensorMap m1)
{
    extern __shared__ char smem_raw[];
    const uint32_t sb = (s2u(smem_raw) + 1023u) & ~1023u;
    const int G = gridDim.x - NRD;
    const int b = blockIdx.x - NRD;
    if (threadIdx.x == 0 && b >= 0) {
        const char* a = f0 + (uint32_t)(b * (4 * TP * C * 2) + (b >> 4) * (W0 * C * 2));
        prefetch_l2(a, 4 * TP * C * 2);
        prefetch_l2(a + W0 * C * 2, 4 * TP * C * 2);
        prefetch_l2(f1 + b * (2 * TP * C * 2), 2 * TP * C * 2);
        prefetch_l2((const char*)(b % (2 * WSL) < WSL ? wq : wk) + b % WSL * (C * C * 2 / WSL), C * C * 2 / WSL);
    }
    if (b < 0) { reducer(f0, f1, q, wq, wk, scr, wv, wo, out, sb, G); return; }
    const int warp = __shfl_sync(~0u, threadIdx.x >> 5, 0), lane = threadIdx.x & 31;
    const int g = lane >> 2, t = lane & 3;

    if (warp >= 8) {
        if (warp < 10) {
            const int p = warp - 8;
            const unsigned c0 = clock32();
            const uint32_t sbp = opaque(sb), bar = sbp + SM_BAR + p * 8;
            uint64_t pol; asm volatile("createpolicy.fractional.L2::evict_first.b64 %0, 1.0;" : "=l"(pol));
            if (elect()) {
                if (p == 0) TS(0);
                asm volatile("prefetch.tensormap [%0];" ::"l"(p ? &m1 : &m0) : "memory");
#pragma unroll
                for (int n = 0; n < NI; n++) mbar_init(bar + n * 16, 2);
                asm volatile("fence.mbarrier_init.release.cluster;" ::: "memory");
#pragma unroll
                for (int n = 0; n < NI; n++) {
                    issue_tile(&m0, &m1, sbp, p + 2 * n, 2 * b + p + 2 * n * G, pol);
                    TR(0, 2 * n + p);
                    sts32(sbp + SM_FLAG + (p + 2 * n) * 4, 0);
                    mbar_arrive(bar + n * 16);
                }
#pragma unroll
                for (int n = 0; n < NS / 2; n++) {
                    if (n >= NI) mbar_init(bar + n * 16, 2);
                    mbar_init(bar + NS * 8 + n * 16, 1);
                }
                if (p == 0) mbar_init(sbp + SM_REF, 1);
                asm volatile("fence.mbarrier_init.release.cluster;" ::: "memory");
            }
            __syncwarp();
            bar_arrive(B_QK, NTHREADS);
            if (elect()) {
                int tl = 2 * b + p + 2 * NI * G;
                int s = p + 2 * NI; uint32_t ph = 1;
                int sa = p, na = 0; uint32_t pa = 0;
                bool late = false;
                for (int n = NI;; n++) {
                    const int d = n < NRAMP ? D0 : (tl >= NT - TAILT ? D2 : D1);
                    while (n - na >= d) {
                        mbar_wait(sbp + SM_BAR + sa * 8, pa);
                        if (na < NS / 2) TR(1, 2 * na + p);
                        na++; sa += 2;
                        if (sa >= NS) { sa -= NS; pa ^= 1; }
                    }
                    mbar_wait(sbp + SM_BAR + (NS + s) * 8, ph);
                    if (n < NPACE) while (clock32() - c0 < (n ? T1 + (2 * (n - 1) + p) * TG : T0)) {}
                    issue_tile(&m0, &m1, sbp, s, tl, pol);
                    TR(0, 2 * n + p);
                    int nxt = tl + 2 * G;
                    if (n >= NST - 1) nxt = grab_tile(g_ctr) + 2 * NST * G;
                    const bool last = nxt >= NT;
                    uint32_t flag = last;
                    if (!late && nxt >= NT - MAXT - 16 * b) { late = true; flag |= 2; }
                    if (last) mbar_wait(sbp + SM_REF, 0);
                    sts32(sbp + SM_FLAG + s * 4, flag);
                    mbar_arrive(sbp + SM_BAR + s * 8);
                    if (last) break;
                    s += 2;
                    if (s >= NS) { s -= NS; ph ^= 1; }
                    tl = nxt;
                }
                if (p) TSE(5);
            }
            return;
        }
        const int h = threadIdx.x - 320;
        uint4 v[6];
        for (int it = 0;; it++) {
            bool miss = false;
#pragma unroll
            for (int k = 0; k < 6; k++) v[k] = ldg_relaxed(g_qk + k * 64 + h);
#pragma unroll
            for (int k = 0; k < 6; k++) miss |= has(v[k], 0);
            if (!miss) break;
            if (it > SPIN_LIMIT) __trap();
            if (it == 0) __nanosleep(QSLEEP);
        }
#pragma unroll
        for (int k = 0; k < 6; k++) sts128(sb + SM_QK + (k * 64 + h) * 16, ~v[k].x, ~v[k].y, ~v[k].z, ~v[k].w);
        __syncwarp();
        bar_sync(B_QK, NTHREADS);
        if (warp == 11) return;
        uint32_t r = 1;
        for (int it = 0;; it++) {
            __nanosleep(500);
            if (lane < NQ) asm volatile("ld.acquire.gpu.global.u32 %0, [%1];" : "=r"(r) : "l"(g_mref + lane) : "memory");
            if (__all_sync(~0u, r != 0)) break;
            if (it > SPIN_LIMIT) __trap();
        }
        if (lane < NQ) sts32(sb + SM_M + lane * 4, ~r);
        __syncwarp();
        if (lane == 0) { mbar_arrive(sb + SM_REF); TSE(7); }
        return;
    }

    const int grp = warp >> 2, cw = warp & 3;
    const int xp = lane & 7, mi = lane >> 3;
    const uint32_t offS1 = opaque(12288 + xp * 128 + ((mi ^ xp) << 4)), offS1x = opaque(offS1 ^ 64);
    const uint32_t offS0 = opaque(offS1 - 12288 + cw * 3072), offS0x = opaque(offS0 ^ 64);
    const uint32_t offT = opaque(mi * 3072 + xp * 128 + (((cw + 4 * grp) ^ xp) << 4)), offTx = opaque(offT ^ 64);
    const uint32_t offU = opaque(12288 + (mi % 3) * 1024 + xp * 128 + (((cw + 4 * (grp ^ (mi / 3))) ^ xp) << 4));
    const uint32_t offV = opaque(12288 + (1 + (mi & 1)) * 1024 + xp * 128 + (((cw + 4 * (grp ^ 1)) ^ xp) << 4));
    const int shl = opaque(9 * t), shl4 = opaque(9 * t + 4);
    const uint32_t pw = opaque((cw >> 1) * 512 + lane * 16 + (cw & 1) * 8), muw = opaque(1024 + t * 16 + cw * 4);
    const uint32_t prd = opaque(lane * 16), mur = opaque(1024 + t * 16);
    uint32_t pb0 = sb + SM_P + grp * 2 * PBUF;
    const uint32_t pbx = pb0 ^ (pb0 + PBUF);
    const bool odd = g & 1;
    const int barid = B_GRP + grp;
    const bool elected = cw == 3 && lane == 0;

    uint32_t qa[48];
    float r_lo, r_hi;
    bar_sync(B_QK, NTHREADS);
    {
        float rr[2][4] = {{0.f, 0.f, 0.f, 0.f}, {0.f, 0.f, 0.f, 0.f}};
#pragma unroll
        for (int kk = 0; kk < 12; kk++) {
            const uint4 v = lds128(sb + SM_QK + kk * 512 + lane * 16);
            qa[4 * kk] = v.x; qa[4 * kk + 1] = v.y; qa[4 * kk + 2] = v.z; qa[4 * kk + 3] = v.w;
            mma(rr[kk & 1], v.x, v.y, v.z, v.w, ONES, ONES);
        }
        r_lo = rr[0][0] + rr[1][0]; r_hi = rr[0][2] + rr[1][2];
    }
    if (threadIdx.x == 0) TS(1);

    float acc[6][4];
#pragma unroll
    for (int i = 0; i < 6; i++) acc[i][0] = acc[i][1] = acc[i][2] = acc[i][3] = 0.f;
    float m_lo = -INFINITY, m_hi = -INFINITY, l_lo = 0.f, l_hi = 0.f;
    float cm[4] = {0.f, 0.f, 0.f, 0.f};
    uint32_t xt[6][4], yt[6]; uint4 pa, pb, mv;
    int s = grp; uint32_t ph = 0;
    while (true) {
        mbar_wait(sb + SM_BAR + s * 8, ph);
        PH(0, 0);
        const uint32_t stop = lds32(sb + SM_FLAG + s * 4);
        const uint32_t st = sb + SM_STAGES + s * STAGE;
        float sc[2][4], gr[4][4], sx[4];
#pragma unroll
        for (int e = 0; e < 4; e++) sc[0][e] = sc[1][e] = gr[0][e] = gr[1][e] = gr[2][e] = gr[3][e] = sx[e] = 0.f;
#pragma unroll
        for (int qq = 0; qq < 6; qq++) {
            uint32_t x[4], y[4];
            ldsm4(x, st + (qq & 1 ? offS0x : offS0) + (qq >> 1) * 1024);
            ldsm4(y, st + (qq & 1 ? offS1x : offS1) + (qq >> 1) * 1024);
#pragma unroll
            for (int e = 0; e < 4; e++) x[e] = hadd2(x[e], y[e]);
            mma8(gr[0], x[0], x[1], x[0]);
            mma8(gr[1], x[0], x[1], x[1]);
            mma(sx, x[0], x[1], x[2], x[3], ONES, ONES);
            mma8(gr[GR4 ? 2 : 0], x[2], x[3], x[2]);
            mma8(gr[GR4 ? 3 : 1], x[2], x[3], x[3]);
            mma(sc[0], qa[8 * qq], qa[8 * qq + 1], qa[8 * qq + 2], qa[8 * qq + 3], x[0], x[1]);
            mma(sc[1], qa[8 * qq + 4], qa[8 * qq + 5], qa[8 * qq + 6], qa[8 * qq + 7], x[2], x[3]);
        }
        ldsm4t(yt, st + offU);
        ldsm2t(yt + 4, st + offV);
#pragma unroll
        for (int i = 0; i < 6; i++) ldsm4t(xt[i], st + (i < 3 ? offT : offTx) + (i % 3) * 1024);

        const float mu = (sx[0] + sx[2]) * (1.f / C), ss = GR4 ? (odd ? (gr[0][1] + gr[1][3]) + (gr[2][1] + gr[3][3]) : (gr[0][0] + gr[1][2]) + (gr[2][0] + gr[3][2])) : (odd ? gr[0][1] + gr[1][3] : gr[0][0] + gr[1][2]);
        const float rs = rsq(fmaxf(fmaf(-mu, mu, fmaf(ss, 1.f / C, 1e-5f)), 1e-5f));
        const float mu0 = __shfl_sync(~0u, mu, shl), mu1 = __shfl_sync(~0u, mu, shl4);
        const float rs0 = __shfl_sync(~0u, rs, shl), rs1 = __shfl_sync(~0u, rs, shl4);
        const float u0 = fmaf(-mu0, r_lo, sc[0][0] + sc[1][0]), u1 = fmaf(-mu1, r_lo, sc[0][1] + sc[1][1]);
        const float u2 = fmaf(-mu0, r_hi, sc[0][2] + sc[1][2]), u3 = fmaf(-mu1, r_hi, sc[0][3] + sc[1][3]);
        const float d0 = fmaf(u0, rs0, -m_lo), d1 = fmaf(u1, rs1, -m_lo), d2 = fmaf(u2, rs0, -m_hi), d3 = fmaf(u3, rs1, -m_hi);
        PH(1, u(d0 + d2));
        float p0 = ex2(d0), p1 = ex2(d1), p2 = ex2(d2), p3 = ex2(d3);
        sts64(pb0 + pw, pack2(p0 * rs0, p1 * rs1), pack2(p2 * rs0, p3 * rs1));
        if (lane < 4) sts32(pb0 + muw, pack2(mu0, mu1));
        const bool over = bar_any(barid, 128, fmaxf(fmaxf(d0, d1), fmaxf(d2, d3)) > LAZY);
        PH(3, 0);
        pa = lds128(pb0 + prd); pb = lds128(pb0 + prd + 512); mv = lds128(pb0 + mur);
        if (elected) mbar_arrive(sb + SM_BAR + (NS + s) * 8);
        if (__builtin_expect(over, 0)) {
            const float s0 = u0 * rs0, s1 = u1 * rs1, s2 = u2 * rs0, s3 = u3 * rs1;
            float xl = fmaxf(s0, s1), xh = fmaxf(s2, s3);
            xl = fmaxf(xl, __shfl_xor_sync(~0u, xl, 1)); xh = fmaxf(xh, __shfl_xor_sync(~0u, xh, 1));
            xl = fmaxf(xl, __shfl_xor_sync(~0u, xl, 2)); xh = fmaxf(xh, __shfl_xor_sync(~0u, xh, 2));
            if (t < 2) sts32(sb + SM_MX + grp * 256 + ((g + 8 * t) * 4 + cw) * 4, u(t ? xh : xl));
            bar_sync(B_MAX + grp, 128);
            const uint4 ml4 = lds128(sb + SM_MX + grp * 256 + g * 16), mh4 = lds128(sb + SM_MX + grp * 256 + g * 16 + 128);
            const float nl = fmaxf(fmaxf(fmaxf(f(ml4.x), f(ml4.y)), fmaxf(f(ml4.z), f(ml4.w))), m_lo);
            const float nh = fmaxf(fmaxf(fmaxf(f(mh4.x), f(mh4.y)), fmaxf(f(mh4.z), f(mh4.w))), m_hi);
            p0 = ex2(s0 - nl); p1 = ex2(s1 - nl); p2 = ex2(s2 - nh); p3 = ex2(s3 - nh);
            sts64(pb0 + pw, pack2(p0 * rs0, p1 * rs1), pack2(p2 * rs0, p3 * rs1));
            const float al = ex2(m_lo - nl), ah = ex2(m_hi - nh);
            m_lo = nl; m_hi = nh;
            l_lo *= al; l_hi *= ah; cm[0] *= al; cm[2] *= ah;
#pragma unroll
            for (int i = 0; i < 6; i++) { acc[i][0] *= al; acc[i][1] *= al; acc[i][2] *= ah; acc[i][3] *= ah; }
            bar_sync(B_MAX + grp, 128);
            pa = lds128(pb0 + prd); pb = lds128(pb0 + prd + 512);
        }
        l_lo += p0 + p1; l_hi += p2 + p3;
        if (stop & 1) break;
#pragma unroll
        for (int i = 0; i < 6; i++) mma(acc[i], pa.x, pa.y, pa.z, pa.w, hadd2v(xt[i][0], yt[i]), hadd2v(xt[i][1], yt[i]));
        mma(cm, pa.x, pa.y, pa.z, pa.w, mv.x, mv.y);
#pragma unroll
        for (int i = 0; i < 6; i++) mma(acc[i], pb.x, pb.y, pb.z, pb.w, hadd2v(xt[i][2], yt[i]), hadd2v(xt[i][3], yt[i]));
        mma(cm, pb.x, pb.y, pb.z, pb.w, mv.z, mv.w);
        PH(4, u(acc[5][0]));
        if (stop) {
            float a = l_lo + __shfl_xor_sync(~0u, l_lo, 1), c = l_hi + __shfl_xor_sync(~0u, l_hi, 1);
            a += __shfl_xor_sync(~0u, a, 2); c += __shfl_xor_sync(~0u, c, 2);
            const uint32_t m = u((t ? m_hi : m_lo) + lg2(fmaxf(t ? c : a, 1.f)));
            if (t < 2) asm volatile("red.relaxed.gpu.global.max.u32 [%0], %1;" ::"l"(g_mmax + g + 8 * t), "r"(m >> 31 ? ~m : m | 0x80000000u) : "memory");
        }
        pb0 ^= pbx;
        s += 2;
        if (s >= NS) { s -= NS; ph ^= 1; }
    }
    const float al = ex2(m_lo - f(lds32(sb + SM_M + g * 4))), ah = ex2(m_hi - f(lds32(sb + SM_M + 32 + g * 4)));
    mma(cm, pa.x, pa.y, pa.z, pa.w, mv.x, mv.y);
#pragma unroll
    for (int i = 3; i < 6; i++) mma(acc[i], pa.x, pa.y, pa.z, pa.w, hadd2v(xt[i][0], yt[i]), hadd2v(xt[i][1], yt[i]));
    mma(cm, pb.x, pb.y, pb.z, pb.w, mv.z, mv.w);
#pragma unroll
    for (int i = 3; i < 6; i++) mma(acc[i], pb.x, pb.y, pb.z, pb.w, hadd2v(xt[i][2], yt[i]), hadd2v(xt[i][3], yt[i]));
#pragma unroll
    for (int i = 0; i < 3; i++) mma(acc[i], pa.x, pa.y, pa.z, pa.w, hadd2v(xt[i][0], yt[i]), hadd2v(xt[i][1], yt[i]));
#pragma unroll
    for (int i = 0; i < 3; i++) mma(acc[i], pb.x, pb.y, pb.z, pb.w, hadd2v(xt[i][2], yt[i]), hadd2v(xt[i][3], yt[i]));
    if (threadIdx.x == grp * 128) TSE(2 + grp);
    if (threadIdx.x == grp * 128 + 96) TSX(2 + grp, u(acc[5][0]));

    uint4* const dst = g_acc + (b & 1) * ACC + ((g >> 1) * 8 + cw + 4 * grp) * 8 + (lane & 7);
    const uint32_t xw = opaque(sb + SM_STAGES + grp * STAGE + cw * 1536 + lane * 16), xr = opaque(sb + SM_STAGES + (grp ^ 1) * STAGE + cw * 1536 + lane * 16);
    asm volatile("" ::"l"(dst));
    const float cl = -cm[0] * al, ch = -cm[2] * ah;
#pragma unroll
    for (int i = 0; i < 3; i++)
        sts128(xw + i * 512, u(fmaf(acc[3 + i][0], al, cl)), u(fmaf(acc[3 + i][1], al, cl)), u(fmaf(acc[3 + i][2], ah, ch)), u(fmaf(acc[3 + i][3], ah, ch)));
#pragma unroll
    for (int i = 0; i < 3; i++) { acc[i][0] = fmaf(acc[i][0], al, cl); acc[i][1] = fmaf(acc[i][1], al, cl); acc[i][2] = fmaf(acc[i][2], ah, ch); acc[i][3] = fmaf(acc[i][3], ah, ch); }
    const uint32_t w_lo = packh(l_lo * al, 1.f), w_hi = packh(l_hi * ah, 1.f);
    bar_sync(B_MERGE, 256);
    if (threadIdx.x == 224) TSX(4, 0);
    uint4 o[3];
#pragma unroll
    for (int i = 0; i < 3; i++) o[i] = lds128(xr + i * 512);
    red8h(dst, packh(acc[0][0] + f(o[0].x), acc[0][1] + f(o[0].y)), packh(acc[1][0] + f(o[1].x), acc[1][1] + f(o[1].y)), packh(acc[2][0] + f(o[2].x), acc[2][1] + f(o[2].y)), w_lo);
    red8h(dst + 256, packh(acc[0][2] + f(o[0].z), acc[0][3] + f(o[0].w)), packh(acc[1][2] + f(o[1].z), acc[1][3] + f(o[1].w)), packh(acc[2][2] + f(o[2].z), acc[2][3] + f(o[2].w)), w_hi);
    if (threadIdx.x == 0) TSE(4);
    if (threadIdx.x == 224) TSX(9, 0);
}

typedef CUresult (*EncodeFn)(CUtensorMap*, CUtensorMapDataType, cuuint32_t, void*, const cuuint64_t*, const cuuint64_t*,
                             const cuuint32_t*, const cuuint32_t*, CUtensorMapInterleave, CUtensorMapSwizzle,
                             CUtensorMapL2promotion, CUtensorMapFloatOOBfill);

}

extern "C" void kernel_launch(void* const* d_in, const int* in_sizes, int n_in, void* d_out, int out_size) {
    const __nv_bfloat16* q = (const __nv_bfloat16*)d_in[0];
    char* f0 = (char*)d_in[1];
    char* f1 = (char*)d_in[2];
    const __nv_bfloat16* wq = (const __nv_bfloat16*)d_in[3];
    const __nv_bfloat16* wk = (const __nv_bfloat16*)d_in[4];
    const __nv_bfloat16* wv = (const __nv_bfloat16*)d_in[5];
    const __nv_bfloat16* wo = (const __nv_bfloat16*)d_in[6];

    static EncodeFn enc = nullptr;
    static int grid = 0;
    static Scratch* scr = nullptr;
    if (!enc) {
        void* fn = nullptr; cudaDriverEntryPointQueryResult qr;
        cudaGetDriverEntryPoint("cuTensorMapEncodeTiled", &fn, cudaEnableDefault, &qr);
        enc = (EncodeFn)fn;
        cudaGetSymbolAddress((void**)&scr, g_scratch);
        int dev = 0, sms = 0;
        cudaGetDevice(&dev);
        cudaDeviceGetAttribute(&sms, cudaDevAttrMultiProcessorCount, dev);
        grid = sms < MAXG ? sms : MAXG;
        cudaFuncSetAttribute(attn_main, cudaFuncAttributeMaxDynamicSharedMemorySize, SMEM_BYTES);
    }
    CUtensorMap m0, m1;
    {
        cuuint64_t dims[5] = {64, W1, 3, 2, W0};
        cuuint64_t str[4] = {2 * C * 2, 128, C * 2, (cuuint64_t)W0 * C * 2};
        cuuint32_t box[5] = {64, TP, 3, 2, 2}, es[5] = {1, 1, 1, 1, 1};
        enc(&m0, CU_TENSOR_MAP_DATA_TYPE_BFLOAT16, 5, f0, dims, str, box, es, CU_TENSOR_MAP_INTERLEAVE_NONE,
            CU_TENSOR_MAP_SWIZZLE_128B, CU_TENSOR_MAP_L2_PROMOTION_NONE, CU_TENSOR_MAP_FLOAT_OOB_FILL_NONE);
    }
    {
        cuuint64_t dims[4] = {64, W1, 3, W1};
        cuuint64_t str[3] = {C * 2, 128, (cuuint64_t)W1 * C * 2};
        cuuint32_t box[4] = {64, TP, 3, 1}, es[4] = {1, 1, 1, 1};
        enc(&m1, CU_TENSOR_MAP_DATA_TYPE_BFLOAT16, 4, f1, dims, str, box, es, CU_TENSOR_MAP_INTERLEAVE_NONE,
            CU_TENSOR_MAP_SWIZZLE_128B, CU_TENSOR_MAP_L2_PROMOTION_NONE, CU_TENSOR_MAP_FLOAT_OOB_FILL_NONE);
    }
    attn_main<<<grid, NTHREADS, SMEM_BYTES, cudaStreamPerThread>>>(f0, f1, q, wq, wk, scr, wv, wo, (__nv_bfloat16*)d_out, m0, m1);
}
```

```cpp
#include <cuda_runtime.h>
#include <cuda_bf16.h>
#include <cuda.h>
#include <stdint.h>

namespace {

constexpr int C = 192;
constexpr int NQ = 16;
constexpr int W0 = 512;
constexpr int W1 = 256;
constexpr int TP = 8;
constexpr int NT = W1 * W1 / TP;
constexpr int STAGE = TP * 5 * C * 2;
#define NS 14
#define D0 3
#define D1 2
#define D2 1
#define NRAMP 5
#define TAILT 150
#define QSLEEP 700
#define WSL 24
#define MAXT 3000
#define REFT 1800
#define POLLN 1
#define PGAP 110
#define LAZY 12.f
#define GR4 1
#define NST 4
#define NI 1
#define NPACE 5
#define T0 0
#define T1 1600
#define TG 960
static_assert(NST > D0, "the first dynamic tile index must not delay the start");
constexpr int NTHREADS = 384;
constexpr int MAXG = 132;
constexpr int NRD = NQ;
constexpr int ACC = NQ * 32;
constexpr int NSRC = 12;
constexpr int SPIN_LIMIT = 1 << 22;

constexpr int SM_STAGES = 0;
constexpr int SM_P = NS * STAGE;
constexpr int PBUF = 1088;
constexpr int SM_QK = SM_P + 4 * PBUF;
constexpr int SM_MX = SM_QK + 6144;
constexpr int SM_M = SM_MX + 512;
constexpr int SM_BAR = SM_M + 64;
constexpr int SM_REF = SM_BAR + 16 * NS;
constexpr int SM_FLAG = SM_REF + 8;
constexpr int SM_TOTAL = SM_FLAG + 4 * NS;
constexpr int SMEM_BYTES = SM_TOTAL + 1024;
static_assert(SMEM_BYTES <= 232448, "smem");
constexpr int WROW = 400;
constexpr int RD_W = 0;
constexpr int RD_QN = 2 * C * WROW;
constexpr int RD_KQ = RD_QN + 6144;
constexpr int RD_B = RD_KQ + 7168;
constexpr int RD_RDY = RD_B + 32 * 144 + 256;
constexpr int RD_BAR = RD_RDY + 16;
static_assert(RD_BAR + 64 <= SM_TOTAL, "smem");

struct Scratch {
    uint4 acc[2 * ACC];
    uint4 qk[NSRC * 32];
    unsigned ctr[32];
    unsigned mmax[32];
    unsigned mref[32];
};
__device__ __align__(128) Scratch g_scratch;
#define g_acc (scr->acc)
#define g_qk (scr->qk)
#define g_ctr (scr->ctr)
#define g_mmax (scr->mmax)
#define g_mref (scr->mref)
#define g_ts (scr->ts)
#define g_tr (scr->tr)
#define TR(k, i) do {} while (0)
#define TS(i) do {} while (0)
#define TSD(i, dep) do {} while (0)
#define TSX(i, dep) do {} while (0)
#define TSP(i, dep) do {} while (0)
#define TSE(i) TS(i)
#define CK_(i, dep) do {} while (0)
#define PH(i, dep) do {} while (0)

__device__ __forceinline__ uint32_t s2u(const void* p) { return (uint32_t)__cvta_generic_to_shared(p); }
__device__ __forceinline__ void mbar_init(uint32_t a, int c) { asm volatile("mbarrier.init.shared::cta.b64 [%0], %1;" ::"r"(a), "r"(c) : "memory"); }
__device__ __forceinline__ void mbar_expect(uint32_t a, uint32_t b) { asm volatile("mbarrier.arrive.expect_tx.shared::cta.b64 _, [%0], %1;" ::"r"(a), "r"(b) : "memory"); }
__device__ __forceinline__ void mbar_arrive(uint32_t a) { asm volatile("mbarrier.arrive.shared::cta.b64 _, [%0];" ::"r"(a) : "memory"); }
__device__ __forceinline__ void mbar_wait(uint32_t a, uint32_t ph) {
    uint32_t ok; int it = 0;
    do {
        asm volatile("{.reg .pred p; mbarrier.try_wait.parity.shared::cta.b64 p, [%1], %2; selp.u32 %0,1,0,p;}" : "=r"(ok) : "r"(a), "r"(ph) : "memory");
        if (++it > SPIN_LIMIT) __trap();
    } while (!ok);
}
__device__ __forceinline__ bool elect() {
    uint32_t r; asm volatile("{.reg .pred p; elect.sync _|p, 0xffffffff; selp.u32 %0, 1, 0, p;}" : "=r"(r)); return r;
}
__device__ __forceinline__ void bar_sync(int id, int n) { asm volatile("bar.sync %0, %1;" ::"r"(id), "r"(n) : "memory"); }
__device__ __forceinline__ bool bar_any(int id, int n, bool c) {
    uint32_t r;
    asm volatile("{.reg .pred p, q; setp.ne.u32 q, %3, 0; bar.red.or.pred p, %1, %2, q; selp.u32 %0, 1, 0, p;}" : "=r"(r) : "r"(id), "r"(n), "r"((uint32_t)c) : "memory");
    return r;
}
__device__ __forceinline__ void bar_arrive(int id, int n) { asm volatile("bar.arrive %0, %1;" ::"r"(id), "r"(n) : "memory"); }
__device__ __forceinline__ void ldsm4(uint32_t* r, uint32_t a) {
    asm volatile("ldmatrix.sync.aligned.m8n8.x4.shared.b16 {%0,%1,%2,%3}, [%4];" : "=r"(r[0]), "=r"(r[1]), "=r"(r[2]), "=r"(r[3]) : "r"(a) : "memory");
}
__device__ __forceinline__ void ldsm4t(uint32_t* r, uint32_t a) {
    asm volatile("ldmatrix.sync.aligned.m8n8.x4.trans.shared.b16 {%0,%1,%2,%3}, [%4];" : "=r"(r[0]), "=r"(r[1]), "=r"(r[2]), "=r"(r[3]) : "r"(a) : "memory");
}
__device__ __forceinline__ void ldsm2t(uint32_t* r, uint32_t a) {
    asm volatile("ldmatrix.sync.aligned.m8n8.x2.trans.shared.b16 {%0,%1}, [%2];" : "=r"(r[0]), "=r"(r[1]) : "r"(a) : "memory");
}
__device__ __forceinline__ void mma(float* d, uint32_t a0, uint32_t a1, uint32_t a2, uint32_t a3, uint32_t b0, uint32_t b1) {
    asm("mma.sync.aligned.m16n8k16.row.col.f32.bf16.bf16.f32 {%0,%1,%2,%3}, {%4,%5,%6,%7}, {%8,%9}, {%0,%1,%2,%3};"
        : "+f"(d[0]), "+f"(d[1]), "+f"(d[2]), "+f"(d[3]) : "r"(a0), "r"(a1), "r"(a2), "r"(a3), "r"(b0), "r"(b1));
}
__device__ __forceinline__ void mmah(float* d, uint32_t a0, uint32_t a1, uint32_t a2, uint32_t a3, uint32_t b0, uint32_t b1) {
    asm("mma.sync.aligned.m16n8k16.row.col.f32.f16.f16.f32 {%0,%1,%2,%3}, {%4,%5,%6,%7}, {%8,%9}, {%0,%1,%2,%3};"
        : "+f"(d[0]), "+f"(d[1]), "+f"(d[2]), "+f"(d[3]) : "r"(a0), "r"(a1), "r"(a2), "r"(a3), "r"(b0), "r"(b1));
}
__device__ __forceinline__ void mma8(float* d, uint32_t a0, uint32_t a1, uint32_t b0) {
    asm("mma.sync.aligned.m16n8k8.row.col.f32.bf16.bf16.f32 {%0,%1,%2,%3}, {%4,%5}, {%6}, {%0,%1,%2,%3};"
        : "+f"(d[0]), "+f"(d[1]), "+f"(d[2]), "+f"(d[3]) : "r"(a0), "r"(a1), "r"(b0));
}
__device__ __forceinline__ uint32_t hadd2(uint32_t a, uint32_t b) {
    uint32_t r; asm("add.rn.bf16x2 %0, %1, %2;" : "=r"(r) : "r"(a), "r"(b)); return r;
}
__device__ __forceinline__ uint32_t pack2(float lo, float hi) {
    uint32_t r; asm("cvt.rn.bf16x2.f32 %0, %1, %2;" : "=r"(r) : "f"(hi), "f"(lo)); return r;
}
__device__ __forceinline__ uint32_t packh(float lo, float hi) {
    uint32_t r; asm("cvt.rn.f16x2.f32 %0, %1, %2;" : "=r"(r) : "f"(hi), "f"(lo)); return r;
}
__device__ __forceinline__ float2 unpackh(uint32_t v) {
    float2 r; asm("{.reg .b16 l, h; mov.b32 {l, h}, %2; cvt.f32.f16 %0, l; cvt.f32.f16 %1, h;}" : "=f"(r.x), "=f"(r.y) : "r"(v)); return r;
}
__device__ __forceinline__ float bflo(uint32_t v) { return __uint_as_float(v << 16); }
__device__ __forceinline__ float bfhi(uint32_t v) { return __uint_as_float(v & 0xffff0000u); }
__device__ __forceinline__ float ex2(float x) { float r; asm("ex2.approx.ftz.f32 %0, %1;" : "=f"(r) : "f"(x)); return r; }
__device__ __forceinline__ void sts128(uint32_t a, uint32_t x, uint32_t y, uint32_t z, uint32_t w) {
    asm volatile("st.shared.v4.b32 [%0], {%1,%2,%3,%4};" ::"r"(a), "r"(x), "r"(y), "r"(z), "r"(w) : "memory");
}
__device__ __forceinline__ void sts64(uint32_t a, uint32_t x, uint32_t y) {
    asm volatile("st.shared.v2.b32 [%0], {%1,%2};" ::"r"(a), "r"(x), "r"(y) : "memory");
}
__device__ __forceinline__ void sts32(uint32_t a, uint32_t x) { asm volatile("st.shared.b32 [%0], %1;" ::"r"(a), "r"(x) : "memory"); }
__device__ __forceinline__ uint4 lds128(uint32_t a) {
    uint4 v; asm volatile("ld.shared.v4.b32 {%0,%1,%2,%3}, [%4];" : "=r"(v.x), "=r"(v.y), "=r"(v.z), "=r"(v.w) : "r"(a) : "memory"); return v;
}
__device__ __forceinline__ uint32_t lds32(uint32_t a) { uint32_t v; asm volatile("ld.shared.b32 %0, [%1];" : "=r"(v) : "r"(a) : "memory"); return v; }
__device__ __forceinline__ int grab_tile(unsigned* ctr) {
    int v; asm volatile("atom.relaxed.gpu.global.inc.u32 %0, [%1], 0x7fffffff;" : "=r"(v) : "l"(ctr) : "memory"); return v;
}
__device__ __forceinline__ uint32_t opaque(uint32_t v) { uint32_t r; asm volatile("mov.b32 %0, %1;" : "=r"(r) : "r"(v)); return r; }
__device__ __forceinline__ unsigned clock32() { unsigned c; asm volatile("mov.u32 %0, %%clock;" : "=r"(c)); return c; }
__device__ __forceinline__ float rsq(float x) { float r; asm("rsqrt.approx.ftz.f32 %0, %1;" : "=f"(r) : "f"(x)); return r; }
__device__ __forceinline__ float rcp(float x) { float r; asm("rcp.approx.ftz.f32 %0, %1;" : "=f"(r) : "f"(x)); return r; }
__device__ __forceinline__ float lg2(float x) { float r; asm("lg2.approx.ftz.f32 %0, %1;" : "=f"(r) : "f"(x)); return r; }
__device__ __forceinline__ float f(uint32_t v) { return __uint_as_float(v); }
__device__ __forceinline__ uint32_t u(float v) { return __float_as_uint(v); }

constexpr uint32_t ONES = 0x3F803F80u;
constexpr float QSCALE = 0.07216878364870322f * 1.4426950408889634f;

__device__ __forceinline__ void issue_tile(const CUtensorMap* m0, const CUtensorMap* m1, uint32_t sb, int s, int tl, uint64_t pol) {
    const uint32_t full = sb + SM_BAR + s * 8, dst = sb + SM_STAGES + s * STAGE;
    const int par = tl * TP, y = par >> 8, x = par & 255;
    mbar_expect(full, STAGE);
    asm volatile("cp.async.bulk.tensor.5d.shared::cluster.global.mbarrier::complete_tx::bytes.L2::cache_hint [%0], [%1, {%3,%4,%3,%3,%5}], [%2], %6;"
                 ::"r"(dst), "l"(m0), "r"(full), "r"(0), "r"(x), "r"(2 * y), "l"(pol) : "memory");
    asm volatile("cp.async.bulk.tensor.4d.shared::cluster.global.mbarrier::complete_tx::bytes.L2::cache_hint [%0], [%1, {%3,%4,%3,%5}], [%2], %6;"
                 ::"r"(dst + TP * 4 * C * 2), "l"(m1), "r"(full), "r"(0), "r"(x), "r"(y), "l"(pol) : "memory");
}

__device__ __forceinline__ void prefetch_l2(const void* a, int n) { asm volatile("cp.async.bulk.prefetch.L2.global [%0], %1;" ::"l"(a), "r"(n) : "memory"); }
__device__ __forceinline__ uint4 ldg_relaxed(const uint4* p) {
    uint4 v; asm volatile("ld.relaxed.gpu.global.v4.u32 {%0,%1,%2,%3}, [%4];" : "=r"(v.x), "=r"(v.y), "=r"(v.z), "=r"(v.w) : "l"(p) : "memory"); return v;
}
__device__ __forceinline__ uint32_t ldg_relaxed32(const void* p) {
    uint32_t v; asm volatile("ld.relaxed.gpu.global.u32 %0, [%1];" : "=r"(v) : "l"(p) : "memory"); return v;
}
__device__ __forceinline__ void stg_relaxed(uint4* p, uint32_t x, uint32_t y, uint32_t z, uint32_t w) {
    asm volatile("st.relaxed.gpu.global.v4.u32 [%0], {%1,%2,%3,%4};" ::"l"(p), "r"(x), "r"(y), "r"(z), "r"(w) : "memory");
}
__device__ __forceinline__ void stg_relaxed32(void* p, uint32_t x) { asm volatile("st.relaxed.gpu.global.u32 [%0], %1;" ::"l"(p), "r"(x) : "memory"); }
__device__ __forceinline__ bool has(const uint4& v, uint32_t m) { return v.x == m || v.y == m || v.z == m || v.w == m; }
__device__ __forceinline__ uint32_t hadd2v(uint32_t a, uint32_t b) {
    uint32_t r; asm volatile("add.rn.bf16x2 %0, %1, %2;" : "=r"(r) : "r"(a), "r"(b)); return r;
}

__device__ __forceinline__ void red8h(uint4* p, uint32_t x, uint32_t y, uint32_t z, uint32_t w) {
    asm volatile("red.relaxed.gpu.global.add.noftz.v4.f16x2 [%0], {%1,%2,%3,%4};" ::"l"(p), "r"(x), "r"(y), "r"(z), "r"(w) : "memory");
}
__device__ __forceinline__ uint2 lds64v(uint32_t a) {
    uint2 v; asm volatile("ld.volatile.shared.v2.b32 {%0,%1}, [%2];" : "=r"(v.x), "=r"(v.y) : "r"(a) : "memory"); return v;
}
__device__ __forceinline__ uint4 lds128v(uint32_t a) {
    uint4 v; asm volatile("ld.volatile.shared.v4.b32 {%0,%1,%2,%3}, [%4];" : "=r"(v.x), "=r"(v.y), "=r"(v.z), "=r"(v.w) : "r"(a) : "memory"); return v;
}
__device__ __forceinline__ uint32_t brow(int r) { return RD_B + r * 144 + (r >> 3) * 64; }

enum { B_QK = 1, B_QN = 2, B_GRP = 3  , B_Q = 5, B_MERGE = 6, B_ALL = 7, B_MAX = 8  , B_WARP = 10, B_POLL = 11, B_SLOW = 12 };

__device__ __noinline__ void slow_rows(const char* __restrict__ f0, const char* __restrict__ f1, const __nv_bfloat16* __restrict__ q,
                                       const __nv_bfloat16* __restrict__ wq, const __nv_bfloat16* __restrict__ wk, const uint32_t sb)
{
    const int warp = threadIdx.x >> 5, lane = threadIdx.x & 31;
    float* const sm = reinterpret_cast<float*>(__cvta_shared_to_generic(sb + RD_W));
    bar_sync(B_POLL, 352);
    for (int i = threadIdx.x; i < 4 * C; i += 96) sm[i] = __bfloat162float(q[(blockIdx.x & 12) * C + i]);
    bar_sync(B_SLOW, 96);
#pragma unroll 1
    for (int j = threadIdx.x; j < 4 * C; j += 96) {
        const float* const x = sm + j / C * C;
        float mu = 0.f, var = 0.f, s = 0.f;
#pragma unroll 1
        for (int i = 0; i < C; i++) mu += x[i];
        mu *= 1.f / C;
#pragma unroll 4
        for (int i = 0; i < C; i++) { var = fmaf(x[i] - mu, x[i] - mu, var); s = fmaf(x[i] - mu, __bfloat162float(wq[i * C + j % C]), s); }
        sm[4 * C + j] = s * rsq(var * (1.f / C) + 1e-5f);
    }
    bar_sync(B_SLOW, 96);
#pragma unroll 1
    for (int j = threadIdx.x; j < 4 * C; j += 96) {
        float s = 0.f;
#pragma unroll 4
        for (int i = 0; i < C; i++) s = fmaf(sm[4 * C + j / C * C + i], __bfloat162float(wk[j % C * C + i]), s);
        sm[j] = s * QSCALE;
    }
    bar_sync(B_SLOW, 96);
    float k[4][6], a[4][6], m[4], l[4];
#pragma unroll
    for (int r = 0; r < 4; r++) {
        m[r] = -INFINITY; l[r] = 0.f;
#pragma unroll
        for (int i = 0; i < 6; i++) { k[r][i] = sm[r * C + 64 * (i >> 1) + 2 * lane + (i & 1)]; a[r][i] = 0.f; }
    }
#pragma unroll 1
    for (int par = warp; par < W1 * W1; par += 3) {
        const uint32_t* p0 = reinterpret_cast<const uint32_t*>(f0 + (size_t)((par >> 8) * 2 * W0 + (par & 255) * 2) * (C * 2)) + lane;
        const uint32_t* p1 = reinterpret_cast<const uint32_t*>(f1 + (size_t)par * (C * 2)) + lane;
        uint32_t v[4][3];
#pragma unroll
        for (int i = 0; i < 3; i++)
#pragma unroll
            for (int j = 0; j < 4; j++) v[j][i] = hadd2(__ldg(p0 + ((j >> 1) * W0 + (j & 1)) * (C / 2) + 32 * i), __ldg(p1 + 32 * i));
#pragma unroll
        for (int j = 0; j < 4; j++) {
            float x[6], s1 = 0.f, s2 = 0.f, d[4] = {0.f, 0.f, 0.f, 0.f};
#pragma unroll
            for (int i = 0; i < 3; i++) { x[2 * i] = bflo(v[j][i]); x[2 * i + 1] = bfhi(v[j][i]); s1 += x[2 * i] + x[2 * i + 1]; }
#pragma unroll
            for (int o = 1; o < 32; o <<= 1) s1 += __shfl_xor_sync(~0u, s1, o);
#pragma unroll
            for (int i = 0; i < 6; i++) {
                x[i] -= s1 * (1.f / C); s2 = fmaf(x[i], x[i], s2);
#pragma unroll
                for (int r = 0; r < 4; r++) d[r] = fmaf(x[i], k[r][i], d[r]);
            }
#pragma unroll
            for (int o = 1; o < 32; o <<= 1) {
                s2 += __shfl_xor_sync(~0u, s2, o);
#pragma unroll
                for (int r = 0; r < 4; r++) d[r] += __shfl_xor_sync(~0u, d[r], o);
            }
            const float rs = rsq(s2 * (1.f / C) + 1e-5f);
#pragma unroll
            for (int r = 0; r < 4; r++) {
                const float nm = fmaxf(m[r], d[r] * rs), al = ex2(m[r] - nm), p = ex2(d[r] * rs - nm);
                m[r] = nm; l[r] = fmaf(l[r], al, p);
#pragma unroll
                for (int i = 0; i < 6; i++) a[r][i] = fmaf(a[r][i], al, x[i] * (p * rs));
            }
        }
    }
    bar_sync(B_SLOW, 96);
#pragma unroll
    for (int r = 0; r < 4; r++) {
        float* const o = sm + ((r * 3 + warp) * 32 + lane) * 8;
#pragma unroll
        for (int i = 0; i < 6; i++) o[i] = a[r][i];
        o[6] = l[r]; o[7] = m[r];
    }
    bar_sync(B_SLOW, 96);
#pragma unroll 1
    for (int r = warp; r < 4; r += 3) {
        const float* const o = sm + (r * 96 + lane) * 8;
        const float M = fmaxf(fmaxf(o[7], o[256 + 7]), o[512 + 7]), e0 = ex2(o[7] - M), e1 = ex2(o[256 + 7] - M), e2 = ex2(o[512 + 7] - M);
        float x[7];
#pragma unroll
        for (int i = 0; i < 7; i++) x[i] = o[i] * e0 + o[256 + i] * e1 + o[512 + i] * e2;
        uint32_t hi[3], lo[3];
        const float rl = 1.f / x[6];
#pragma unroll
        for (int i = 0; i < 3; i++) {
            hi[i] = packh(x[2 * i] * rl, x[2 * i + 1] * rl);
            const float2 h = unpackh(hi[i]);
            lo[i] = packh(fmaf(x[2 * i], rl, -h.x), fmaf(x[2 * i + 1], rl, -h.y));
        }
        const uint32_t bw = sb + brow(8 * r + (lane & 3)) + (lane >> 2) * 16;
        sts128(bw, hi[0], hi[1], hi[2], lane ? 0u : 0x3C00u);
        sts128(bw + 4 * 144, lo[0], lo[1], lo[2], 0);
    }
    bar_sync(B_SLOW, 96);
}

__device__ __forceinline__ void reducer(const char* __restrict__ f0, const char* __restrict__ f1, const __nv_bfloat16* __restrict__ q, const __nv_bfloat16* __restrict__ wq, const __nv_bfloat16* __restrict__ wk,
                                        Scratch* scr, const __nv_bfloat16* __restrict__ wv, const __nv_bfloat16* __restrict__ wo,
                                        __nv_bfloat16* __restrict__ out, const uint32_t sb, const int GS)
{
    const int warp = threadIdx.x >> 5, lane = threadIdx.x & 31, b = blockIdx.x;
    const int g = lane >> 2, t = lane & 3;
    if (threadIdx.x == 256) TS(0);
    if (b < NSRC && warp < 8) {
        const uint32_t wqs = sb + RD_W, wbar = sb + RD_BAR;
        const int hr = lane >> 4, qt = (lane >> 2) & 3, sub = lane & 3;
        const uint32_t* qp = reinterpret_cast<const uint32_t*>(q + (warp + 8 * hr) * C + 48 * qt + 6 * sub);
        uint32_t qw[6];
#pragma unroll
        for (int j = 0; j < 3; j++) { qw[j] = __ldg(qp + j); qw[3 + j] = __ldg(qp + 12 + j); }
        if (lane == 0) { mbar_init(wbar + warp * 8, 1); asm volatile("fence.mbarrier_init.release.cluster;" ::: "memory"); mbar_expect(wbar + warp * 8, 9216);
            asm volatile("cp.async.bulk.shared::cluster.global.mbarrier::complete_tx::bytes [%0], [%1], 9216, [%2];"
                         ::"r"(wqs + warp * 9232), "l"(wq + 24 * warp * C), "r"(wbar + warp * 8) : "memory");
        }
        __syncwarp();
        if (threadIdx.x == 0) TSP(2, 0);
        float e[12];
#pragma unroll
        for (int j = 0; j < 6; j++) { e[2 * j] = bflo(qw[j]); e[2 * j + 1] = bfhi(qw[j]); }
        float sm = ((e[0] + e[1]) + (e[2] + e[3])) + ((e[4] + e[5]) + (e[6] + e[7])) + ((e[8] + e[9]) + (e[10] + e[11]));
#pragma unroll
        for (int o = 1; o < 16; o <<= 1) sm += __shfl_xor_sync(~0u, sm, o);
        if (threadIdx.x == 0) TSP(5, u(sm));
        float v0 = 0.f, v1 = 0.f;
#pragma unroll
        for (int j = 0; j < 12; j++) e[j] -= sm * (1.f / C);
#pragma unroll
        for (int j = 0; j < 6; j++) { v0 = fmaf(e[j], e[j], v0); v1 = fmaf(e[6 + j], e[6 + j], v1); }
        v0 += v1;
#pragma unroll
        for (int o = 1; o < 16; o <<= 1) v0 += __shfl_xor_sync(~0u, v0, o);
        const float rq = rsq(v0 * (1.f / C) + 1e-5f);
#pragma unroll
        for (int j = 0; j < 6; j++)
            sts32(sb + RD_QN + (3 * sub + (j >> 1)) * 512 + (4 * warp + qt) * 16 + (2 * (j & 1) + hr) * 4, pack2(e[j] * rq, e[6 + j] * rq));
        if (threadIdx.x == 0) TSP(8, 0);
        uint32_t wkf[2][3];
#pragma unroll
        for (int i = 0; i < 2; i++)
#pragma unroll
            for (int j = 0; j < 3; j++) wkf[i][j] = __ldg(reinterpret_cast<const uint32_t*>(wk + (16 * b + 8 * i + g) * C + 24 * warp + 8 * j + 2 * t));
        bar_sync(B_QN, 256);
        float acc[2][3][4];
#pragma unroll
        for (int i = 0; i < 3; i++)
#pragma unroll
            for (int e = 0; e < 4; e++) acc[0][i][e] = acc[1][i][e] = 0.f;
        const uint32_t ba = wqs + (lane & 7) * 9232 + (lane >> 3) * 384 + 48 * warp;
        uint4 a[12];
#pragma unroll
        for (int kk = 0; kk < 12; kk++) a[kk] = lds128(sb + RD_QN + kk * 512 + lane * 16);
        mbar_wait(wbar + (lane & 7) * 8, 0);
        __syncwarp();
        if (threadIdx.x == 0) TSP(4, 0);
#pragma unroll
        for (int kp = 0; kp < 6; kp++)
#pragma unroll
            for (int i = 0; i < 3; i++) {
                uint32_t bb[4];
                ldsm4t(bb, ba + kp * 1536 + i * 16);
                mma(acc[0][i], a[2 * kp].x, a[2 * kp].y, a[2 * kp].z, a[2 * kp].w, bb[0], bb[1]);
                mma(acc[1][i], a[2 * kp + 1].x, a[2 * kp + 1].y, a[2 * kp + 1].z, a[2 * kp + 1].w, bb[2], bb[3]);
            }
        if (threadIdx.x == 0) TSP(7, u(acc[1][2][3]));
        float kq[2][4] = {{0.f, 0.f, 0.f, 0.f}, {0.f, 0.f, 0.f, 0.f}};
#pragma unroll
        for (int j = 0; j < 3; j++) {
            const uint32_t a0 = pack2(acc[0][j][0] + acc[1][j][0], acc[0][j][1] + acc[1][j][1]), a1 = pack2(acc[0][j][2] + acc[1][j][2], acc[0][j][3] + acc[1][j][3]);
            mma8(kq[0], a0, a1, wkf[0][j]);
            mma8(kq[1], a0, a1, wkf[1][j]);
        }
        if (warp < 7) {
            sts128(sb + RD_KQ + warp * 1024 + lane * 16, u(kq[0][0]), u(kq[0][1]), u(kq[0][2]), u(kq[0][3]));
            sts128(sb + RD_KQ + warp * 1024 + 512 + lane * 16, u(kq[1][0]), u(kq[1][1]), u(kq[1][2]), u(kq[1][3]));
            bar_arrive(B_Q, 256);
        } else {
            bar_sync(B_Q, 256);
#pragma unroll
            for (int w = 0; w < 7; w++)
#pragma unroll
                for (int i = 0; i < 2; i++) {
                    const uint4 o = lds128(sb + RD_KQ + w * 1024 + i * 512 + lane * 16);
                    kq[i][0] += f(o.x); kq[i][1] += f(o.y); kq[i][2] += f(o.z); kq[i][3] += f(o.w);
                }
            stg_relaxed(g_qk + b * 32 + lane, ~pack2(kq[0][0] * QSCALE, kq[0][1] * QSCALE), ~pack2(kq[0][2] * QSCALE, kq[0][3] * QSCALE),
                        ~pack2(kq[1][0] * QSCALE, kq[1][1] * QSCALE), ~pack2(kq[1][2] * QSCALE, kq[1][3] * QSCALE));
            if (lane == 0) TS(10);
        }
    } else if (b >= NSRC) {
        if (b == NSRC && warp == 0) stg_relaxed32(g_mmax + lane, 0);
        __nanosleep(2500);
    }
    bar_sync(B_ALL, NTHREADS);

#pragma unroll 1
    for (int r = 0; r < 3; r++) {
        uint4 v[8];
#pragma unroll
        for (int k = 0; k < 8; k++) {
            const int idx = (8 * r + k) * 384 + threadIdx.x;
            v[k] = __ldg(reinterpret_cast<const uint4*>(idx < 4608 ? wv : wo - C * C) + idx);
        }
#pragma unroll
        for (int k = 0; k < 8; k++) {
            const int idx = (8 * r + k) * 384 + threadIdx.x, row = idx / 24;
            sts128(sb + RD_W + row * WROW + (idx - 24 * row) * 16, v[k].x, v[k].y, v[k].z, v[k].w);
        }
    }
    if (threadIdx.x < 256) {
        stg_relaxed(g_acc + (threadIdx.x >> 7) * ACC + (b >> 2) * 128 + (threadIdx.x & 127), 0, 0, 0, 0);
        __threadfence();
    }
    if (threadIdx.x == 0) sts128(sb + RD_RDY, 0, 0, 0, 0);
    bar_sync(B_ALL, NTHREADS);
    uint32_t wa[12][4];
    float ws0 = 0.f, ws1 = 0.f, qv0 = 0.f, qv1 = 0.f;
    __nv_bfloat16* op = out;
    if (warp < 3) {
        const int col = 48 * (b & 3) + 16 * warp;
        float d[24][4];
#pragma unroll
        for (int i = 0; i < 24; i++) d[i][0] = d[i][1] = d[i][2] = d[i][3] = 0.f;
        const int mi = lane >> 3, r = lane & 7;
        const uint32_t aa = sb + RD_W + (C + (mi >> 1) * 8 + r) * WROW + (col + (mi & 1) * 8) * 2;
        const uint32_t ba = sb + RD_W + ((mi >> 1) * 8 + r) * WROW + (mi & 1) * 16;
#pragma unroll 1
        for (int kk = 0; kk < 12; kk++) {
            uint32_t a[4];
            ldsm4t(a, aa + kk * 16 * WROW);
#pragma unroll
            for (int i = 0; i < 12; i++) {
                uint32_t bb[4];
                ldsm4(bb, ba + i * 16 * WROW + kk * 32);
                mma(d[2 * i], a[0], a[1], a[2], a[3], bb[0], bb[1]);
                mma(d[2 * i + 1], a[0], a[1], a[2], a[3], bb[2], bb[3]);
            }
        }
        float c0 = 0.f, c1 = 0.f, m0 = 0.f, m1 = 0.f;
#pragma unroll
        for (int i = 0; i < 24; i++) { c0 += d[i][0] + d[i][1]; c1 += d[i][2] + d[i][3]; }
        c0 += __shfl_xor_sync(~0u, c0, 1); c1 += __shfl_xor_sync(~0u, c1, 1);
        c0 += __shfl_xor_sync(~0u, c0, 2); c1 += __shfl_xor_sync(~0u, c1, 2);
        c0 *= 1.f / C; c1 *= 1.f / C;
#pragma unroll
        for (int i = 0; i < 24; i++) {
            d[i][0] -= c0; d[i][1] -= c0; d[i][2] -= c1; d[i][3] -= c1;
            m0 = fmaxf(m0, fmaxf(fabsf(d[i][0]), fabsf(d[i][1]))); m1 = fmaxf(m1, fmaxf(fabsf(d[i][2]), fabsf(d[i][3])));
        }
        m0 = fmaxf(m0, __shfl_xor_sync(~0u, m0, 1)); m1 = fmaxf(m1, __shfl_xor_sync(~0u, m1, 1));
        m0 = fmaxf(m0, __shfl_xor_sync(~0u, m0, 2)); m1 = fmaxf(m1, __shfl_xor_sync(~0u, m1, 2));
        const uint32_t e0 = min(max(u(m0) >> 23, 12u), 254u), e1 = min(max(u(m1) >> 23, 12u), 254u);
        const float s0 = f((265u - e0) << 23), s1 = f((265u - e1) << 23);
        const bool k0 = fabsf(c0) < INFINITY, k1 = fabsf(c1) < INFINITY;
        ws0 = k0 ? f((e0 - 11u) << 23) : c0; ws1 = k1 ? f((e1 - 11u) << 23) : c1;
#pragma unroll
        for (int i = 0; i < 24; i++) {
            const int kk = i < 16 ? i & 7 : i >> 1, hf = i < 16 ? i >> 3 : i & 1;
            wa[kk][2 * hf] = k0 ? packh(d[i][0] * s0, d[i][1] * s0) : 0u;
            wa[kk][2 * hf + 1] = k1 ? packh(d[i][2] * s1, d[i][3] * s1) : 0u;
        }
        const int o = ((b & 12) + t) * C + col + g;
        qv0 = __bfloat162float(q[o]); qv1 = __bfloat162float(q[o + 8]);
        op = out + o;
        asm volatile("" : "+l"(op));
        if (threadIdx.x == 0) TSE(6);
    } else if (warp == 3) {
        if (lane == 0) {
            uint32_t m;
            for (int it = 0;; it++) {
                const int left = NT - 2 * NST * GS - (int)ldg_relaxed32(g_ctr);
                m = ldg_relaxed32(g_mmax + b);
                if (left <= REFT && m) break;
                if (left <= 0) { m = 0x80000000u; break; }
                if (it > SPIN_LIMIT) __trap();
                __nanosleep(300);
            }
            asm volatile("st.release.gpu.global.u32 [%0], %1;" ::"l"(g_mref + b), "r"(~u(f(m >> 31 ? m ^ 0x80000000u : ~m) + 8.f)) : "memory");
            TSE(7);
        }
        return;
    } else {
        const int pr = warp & 1;
        const uint4* const pa = g_acc + ((b >> 2) * 2 + pr) * 64 + lane;
        const uint32_t bw = opaque(sb + brow(16 * pr + 8 * ((lane >> 2) & 1) + t) + (lane >> 3) * 16);
        const uint32_t fw = opaque(sb + RD_RDY + pr * 4);
        const uint32_t n0 = packh(0.f, (float)((GS + 1) >> 1)), n1 = packh(0.f, (float)(GS >> 1)), nstart = packh(0.f, (float)POLLN);
        for (int it = 0; ldg_relaxed32(reinterpret_cast<const uint32_t*>(pa - lane) + 3) < nstart; it++)
            if (it > SPIN_LIMIT) __trap();
        for (const unsigned c = clock32(); clock32() - c < ((warp - 4) >> 1) * PGAP;) {}
        for (int it = 0;; it++) {
            const uint4 a0 = ldg_relaxed(pa), a1 = ldg_relaxed(pa + ACC), b0 = ldg_relaxed(pa + 32), b1 = ldg_relaxed(pa + ACC + 32);
            bar_sync(B_WARP, 32);
            const bool ok = a0.w >= n0 && a1.w >= n1 && b0.w >= n0 && b1.w >= n1, all = __all_sync(~0u, ok);
            const uint32_t w = ok ? bw : bw - (RD_B - RD_QN);
            sts128(w, a0.x, a0.y, a0.z, a0.w); sts128(w + 4 * 144, a1.x, a1.y, a1.z, a1.w);
            sts128(w + 64, b0.x, b0.y, b0.z, b0.w); sts128(w + 4 * 144 + 64, b1.x, b1.y, b1.z, b1.w);
            sts32(all ? fw : fw + 8, 1);
            if (all) break;
            if (it > SPIN_LIMIT) __trap();
        }
        bar_arrive(B_POLL, 352);
        if (warp == 4) {
            if (b < NSRC) g_qk[b * 32 + lane] = make_uint4(0, 0, 0, 0);
            if (lane == 0) { g_mref[b] = 0; if (b == NSRC) g_ctr[0] = 0; }
        }
        return;
    }
    const uint32_t br = opaque(sb + brow(lane));
#pragma unroll 1
    for (uint32_t pass = 0;; pass = 1) {
        uint4 x[8];
        float o[5][4];
        for (int it = 0;; it++) {
            const uint2 rdy = lds64v(sb + RD_RDY);
            x[0] = lds128v(br); x[1] = lds128v(br + 16);
            if (it > 64 * SPIN_LIMIT) __trap();
            if (rdy.x & rdy.y) break;
        }
        if (threadIdx.x == 0) TSX(8, 0);
#pragma unroll
        for (int j = 2; j < 8; j++) x[j] = lds128v(br + j * 16);
#pragma unroll
        for (int j = 0; j < 5; j++) o[j][0] = o[j][1] = o[j][2] = o[j][3] = 0.f;
#pragma unroll
        for (int i = 0; i < 4; i++) {
            mmah(o[3 + (i & 1)], 0x3C00u, 0x3C00u, 0x3C00u, 0x3C00u, x[2 * i].w, x[2 * i + 1].w);
            mmah(o[0], wa[2 * i][0], wa[2 * i][1], wa[2 * i][2], wa[2 * i][3], x[2 * i].x, x[2 * i].y);
            mmah(o[1], wa[2 * i + 1][0], wa[2 * i + 1][1], wa[2 * i + 1][2], wa[2 * i + 1][3], x[2 * i + 1].x, x[2 * i + 1].y);
            mmah(o[2], wa[8 + i][0], wa[8 + i][1], wa[8 + i][2], wa[8 + i][3], x[2 * i].z, x[2 * i + 1].z);
        }
        const float L = (o[3][0] + o[3][1]) + (o[4][0] + o[4][1]), r = rcp(L);
        const float y0 = ((o[0][0] + o[0][1]) + (o[1][0] + o[1][1])) + (o[2][0] + o[2][1]);
        const float y1 = ((o[0][2] + o[0][3]) + (o[1][2] + o[1][3])) + (o[2][2] + o[2][3]);
        const uint32_t y = pack2(fmaf(y0, r * ws0, qv0), fmaf(y1, r * ws1, qv1));
        asm volatile("{.reg .b16 l, h; mov.b32 {l, h}, %1; st.global.b16 [%0], l; st.global.b16 [%0 + 16], h;}" ::"l"(op), "r"(y) : "memory");
        if (threadIdx.x == 0) TSD(11, y);
        if (__builtin_expect(__all_sync(~0u, L >= 0.001953125f && L <= 2048.f && fabsf(y0) < INFINITY) || pass, 1)) break;
        const uint32_t keep = sb + RD_W + 32768 + warp * 6144 + lane * 16;
#pragma unroll
        for (int kk = 0; kk < 12; kk++) sts128(keep + kk * 512, wa[kk][0], wa[kk][1], wa[kk][2], wa[kk][3]);
        slow_rows(f0, f1, q, wq, wk, sb);
#pragma unroll
        for (int kk = 0; kk < 12; kk++) {
            const uint4 v = lds128(keep + kk * 512);
            wa[kk][0] = v.x; wa[kk][1] = v.y; wa[kk][2] = v.z; wa[kk][3] = v.w;
        }
    }
}

__global__ void __launch_bounds__(NTHREADS, 1)
attn_main(const char* __restrict__ f0, const char* __restrict__ f1,
          const __nv_bfloat16* __restrict__ q, const __nv_bfloat16* __restrict__ wq, const __nv_bfloat16* __restrict__ wk, Scratch* scr,
          const __nv_bfloat16* __restrict__ wv, const __nv_bfloat16* __restrict__ wo, __nv_bfloat16* __restrict__ out,
          const __grid_constant__ CUtensorMap m0, const __grid_constant__ CUtensorMap m1)
{
    extern __shared__ char smem_raw[];
    const uint32_t sb = (s2u(smem_raw) + 1023u) & ~1023u;
    const int G = gridDim.x - NRD;
    const int b = blockIdx.x - NRD;
    if (threadIdx.x == 0 && b >= 0) {
        const char* a = f0 + (uint32_t)(b * (4 * TP * C * 2) + (b >> 4) * (W0 * C * 2));
        prefetch_l2(a, 4 * TP * C * 2);
        prefetch_l2(a + W0 * C * 2, 4 * TP * C * 2);
        prefetch_l2(f1 + b * (2 * TP * C * 2), 2 * TP * C * 2);
        prefetch_l2((const char*)(b % (2 * WSL) < WSL ? wq : wk) + b % WSL * (C * C * 2 / WSL), C * C * 2 / WSL);
    }
    if (b < 0) { reducer(f0, f1, q, wq, wk, scr, wv, wo, out, sb, G); return; }
    const int warp = __shfl_sync(~0u, threadIdx.x >> 5, 0), lane = threadIdx.x & 31;
    const int g = lane >> 2, t = lane & 3;

    if (warp >= 8) {
        if (warp < 10) {
            const int p = warp - 8;
            const unsigned c0 = clock32();
            const uint32_t sbp = opaque(sb), bar = sbp + SM_BAR + p * 8;
            uint64_t pol; asm volatile("createpolicy.fractional.L2::evict_first.b64 %0, 1.0;" : "=l"(pol));
            if (elect()) {
                if (p == 0) TS(0);
                asm volatile("prefetch.tensormap [%0];" ::"l"(p ? &m1 : &m0) : "memory");
#pragma unroll
                for (int n = 0; n < NI; n++) mbar_init(bar + n * 16, 2);
                asm volatile("fence.mbarrier_init.release.cluster;" ::: "memory");
#pragma unroll
                for (int n = 0; n < NI; n++) {
                    issue_tile(&m0, &m1, sbp, p + 2 * n, 2 * b + p + 2 * n * G, pol);
                    TR(0, 2 * n + p);
                    sts32(sbp + SM_FLAG + (p + 2 * n) * 4, 0);
                    mbar_arrive(bar + n * 16);
                }
#pragma unroll
                for (int n = 0; n < NS / 2; n++) {
                    if (n >= NI) mbar_init(bar + n * 16, 2);
                    mbar_init(bar + NS * 8 + n * 16, 1);
                }
                if (p == 0) mbar_init(sbp + SM_REF, 1);
                asm volatile("fence.mbarrier_init.release.cluster;" ::: "memory");
            }
            __syncwarp();
            bar_arrive(B_QK, NTHREADS);
            if (elect()) {
                int tl = 2 * b + p + 2 * NI * G;
                int s = p + 2 * NI; uint32_t ph = 1;
                int sa = p, na = 0; uint32_t pa = 0;
                bool late = false;
                for (int n = NI;; n++) {
                    const int d = n < NRAMP ? D0 : (tl >= NT - TAILT ? D2 : D1);
                    while (n - na >= d) {
                        mbar_wait(sbp + SM_BAR + sa * 8, pa);
                        if (na < NS / 2) TR(1, 2 * na + p);
                        na++; sa += 2;
                        if (sa >= NS) { sa -= NS; pa ^= 1; }
                    }
                    mbar_wait(sbp + SM_BAR + (NS + s) * 8, ph);
                    if (n < NPACE) while (clock32() - c0 < (n ? T1 + (2 * (n - 1) + p) * TG : T0)) {}
                    issue_tile(&m0, &m1, sbp, s, tl, pol);
                    TR(0, 2 * n + p);
                    int nxt = tl + 2 * G;
                    if (n >= NST - 1) nxt = grab_tile(g_ctr) + 2 * NST * G;
                    const bool last = nxt >= NT;
                    uint32_t flag = last;
                    if (!late && nxt >= NT - MAXT - 16 * b) { late = true; flag |= 2; }
                    if (last) mbar_wait(sbp + SM_REF, 0);
                    sts32(sbp + SM_FLAG + s * 4, flag);
                    mbar_arrive(sbp + SM_BAR + s * 8);
                    if (last) break;
                    s += 2;
                    if (s >= NS) { s -= NS; ph ^= 1; }
                    tl = nxt;
                }
                if (p) TSE(5);
            }
            return;
        }
        const int h = threadIdx.x - 320;
        uint4 v[6];
        for (int it = 0;; it++) {
            bool miss = false;
#pragma unroll
            for (int k = 0; k < 6; k++) v[k] = ldg_relaxed(g_qk + k * 64 + h);
#pragma unroll
            for (int k = 0; k < 6; k++) miss |= has(v[k], 0);
            if (!miss) break;
            if (it > SPIN_LIMIT) __trap();
            if (it == 0) __nanosleep(QSLEEP);
        }
#pragma unroll
        for (int k = 0; k < 6; k++) sts128(sb + SM_QK + (k * 64 + h) * 16, ~v[k].x, ~v[k].y, ~v[k].z, ~v[k].w);
        __syncwarp();
        bar_sync(B_QK, NTHREADS);
        if (warp == 11) return;
        uint32_t r = 1;
        for (int it = 0;; it++) {
            __nanosleep(500);
            if (lane < NQ) asm volatile("ld.acquire.gpu.global.u32 %0, [%1];" : "=r"(r) : "l"(g_mref + lane) : "memory");
            if (__all_sync(~0u, r != 0)) break;
            if (it > SPIN_LIMIT) __trap();
        }
        if (lane < NQ) sts32(sb + SM_M + lane * 4, ~r);
        __syncwarp();
        if (lane == 0) { mbar_arrive(sb + SM_REF); TSE(7); }
        return;
    }

    const int grp = warp >> 2, cw = warp & 3;
    const int xp = lane & 7, mi = lane >> 3;
    const uint32_t offS1 = opaque(12288 + xp * 128 + ((mi ^ xp) << 4)), offS1x = opaque(offS1 ^ 64);
    const uint32_t offS0 = opaque(offS1 - 12288 + cw * 3072), offS0x = opaque(offS0 ^ 64);
    const uint32_t offT = opaque(mi * 3072 + xp * 128 + (((cw + 4 * grp) ^ xp) << 4)), offTx = opaque(offT ^ 64);
    const uint32_t offU = opaque(12288 + (mi % 3) * 1024 + xp * 128 + (((cw + 4 * (grp ^ (mi / 3))) ^ xp) << 4));
    const uint32_t offV = opaque(12288 + (1 + (mi & 1)) * 1024 + xp * 128 + (((cw + 4 * (grp ^ 1)) ^ xp) << 4));
    const int shl = opaque(9 * t), shl4 = opaque(9 * t + 4);
    const uint32_t pw = opaque((cw >> 1) * 512 + lane * 16 + (cw & 1) * 8), muw = opaque(1024 + t * 16 + cw * 4);
    const uint32_t prd = opaque(lane * 16), mur = opaque(1024 + t * 16), mof = g * 4;
    uint32_t pb0 = sb + SM_P + grp * 2 * PBUF;
    const uint32_t pbx = pb0 ^ (pb0 + PBUF);
    const bool odd = g & 1;
    const int barid = B_GRP + grp;
    const bool elected = cw == 3 && lane == 0;

    uint32_t qa[48];
    float r_lo, r_hi;
    bar_sync(B_QK, NTHREADS);
    {
        float rr[2][4] = {{0.f, 0.f, 0.f, 0.f}, {0.f, 0.f, 0.f, 0.f}};
#pragma unroll
        for (int kk = 0; kk < 12; kk++) {
            const uint4 v = lds128(sb + SM_QK + kk * 512 + lane * 16);
            qa[4 * kk] = v.x; qa[4 * kk + 1] = v.y; qa[4 * kk + 2] = v.z; qa[4 * kk + 3] = v.w;
            mma(rr[kk & 1], v.x, v.y, v.z, v.w, ONES, ONES);
        }
        r_lo = rr[0][0] + rr[1][0]; r_hi = rr[0][2] + rr[1][2];
    }
    if (threadIdx.x == 0) TS(1);

    float acc[6][4];
#pragma unroll
    for (int i = 0; i < 6; i++) acc[i][0] = acc[i][1] = acc[i][2] = acc[i][3] = 0.f;
    float m_lo = -INFINITY, m_hi = -INFINITY, l_lo = 0.f, l_hi = 0.f;
    float cm[4] = {0.f, 0.f, 0.f, 0.f};
    uint32_t xt[6][4], yt[6]; uint4 pa, pb, mv;
    const uint32_t dof = opaque(((b & 1) * ACC + ((g >> 1) * 8 + warp) * 8 + (lane & 7)) * 16);
    int s = grp; uint32_t ph = 0;
    while (true) {
        mbar_wait(sb + SM_BAR + s * 8, ph);
        PH(0, 0);
        const uint32_t stop = lds32(sb + SM_FLAG + s * 4);
        const uint32_t st = sb + SM_STAGES + s * STAGE;
        float sc[2][4], gr[4][4], sx[4];
#pragma unroll
        for (int e = 0; e < 4; e++) sc[0][e] = sc[1][e] = gr[0][e] = gr[1][e] = gr[2][e] = gr[3][e] = sx[e] = 0.f;
#pragma unroll
        for (int qq = 0; qq < 6; qq++) {
            uint32_t x[4], y[4];
            ldsm4(x, st + (qq & 1 ? offS0x : offS0) + (qq >> 1) * 1024);
            ldsm4(y, st + (qq & 1 ? offS1x : offS1) + (qq >> 1) * 1024);
#pragma unroll
            for (int e = 0; e < 4; e++) x[e] = hadd2(x[e], y[e]);
            mma8(gr[0], x[0], x[1], x[0]);
            mma8(gr[1], x[0], x[1], x[1]);
            mma(sx, x[0], x[1], x[2], x[3], ONES, ONES);
            mma8(gr[GR4 ? 2 : 0], x[2], x[3], x[2]);
            mma8(gr[GR4 ? 3 : 1], x[2], x[3], x[3]);
            mma(sc[0], qa[8 * qq], qa[8 * qq + 1], qa[8 * qq + 2], qa[8 * qq + 3], x[0], x[1]);
            mma(sc[1], qa[8 * qq + 4], qa[8 * qq + 5], qa[8 * qq + 6], qa[8 * qq + 7], x[2], x[3]);
        }
        ldsm4t(yt, st + offU);
        ldsm2t(yt + 4, st + offV);
#pragma unroll
        for (int i = 0; i < 6; i++) ldsm4t(xt[i], st + (i < 3 ? offT : offTx) + (i % 3) * 1024);

        const float mu = (sx[0] + sx[2]) * (1.f / C), ss = GR4 ? (odd ? (gr[0][1] + gr[1][3]) + (gr[2][1] + gr[3][3]) : (gr[0][0] + gr[1][2]) + (gr[2][0] + gr[3][2])) : (odd ? gr[0][1] + gr[1][3] : gr[0][0] + gr[1][2]);
        const float rs = rsq(fmaxf(fmaf(-mu, mu, fmaf(ss, 1.f / C, 1e-5f)), 1e-5f));
        const float mu0 = __shfl_sync(~0u, mu, shl), mu1 = __shfl_sync(~0u, mu, shl4);
        const float rs0 = __shfl_sync(~0u, rs, shl), rs1 = __shfl_sync(~0u, rs, shl4);
        const float u0 = fmaf(-mu0, r_lo, sc[0][0] + sc[1][0]), u1 = fmaf(-mu1, r_lo, sc[0][1] + sc[1][1]);
        const float u2 = fmaf(-mu0, r_hi, sc[0][2] + sc[1][2]), u3 = fmaf(-mu1, r_hi, sc[0][3] + sc[1][3]);
        const float d0 = fmaf(u0, rs0, -m_lo), d1 = fmaf(u1, rs1, -m_lo), d2 = fmaf(u2, rs0, -m_hi), d3 = fmaf(u3, rs1, -m_hi);
        PH(1, u(d0 + d2));
        float p0 = ex2(d0), p1 = ex2(d1), p2 = ex2(d2), p3 = ex2(d3);
        sts64(pb0 + pw, pack2(p0 * rs0, p1 * rs1), pack2(p2 * rs0, p3 * rs1));
        if (lane < 4) sts32(pb0 + muw, pack2(mu0, mu1));
        const bool over = bar_any(barid, 128, fmaxf(fmaxf(d0, d1), fmaxf(d2, d3)) > LAZY);
        PH(3, 0);
        pa = lds128(pb0 + prd); pb = lds128(pb0 + prd + 512); mv = lds128(pb0 + mur);
        if (elected) mbar_arrive(sb + SM_BAR + (NS + s) * 8);
        if (__builtin_expect(over, 0)) {
            const float s0 = u0 * rs0, s1 = u1 * rs1, s2 = u2 * rs0, s3 = u3 * rs1;
            float xl = fmaxf(s0, s1), xh = fmaxf(s2, s3);
            xl = fmaxf(xl, __shfl_xor_sync(~0u, xl, 1)); xh = fmaxf(xh, __shfl_xor_sync(~0u, xh, 1));
            xl = fmaxf(xl, __shfl_xor_sync(~0u, xl, 2)); xh = fmaxf(xh, __shfl_xor_sync(~0u, xh, 2));
            if (t < 2) sts32(sb + SM_MX + grp * 256 + ((g + 8 * t) * 4 + cw) * 4, u(t ? xh : xl));
            bar_sync(B_MAX + grp, 128);
            const uint4 ml4 = lds128(sb + SM_MX + grp * 256 + g * 16), mh4 = lds128(sb + SM_MX + grp * 256 + g * 16 + 128);
            const float nl = fmaxf(fmaxf(fmaxf(f(ml4.x), f(ml4.y)), fmaxf(f(ml4.z), f(ml4.w))), m_lo);
            const float nh = fmaxf(fmaxf(fmaxf(f(mh4.x), f(mh4.y)), fmaxf(f(mh4.z), f(mh4.w))), m_hi);
            p0 = ex2(s0 - nl); p1 = ex2(s1 - nl); p2 = ex2(s2 - nh); p3 = ex2(s3 - nh);
            sts64(pb0 + pw, pack2(p0 * rs0, p1 * rs1), pack2(p2 * rs0, p3 * rs1));
            const float al = ex2(m_lo - nl), ah = ex2(m_hi - nh);
            m_lo = nl; m_hi = nh;
            l_lo *= al; l_hi *= ah; cm[0] *= al; cm[2] *= ah;
#pragma unroll
            for (int i = 0; i < 6; i++) { acc[i][0] *= al; acc[i][1] *= al; acc[i][2] *= ah; acc[i][3] *= ah; }
            bar_sync(B_MAX + grp, 128);
            pa = lds128(pb0 + prd); pb = lds128(pb0 + prd + 512);
        }
        l_lo += p0 + p1; l_hi += p2 + p3;
        if (stop & 1) break;
#pragma unroll
        for (int i = 0; i < 6; i++) mma(acc[i], pa.x, pa.y, pa.z, pa.w, hadd2v(xt[i][0], yt[i]), hadd2v(xt[i][1], yt[i]));
        mma(cm, pa.x, pa.y, pa.z, pa.w, mv.x, mv.y);
#pragma unroll
        for (int i = 0; i < 6; i++) mma(acc[i], pb.x, pb.y, pb.z, pb.w, hadd2v(xt[i][2], yt[i]), hadd2v(xt[i][3], yt[i]));
        mma(cm, pb.x, pb.y, pb.z, pb.w, mv.z, mv.w);
        PH(4, u(acc[5][0]));
        if (stop) {
            float a = l_lo + __shfl_xor_sync(~0u, l_lo, 1), c = l_hi + __shfl_xor_sync(~0u, l_hi, 1);
            a += __shfl_xor_sync(~0u, a, 2); c += __shfl_xor_sync(~0u, c, 2);
            const uint32_t m = u((t ? m_hi : m_lo) + lg2(fmaxf(t ? c : a, 1.f)));
            if (t < 2) asm volatile("red.relaxed.gpu.global.max.u32 [%0], %1;" ::"l"(g_mmax + g + 8 * t), "r"(m >> 31 ? ~m : m | 0x80000000u) : "memory");
        }
        pb0 ^= pbx;
        s += 2;
        if (s >= NS) { s -= NS; ph ^= 1; }
    }
    const float al = ex2(m_lo - f(lds32(sb + SM_M + mof))), ah = ex2(m_hi - f(lds32(sb + SM_M + 32 + mof)));
    mma(cm, pa.x, pa.y, pa.z, pa.w, mv.x, mv.y);
#pragma unroll
    for (int i = 3; i < 6; i++) mma(acc[i], pa.x, pa.y, pa.z, pa.w, hadd2v(xt[i][0], yt[i]), hadd2v(xt[i][1], yt[i]));
    mma(cm, pb.x, pb.y, pb.z, pb.w, mv.z, mv.w);
#pragma unroll
    for (int i = 3; i < 6; i++) mma(acc[i], pb.x, pb.y, pb.z, pb.w, hadd2v(xt[i][2], yt[i]), hadd2v(xt[i][3], yt[i]));
#pragma unroll
    for (int i = 0; i < 3; i++) mma(acc[i], pa.x, pa.y, pa.z, pa.w, hadd2v(xt[i][0], yt[i]), hadd2v(xt[i][1], yt[i]));
#pragma unroll
    for (int i = 0; i < 3; i++) mma(acc[i], pb.x, pb.y, pb.z, pb.w, hadd2v(xt[i][2], yt[i]), hadd2v(xt[i][3], yt[i]));
    if (threadIdx.x == grp * 128) TSE(2 + grp);
    if (threadIdx.x == grp * 128 + 96) TSX(2 + grp, u(acc[5][0]));

    uint4* const dst = reinterpret_cast<uint4*>(reinterpret_cast<char*>(g_acc) + dof);
    const uint32_t xw = sb + SM_STAGES + grp * STAGE + cw * 1536 + prd, xr = sb + SM_STAGES + (grp ^ 1) * STAGE + cw * 1536 + prd;
    const float cl = -cm[0] * al, ch = -cm[2] * ah;
#pragma unroll
    for (int i = 0; i < 3; i++)
        sts128(xw + i * 512, u(fmaf(acc[3 + i][0], al, cl)), u(fmaf(acc[3 + i][1], al, cl)), u(fmaf(acc[3 + i][2], ah, ch)), u(fmaf(acc[3 + i][3], ah, ch)));
#pragma unroll
    for (int i = 0; i < 3; i++) { acc[i][0] = fmaf(acc[i][0], al, cl); acc[i][1] = fmaf(acc[i][1], al, cl); acc[i][2] = fmaf(acc[i][2], ah, ch); acc[i][3] = fmaf(acc[i][3], ah, ch); }
    const uint32_t w_lo = packh(l_lo * al, 1.f), w_hi = packh(l_hi * ah, 1.f);
    bar_sync(B_MERGE, 256);
    if (threadIdx.x == 224) TSX(4, 0);
    uint4 o[3];
#pragma unroll
    for (int i = 0; i < 3; i++) o[i] = lds128(xr + i * 512);
    red8h(dst, packh(acc[0][0] + f(o[0].x), acc[0][1] + f(o[0].y)), packh(acc[1][0] + f(o[1].x), acc[1][1] + f(o[1].y)), packh(acc[2][0] + f(o[2].x), acc[2][1] + f(o[2].y)), w_lo);
    red8h(dst + 256, packh(acc[0][2] + f(o[0].z), acc[0][3] + f(o[0].w)), packh(acc[1][2] + f(o[1].z), acc[1][3] + f(o[1].w)), packh(acc[2][2] + f(o[2].z), acc[2][3] + f(o[2].w)), w_hi);
    if (threadIdx.x == 0) TSE(4);
    if (threadIdx.x == 224) TSX(9, 0);
}

typedef CUresult (*EncodeFn)(CUtensorMap*, CUtensorMapDataType, cuuint32_t, void*, const cuuint64_t*, const cuuint64_t*,
                             const cuuint32_t*, const cuuint32_t*, CUtensorMapInterleave, CUtensorMapSwizzle,
                             CUtensorMapL2promotion, CUtensorMapFloatOOBfill);

}

extern "C" void kernel_launch(void* const* d_in, const int* in_sizes, int n_in, void* d_out, int out_size) {
    const __nv_bfloat16* q = (const __nv_bfloat16*)d_in[0];
    char* f0 = (char*)d_in[1];
    char* f1 = (char*)d_in[2];
    const __nv_bfloat16* wq = (const __nv_bfloat16*)d_in[3];
    const __nv_bfloat16* wk = (const __nv_bfloat16*)d_in[4];
    const __nv_bfloat16* wv = (const __nv_bfloat16*)d_in[5];
    const __nv_bfloat16* wo = (const __nv_bfloat16*)d_in[6];

    static EncodeFn enc = nullptr;
    static int grid = 0;
    static Scratch* scr = nullptr;
    if (!enc) {
        void* fn = nullptr; cudaDriverEntryPointQueryResult qr;
        cudaGetDriverEntryPoint("cuTensorMapEncodeTiled", &fn, cudaEnableDefault, &qr);
        enc = (EncodeFn)fn;
        cudaGetSymbolAddress((void**)&scr, g_scratch);
        int dev = 0, sms = 0;
        cudaGetDevice(&dev);
        cudaDeviceGetAttribute(&sms, cudaDevAttrMultiProcessorCount, dev);
        grid = sms < MAXG ? sms : MAXG;
        cudaFuncSetAttribute(attn_main, cudaFuncAttributeMaxDynamicSharedMemorySize, SMEM_BYTES);
    }
    CUtensorMap m0, m1;
    {
        cuuint64_t dims[5] = {64, W1, 3, 2, W0};
        cuuint64_t str[4] = {2 * C * 2, 128, C * 2, (cuuint64_t)W0 * C * 2};
        cuuint32_t box[5] = {64, TP, 3, 2, 2}, es[5] = {1, 1, 1, 1, 1};
        enc(&m0, CU_TENSOR_MAP_DATA_TYPE_BFLOAT16, 5, f0, dims, str, box, es, CU_TENSOR_MAP_INTERLEAVE_NONE,
            CU_TENSOR_MAP_SWIZZLE_128B, CU_TENSOR_MAP_L2_PROMOTION_NONE, CU_TENSOR_MAP_FLOAT_OOB_FILL_NONE);
    }
    {
        cuuint64_t dims[4] = {64, W1, 3, W1};
        cuuint64_t str[3] = {C * 2, 128, (cuuint64_t)W1 * C * 2};
        cuuint32_t box[4] = {64, TP, 3, 1}, es[4] = {1, 1, 1, 1};
        enc(&m1, CU_TENSOR_MAP_DATA_TYPE_BFLOAT16, 4, f1, dims, str, box, es, CU_TENSOR_MAP_INTERLEAVE_NONE,
            CU_TENSOR_MAP_SWIZZLE_128B, CU_TENSOR_MAP_L2_PROMOTION_NONE, CU_TENSOR_MAP_FLOAT_OOB_FILL_NONE);
    }
    attn_main<<<grid, NTHREADS, SMEM_BYTES, cudaStreamPerThread>>>(f0, f1, q, wq, wk, scr, wv, wo, (__nv_bfloat16*)d_out, m0, m1);
}
```

```cpp
#include <cuda_runtime.h>
#include <cuda_bf16.h>
#include <cuda.h>
#include <stdint.h>

namespace {

constexpr int C = 192;
constexpr int NQ = 16;
constexpr int W0 = 512;
constexpr int W1 = 256;
constexpr int TP = 8;
constexpr int NT = W1 * W1 / TP;
constexpr int STAGE = TP * 5 * C * 2;
#define NS 14
#define D0 3
#define D1 2
#define D2 1
#define NRAMP 5
#define TAILT 150
#define QSLEEP 700
#define WSL 24
#define MAXT 3000
#define REFT 1800
#define POLLN 1
#define PGAP 64
#define NPW 5
#define NPROBE 8
#define MODE 3
#define LAZY 12.f
#define GR4 1
#define NST 4
#define NI 1
#define NPACE 5
#define T0 0
#define T1 1600
#define TG 960
static_assert(NST > D0, "the first dynamic tile index must not delay the start");
constexpr int NTHREADS = 384;
constexpr int MAXG = 132;
constexpr int NRD = NQ;
constexpr int NSRC = 12;
constexpr int SPIN_LIMIT = 1 << 22;

constexpr int SM_STAGES = 0;
constexpr int SM_P = NS * STAGE;
constexpr int PBUF = 1088;
constexpr int SM_QK = SM_P + 4 * PBUF;
constexpr int SM_MX = SM_QK + 6144;
constexpr int SM_M = SM_MX + 512;
constexpr int SM_BAR = SM_M + 64;
constexpr int SM_REF = SM_BAR + 16 * NS;
constexpr int SM_FLAG = SM_REF + 8;
constexpr int SM_TOTAL = SM_FLAG + 4 * NS;
constexpr int SMEM_BYTES = SM_TOTAL + 1024;
static_assert(SMEM_BYTES <= 232448, "smem");
constexpr int WROW = 400;
constexpr int RD_W = 0;
constexpr int RD_QN = 2 * C * WROW;
constexpr int RD_KQ = RD_QN + 6144;
constexpr int RD_B = RD_KQ + 7168;
constexpr int RD_B2 = 17 * 80;
constexpr int RD_PLACE = RD_B + 2 * RD_B2;
constexpr int RD_BAR = RD_PLACE + 16;
constexpr int RD_A = RD_BAR + 64;
constexpr int RD_WS = RD_A + 12 * 6 * 512;
static_assert(RD_WS + 12 * 128 <= SM_TOTAL, "smem");

struct Scratch {
    uint4 acc[2048];
    uint4 qk[NSRC * 32];
    unsigned ctr[32];
    unsigned claim[32];
    unsigned mmax[32];
    unsigned mref[32];
};
__device__ __align__(8192) Scratch g_scratch;
#define g_acc (scr->acc)
#define g_claim (scr->claim)
#define g_qk (scr->qk)
#define g_ctr (scr->ctr)
#define g_mmax (scr->mmax)
#define g_mref (scr->mref)
#define g_ts (scr->ts)
#define g_tr (scr->tr)
#define TR(k, i) do {} while (0)
#define TS(i) do {} while (0)
#define TSD(i, dep) do {} while (0)
#define TSX(i, dep) do {} while (0)
#define TSP(i, dep) do {} while (0)
#define TSE(i) TS(i)
#define CK_(i, dep) do {} while (0)
#define PH(i, dep) do {} while (0)

__device__ __forceinline__ uint32_t s2u(const void* p) { return (uint32_t)__cvta_generic_to_shared(p); }
__device__ __forceinline__ void mbar_init(uint32_t a, int c) { asm volatile("mbarrier.init.shared::cta.b64 [%0], %1;" ::"r"(a), "r"(c) : "memory"); }
__device__ __forceinline__ void mbar_expect(uint32_t a, uint32_t b) { asm volatile("mbarrier.arrive.expect_tx.shared::cta.b64 _, [%0], %1;" ::"r"(a), "r"(b) : "memory"); }
__device__ __forceinline__ void mbar_arrive(uint32_t a) { asm volatile("mbarrier.arrive.shared::cta.b64 _, [%0];" ::"r"(a) : "memory"); }
__device__ __forceinline__ void mbar_wait(uint32_t a, uint32_t ph) {
    uint32_t ok; int it = 0;
    do {
        asm volatile("{.reg .pred p; mbarrier.try_wait.parity.shared::cta.b64 p, [%1], %2; selp.u32 %0,1,0,p;}" : "=r"(ok) : "r"(a), "r"(ph) : "memory");
        if (++it > SPIN_LIMIT) __trap();
    } while (!ok);
}
__device__ __forceinline__ bool elect() {
    uint32_t r; asm volatile("{.reg .pred p; elect.sync _|p, 0xffffffff; selp.u32 %0, 1, 0, p;}" : "=r"(r)); return r;
}
__device__ __forceinline__ void bar_sync(int id, int n) { asm volatile("bar.sync %0, %1;" ::"r"(id), "r"(n) : "memory"); }
__device__ __forceinline__ bool bar_any(int id, int n, bool c) {
    uint32_t r;
    asm volatile("{.reg .pred p, q; setp.ne.u32 q, %3, 0; bar.red.or.pred p, %1, %2, q; selp.u32 %0, 1, 0, p;}" : "=r"(r) : "r"(id), "r"(n), "r"((uint32_t)c) : "memory");
    return r;
}
__device__ __forceinline__ void bar_arrive(int id, int n) { asm volatile("bar.arrive %0, %1;" ::"r"(id), "r"(n) : "memory"); }
__device__ __forceinline__ void ldsm4(uint32_t* r, uint32_t a) {
    asm volatile("ldmatrix.sync.aligned.m8n8.x4.shared.b16 {%0,%1,%2,%3}, [%4];" : "=r"(r[0]), "=r"(r[1]), "=r"(r[2]), "=r"(r[3]) : "r"(a) : "memory");
}
__device__ __forceinline__ void ldsm4t(uint32_t* r, uint32_t a) {
    asm volatile("ldmatrix.sync.aligned.m8n8.x4.trans.shared.b16 {%0,%1,%2,%3}, [%4];" : "=r"(r[0]), "=r"(r[1]), "=r"(r[2]), "=r"(r[3]) : "r"(a) : "memory");
}
__device__ __forceinline__ void ldsm2t(uint32_t* r, uint32_t a) {
    asm volatile("ldmatrix.sync.aligned.m8n8.x2.trans.shared.b16 {%0,%1}, [%2];" : "=r"(r[0]), "=r"(r[1]) : "r"(a) : "memory");
}
__device__ __forceinline__ void mma(float* d, uint32_t a0, uint32_t a1, uint32_t a2, uint32_t a3, uint32_t b0, uint32_t b1) {
    asm("mma.sync.aligned.m16n8k16.row.col.f32.bf16.bf16.f32 {%0,%1,%2,%3}, {%4,%5,%6,%7}, {%8,%9}, {%0,%1,%2,%3};"
        : "+f"(d[0]), "+f"(d[1]), "+f"(d[2]), "+f"(d[3]) : "r"(a0), "r"(a1), "r"(a2), "r"(a3), "r"(b0), "r"(b1));
}
__device__ __forceinline__ void mmah(float* d, uint32_t a0, uint32_t a1, uint32_t a2, uint32_t a3, uint32_t b0, uint32_t b1) {
    asm("mma.sync.aligned.m16n8k16.row.col.f32.f16.f16.f32 {%0,%1,%2,%3}, {%4,%5,%6,%7}, {%8,%9}, {%0,%1,%2,%3};"
        : "+f"(d[0]), "+f"(d[1]), "+f"(d[2]), "+f"(d[3]) : "r"(a0), "r"(a1), "r"(a2), "r"(a3), "r"(b0), "r"(b1));
}
__device__ __forceinline__ void mma8(float* d, uint32_t a0, uint32_t a1, uint32_t b0) {
    asm("mma.sync.aligned.m16n8k8.row.col.f32.bf16.bf16.f32 {%0,%1,%2,%3}, {%4,%5}, {%6}, {%0,%1,%2,%3};"
        : "+f"(d[0]), "+f"(d[1]), "+f"(d[2]), "+f"(d[3]) : "r"(a0), "r"(a1), "r"(b0));
}
__device__ __forceinline__ uint32_t hadd2(uint32_t a, uint32_t b) {
    uint32_t r; asm("add.rn.bf16x2 %0, %1, %2;" : "=r"(r) : "r"(a), "r"(b)); return r;
}
__device__ __forceinline__ uint32_t pack2(float lo, float hi) {
    uint32_t r; asm("cvt.rn.bf16x2.f32 %0, %1, %2;" : "=r"(r) : "f"(hi), "f"(lo)); return r;
}
__device__ __forceinline__ uint32_t packh(float lo, float hi) {
    uint32_t r; asm("cvt.rn.f16x2.f32 %0, %1, %2;" : "=r"(r) : "f"(hi), "f"(lo)); return r;
}
__device__ __forceinline__ float2 unpackh(uint32_t v) {
    float2 r; asm("{.reg .b16 l, h; mov.b32 {l, h}, %2; cvt.f32.f16 %0, l; cvt.f32.f16 %1, h;}" : "=f"(r.x), "=f"(r.y) : "r"(v)); return r;
}
__device__ __forceinline__ float bflo(uint32_t v) { return __uint_as_float(v << 16); }
__device__ __forceinline__ float bfhi(uint32_t v) { return __uint_as_float(v & 0xffff0000u); }
__device__ __forceinline__ float ex2(float x) { float r; asm("ex2.approx.ftz.f32 %0, %1;" : "=f"(r) : "f"(x)); return r; }
__device__ __forceinline__ void sts128(uint32_t a, uint32_t x, uint32_t y, uint32_t z, uint32_t w) {
    asm volatile("st.shared.v4.b32 [%0], {%1,%2,%3,%4};" ::"r"(a), "r"(x), "r"(y), "r"(z), "r"(w) : "memory");
}
__device__ __forceinline__ void sts64(uint32_t a, uint32_t x, uint32_t y) {
    asm volatile("st.shared.v2.b32 [%0], {%1,%2};" ::"r"(a), "r"(x), "r"(y) : "memory");
}
__device__ __forceinline__ void sts32(uint32_t a, uint32_t x) { asm volatile("st.shared.b32 [%0], %1;" ::"r"(a), "r"(x) : "memory"); }
__device__ __forceinline__ uint4 lds128(uint32_t a) {
    uint4 v; asm volatile("ld.shared.v4.b32 {%0,%1,%2,%3}, [%4];" : "=r"(v.x), "=r"(v.y), "=r"(v.z), "=r"(v.w) : "r"(a) : "memory"); return v;
}
__device__ __forceinline__ uint32_t lds32(uint32_t a) { uint32_t v; asm volatile("ld.shared.b32 %0, [%1];" : "=r"(v) : "r"(a) : "memory"); return v; }
__device__ __forceinline__ int grab_tile(unsigned* ctr) {
    int v; asm volatile("atom.relaxed.gpu.global.inc.u32 %0, [%1], 0x7fffffff;" : "=r"(v) : "l"(ctr) : "memory"); return v;
}
__device__ __forceinline__ uint32_t opaque(uint32_t v) { uint32_t r; asm volatile("mov.b32 %0, %1;" : "=r"(r) : "r"(v)); return r; }
__device__ __forceinline__ unsigned clock32() { unsigned c; asm volatile("mov.u32 %0, %%clock;" : "=r"(c)); return c; }
__device__ __forceinline__ float rsq(float x) { float r; asm("rsqrt.approx.ftz.f32 %0, %1;" : "=f"(r) : "f"(x)); return r; }
__device__ __forceinline__ float rcp(float x) { float r; asm("rcp.approx.ftz.f32 %0, %1;" : "=f"(r) : "f"(x)); return r; }
__device__ __forceinline__ float lg2(float x) { float r; asm("lg2.approx.ftz.f32 %0, %1;" : "=f"(r) : "f"(x)); return r; }
__device__ __forceinline__ float f(uint32_t v) { return __uint_as_float(v); }
__device__ __forceinline__ uint32_t u(float v) { return __float_as_uint(v); }

constexpr uint32_t ONES = 0x3F803F80u;
constexpr float QSCALE = 0.07216878364870322f * 1.4426950408889634f;

__device__ __forceinline__ void issue_tile(const CUtensorMap* m0, const CUtensorMap* m1, uint32_t sb, int s, int tl, uint64_t pol) {
    const uint32_t full = sb + SM_BAR + s * 8, dst = sb + SM_STAGES + s * STAGE;
    const int par = tl * TP, y = par >> 8, x = par & 255;
    mbar_expect(full, STAGE);
    asm volatile("cp.async.bulk.tensor.5d.shared::cluster.global.mbarrier::complete_tx::bytes.L2::cache_hint [%0], [%1, {%3,%4,%3,%3,%5}], [%2], %6;"
                 ::"r"(dst), "l"(m0), "r"(full), "r"(0), "r"(x), "r"(2 * y), "l"(pol) : "memory");
    asm volatile("cp.async.bulk.tensor.4d.shared::cluster.global.mbarrier::complete_tx::bytes.L2::cache_hint [%0], [%1, {%3,%4,%3,%5}], [%2], %6;"
                 ::"r"(dst + TP * 4 * C * 2), "l"(m1), "r"(full), "r"(0), "r"(x), "r"(y), "l"(pol) : "memory");
}

__device__ __forceinline__ void prefetch_l2(const void* a, int n) { asm volatile("cp.async.bulk.prefetch.L2.global [%0], %1;" ::"l"(a), "r"(n) : "memory"); }
__device__ __forceinline__ uint4 ldg_relaxed(const uint4* p) {
    uint4 v; asm volatile("ld.relaxed.gpu.global.v4.u32 {%0,%1,%2,%3}, [%4];" : "=r"(v.x), "=r"(v.y), "=r"(v.z), "=r"(v.w) : "l"(p) : "memory"); return v;
}
__device__ __forceinline__ uint32_t ldg_relaxed32(const void* p) {
    uint32_t v; asm volatile("ld.relaxed.gpu.global.u32 %0, [%1];" : "=r"(v) : "l"(p) : "memory"); return v;
}
__device__ __forceinline__ void stg_relaxed(uint4* p, uint32_t x, uint32_t y, uint32_t z, uint32_t w) {
    asm volatile("st.relaxed.gpu.global.v4.u32 [%0], {%1,%2,%3,%4};" ::"l"(p), "r"(x), "r"(y), "r"(z), "r"(w) : "memory");
}
__device__ __forceinline__ void stg_relaxed32(void* p, uint32_t x) { asm volatile("st.relaxed.gpu.global.u32 [%0], %1;" ::"l"(p), "r"(x) : "memory"); }
__device__ __forceinline__ bool has(const uint4& v, uint32_t m) { return v.x == m || v.y == m || v.z == m || v.w == m; }
__device__ __forceinline__ uint32_t hadd2v(uint32_t a, uint32_t b) {
    uint32_t r; asm volatile("add.rn.bf16x2 %0, %1, %2;" : "=r"(r) : "r"(a), "r"(b)); return r;
}

__device__ __forceinline__ void red8h(uint4* p, uint32_t x, uint32_t y, uint32_t z, uint32_t w) {
    asm volatile("red.relaxed.gpu.global.add.noftz.v4.f16x2 [%0], {%1,%2,%3,%4};" ::"l"(p), "r"(x), "r"(y), "r"(z), "r"(w) : "memory");
}
__device__ __forceinline__ uint4 lds128v(uint32_t a) {
    uint4 v; asm volatile("ld.volatile.shared.v4.b32 {%0,%1,%2,%3}, [%4];" : "=r"(v.x), "=r"(v.y), "=r"(v.z), "=r"(v.w) : "r"(a) : "memory"); return v;
}
__device__ __forceinline__ uint32_t brow(int r) { return RD_B + r * 80 + (r >> 3) * 64; }

constexpr uint32_t PLACE = 0x1980;
__device__ __forceinline__ uint32_t acc_line(int k) { return (k >> 2) * 16384 + (k & 2) * 6144 + (k & 1) * 1024; }
__device__ __forceinline__ uint32_t acc_place(int side, int s) { return side * 4096 + (s & 1) * 256 + (s & 2) * 1024 + (s & 4) * 32; }

enum { B_QK = 1, B_QN = 2, B_GRP = 3  , B_Q = 5, B_MERGE = 6, B_ALL = 7, B_MAX = 8  , B_WARP = 10, B_SLOW = 12, B_PARK = 13, B_PLACE = 14, B_RDY = 15 };

__device__ __noinline__ void slow_rows(const char* __restrict__ f0, const char* __restrict__ f1, const __nv_bfloat16* __restrict__ q,
                                       const __nv_bfloat16* __restrict__ wq, const __nv_bfloat16* __restrict__ wk, const uint32_t sb)
{
    const int warp = threadIdx.x >> 5, lane = threadIdx.x & 31;
    float* const sm = reinterpret_cast<float*>(__cvta_shared_to_generic(sb + RD_W));
    for (int i = threadIdx.x; i < 2 * C; i += 128) sm[i] = __bfloat162float(q[(blockIdx.x & 14) * C + i]);
    bar_sync(B_SLOW, 128);
#pragma unroll 1
    for (int j = threadIdx.x; j < 2 * C; j += 128) {
        const float* const x = sm + j / C * C;
        float mu = 0.f, var = 0.f, s = 0.f;
#pragma unroll 1
        for (int i = 0; i < C; i++) mu += x[i];
        mu *= 1.f / C;
#pragma unroll 4
        for (int i = 0; i < C; i++) { var = fmaf(x[i] - mu, x[i] - mu, var); s = fmaf(x[i] - mu, __bfloat162float(wq[i * C + j % C]), s); }
        sm[4 * C + j] = s * rsq(var * (1.f / C) + 1e-5f);
    }
    bar_sync(B_SLOW, 128);
#pragma unroll 1
    for (int j = threadIdx.x; j < 2 * C; j += 128) {
        float s = 0.f;
#pragma unroll 4
        for (int i = 0; i < C; i++) s = fmaf(sm[4 * C + j / C * C + i], __bfloat162float(wk[j % C * C + i]), s);
        sm[j] = s * QSCALE;
    }
    bar_sync(B_SLOW, 128);
    float k[2][6], a[2][6], m[2], l[2];
#pragma unroll
    for (int r = 0; r < 2; r++) {
        m[r] = -INFINITY; l[r] = 0.f;
#pragma unroll
        for (int i = 0; i < 6; i++) { k[r][i] = sm[r * C + 64 * (i >> 1) + 2 * lane + (i & 1)]; a[r][i] = 0.f; }
    }
#pragma unroll 1
    for (int par = warp; par < W1 * W1; par += 4) {
        const uint32_t* p0 = reinterpret_cast<const uint32_t*>(f0 + (size_t)((par >> 8) * 2 * W0 + (par & 255) * 2) * (C * 2)) + lane;
        const uint32_t* p1 = reinterpret_cast<const uint32_t*>(f1 + (size_t)par * (C * 2)) + lane;
        uint32_t v[4][3];
#pragma unroll
        for (int i = 0; i < 3; i++)
#pragma unroll
            for (int j = 0; j < 4; j++) v[j][i] = hadd2(__ldg(p0 + ((j >> 1) * W0 + (j & 1)) * (C / 2) + 32 * i), __ldg(p1 + 32 * i));
#pragma unroll
        for (int j = 0; j < 4; j++) {
            float x[6], s1 = 0.f, s2 = 0.f, d[2] = {0.f, 0.f};
#pragma unroll
            for (int i = 0; i < 3; i++) { x[2 * i] = bflo(v[j][i]); x[2 * i + 1] = bfhi(v[j][i]); s1 += x[2 * i] + x[2 * i + 1]; }
#pragma unroll
            for (int o = 1; o < 32; o <<= 1) s1 += __shfl_xor_sync(~0u, s1, o);
#pragma unroll
            for (int i = 0; i < 6; i++) {
                x[i] -= s1 * (1.f / C); s2 = fmaf(x[i], x[i], s2);
#pragma unroll
                for (int r = 0; r < 2; r++) d[r] = fmaf(x[i], k[r][i], d[r]);
            }
#pragma unroll
            for (int o = 1; o < 32; o <<= 1) {
                s2 += __shfl_xor_sync(~0u, s2, o);
#pragma unroll
                for (int r = 0; r < 2; r++) d[r] += __shfl_xor_sync(~0u, d[r], o);
            }
            const float rs = rsq(s2 * (1.f / C) + 1e-5f);
#pragma unroll
            for (int r = 0; r < 2; r++) {
                const float nm = fmaxf(m[r], d[r] * rs), al = ex2(m[r] - nm), p = ex2(d[r] * rs - nm);
                m[r] = nm; l[r] = fmaf(l[r], al, p);
#pragma unroll
                for (int i = 0; i < 6; i++) a[r][i] = fmaf(a[r][i], al, x[i] * (p * rs));
            }
        }
    }
    bar_sync(B_SLOW, 128);
#pragma unroll
    for (int r = 0; r < 2; r++) {
        float* const o = sm + ((r * 4 + warp) * 32 + lane) * 8;
#pragma unroll
        for (int i = 0; i < 6; i++) o[i] = a[r][i];
        o[6] = l[r]; o[7] = m[r];
    }
    bar_sync(B_SLOW, 128);
    if (warp < 2) {
        const int r = warp;
        const float* const o = sm + (r * 128 + lane) * 8;
        float M = o[7], x[7] = {0.f, 0.f, 0.f, 0.f, 0.f, 0.f, 0.f};
#pragma unroll
        for (int w = 1; w < 4; w++) M = fmaxf(M, o[256 * w + 7]);
#pragma unroll
        for (int w = 0; w < 4; w++) {
            const float e = ex2(o[256 * w + 7] - M);
#pragma unroll
            for (int i = 0; i < 7; i++) x[i] = fmaf(o[256 * w + i], e, x[i]);
        }
        const float rl = 1.f / x[6];
        sts128(sb + RD_B2 + brow(8 * (lane >> 4) + 4 * r + (lane & 3)) + ((lane >> 2) & 3) * 16, packh(x[0] * rl, x[1] * rl), packh(x[2] * rl, x[3] * rl), packh(x[4] * rl, x[5] * rl), lane ? 0u : 0x3C00u);
    }
}

template <bool FIRST>
__device__ __forceinline__ void project(const uint32_t ar, const uint32_t br, const bool hi, const float ws0, const float ws1, const float qv0, const float qv1,
                                        __nv_bfloat16* op0, __nv_bfloat16* op1, Scratch* scr)
{
    uint4 wa[3][6], x[4];
#pragma unroll
    for (int i = 0; i < 18; i++) wa[i / 6][i % 6] = lds128v(ar + i * 512);
    if (FIRST) { bar_arrive(B_PLACE, NTHREADS); bar_sync(B_RDY, 192); }
    else bar_sync(B_SLOW, 128);
    if (FIRST && threadIdx.x == 0) TSX(8, 0);
#pragma unroll
    for (int j = 0; j < 4; j++) x[j] = lds128v(br + 16 * j);
    float o[7][4];
#pragma unroll
    for (int j = 0; j < 7; j++) o[j][0] = o[j][1] = o[j][2] = o[j][3] = 0.f;
#pragma unroll
    for (int i = 0; i < 2; i++) {
        mmah(o[6], 0x3C00u, 0x3C00u, 0x3C00u, 0x3C00u, x[2 * i].w, x[2 * i + 1].w);
#pragma unroll
        for (int n = 0; n < 3; n++) mmah(o[2 * n + i], wa[n][2 * i].x, wa[n][2 * i].y, wa[n][2 * i].z, wa[n][2 * i].w, x[2 * i].x, x[2 * i].y);
#pragma unroll
        for (int n = 0; n < 3; n++) mmah(o[2 * n + 1 - i], wa[n][2 * i + 1].x, wa[n][2 * i + 1].y, wa[n][2 * i + 1].z, wa[n][2 * i + 1].w, x[2 * i + 1].x, x[2 * i + 1].y);
#pragma unroll
        for (int n = 0; n < 3; n++) mmah(o[2 * n + i], wa[n][4 + i].x, wa[n][4 + i].y, wa[n][4 + i].z, wa[n][4 + i].w, x[2 * i].z, x[2 * i + 1].z);
    }
    const float L = o[6][0] + o[6][1], r = rcp(L);
    const float y0 = hi ? (o[2][0] + o[2][3]) + (o[3][0] + o[3][3]) : (o[0][0] + o[0][3]) + (o[1][0] + o[1][3]), y1 = (o[4][0] + o[4][3]) + (o[5][0] + o[5][3]);
    const uint32_t y = pack2(fmaf(y0, r * ws0, qv0), fmaf(y1, r * ws1, qv1));
    asm volatile("{.reg .b16 l, h; mov.b32 {l, h}, %2; st.global.b16 [%0], l; st.global.b16 [%1], h;}" ::"l"(op0), "l"(op1), "r"(y) : "memory");
    if (FIRST && threadIdx.x == 0) TSD(11, y);
    if (FIRST)
        asm volatile("{.reg .pred p; .reg .f32 a; abs.f32 a, %1; setp.ge.f32 p, %0, 0f3B000000; setp.le.and.f32 p, %0, 0f45000000, p; setp.lt.and.f32 p, a, 0f7F800000, p;"
                     " vote.sync.all.pred p, p, 0xffffffff; @p exit;}" ::"f"(L), "f"(y0) : "memory");
}

__device__ __forceinline__ void reducer(const char* __restrict__ f0, const char* __restrict__ f1, const __nv_bfloat16* __restrict__ q, const __nv_bfloat16* __restrict__ wq, const __nv_bfloat16* __restrict__ wk,
                                        Scratch* scr, const __nv_bfloat16* __restrict__ wv, const __nv_bfloat16* __restrict__ wo,
                                        __nv_bfloat16* __restrict__ out, const uint32_t sb, const int GS)
{
    const int warp = threadIdx.x >> 5, lane = threadIdx.x & 31, b = blockIdx.x;
    const int g = lane >> 2, t = lane & 3;
    char* const ap = reinterpret_cast<char*>(g_acc);
    if (threadIdx.x == 256) TS(0);
    if (b < NSRC && warp < 8) {
        const uint32_t wqs = sb + RD_W, wbar = sb + RD_BAR;
        const int hr = lane >> 4, qt = (lane >> 2) & 3, sub = lane & 3;
        const uint32_t* qp = reinterpret_cast<const uint32_t*>(q + (warp + 8 * hr) * C + 48 * qt + 6 * sub);
        uint32_t qw[6];
#pragma unroll
        for (int j = 0; j < 3; j++) { qw[j] = __ldg(qp + j); qw[3 + j] = __ldg(qp + 12 + j); }
        if (lane == 0) { mbar_init(wbar + warp * 8, 1); asm volatile("fence.mbarrier_init.release.cluster;" ::: "memory"); mbar_expect(wbar + warp * 8, 9216);
            asm volatile("cp.async.bulk.shared::cluster.global.mbarrier::complete_tx::bytes [%0], [%1], 9216, [%2];"
                         ::"r"(wqs + warp * 9232), "l"(wq + 24 * warp * C), "r"(wbar + warp * 8) : "memory");
        }
        __syncwarp();
        if (threadIdx.x == 0) TSP(2, 0);
        float e[12];
#pragma unroll
        for (int j = 0; j < 6; j++) { e[2 * j] = bflo(qw[j]); e[2 * j + 1] = bfhi(qw[j]); }
        float sm = ((e[0] + e[1]) + (e[2] + e[3])) + ((e[4] + e[5]) + (e[6] + e[7])) + ((e[8] + e[9]) + (e[10] + e[11]));
#pragma unroll
        for (int o = 1; o < 16; o <<= 1) sm += __shfl_xor_sync(~0u, sm, o);
        if (threadIdx.x == 0) TSP(5, u(sm));
        float v0 = 0.f, v1 = 0.f;
#pragma unroll
        for (int j = 0; j < 12; j++) e[j] -= sm * (1.f / C);
#pragma unroll
        for (int j = 0; j < 6; j++) { v0 = fmaf(e[j], e[j], v0); v1 = fmaf(e[6 + j], e[6 + j], v1); }
        v0 += v1;
#pragma unroll
        for (int o = 1; o < 16; o <<= 1) v0 += __shfl_xor_sync(~0u, v0, o);
        const float rq = rsq(v0 * (1.f / C) + 1e-5f);
#pragma unroll
        for (int j = 0; j < 6; j++)
            sts32(sb + RD_QN + (3 * sub + (j >> 1)) * 512 + (4 * warp + qt) * 16 + (2 * (j & 1) + hr) * 4, pack2(e[j] * rq, e[6 + j] * rq));
        if (threadIdx.x == 0) TSP(8, 0);
        uint32_t wkf[2][3];
#pragma unroll
        for (int i = 0; i < 2; i++)
#pragma unroll
            for (int j = 0; j < 3; j++) wkf[i][j] = __ldg(reinterpret_cast<const uint32_t*>(wk + (16 * b + 8 * i + g) * C + 24 * warp + 8 * j + 2 * t));
        bar_sync(B_QN, 256);
        float acc[2][3][4];
#pragma unroll
        for (int i = 0; i < 3; i++)
#pragma unroll
            for (int e = 0; e < 4; e++) acc[0][i][e] = acc[1][i][e] = 0.f;
        const uint32_t ba = wqs + (lane & 7) * 9232 + (lane >> 3) * 384 + 48 * warp;
        uint4 a[12];
#pragma unroll
        for (int kk = 0; kk < 12; kk++) a[kk] = lds128(sb + RD_QN + kk * 512 + lane * 16);
        mbar_wait(wbar + (lane & 7) * 8, 0);
        __syncwarp();
        if (threadIdx.x == 0) TSP(4, 0);
#pragma unroll
        for (int kp = 0; kp < 6; kp++)
#pragma unroll
            for (int i = 0; i < 3; i++) {
                uint32_t bb[4];
                ldsm4t(bb, ba + kp * 1536 + i * 16);
                mma(acc[0][i], a[2 * kp].x, a[2 * kp].y, a[2 * kp].z, a[2 * kp].w, bb[0], bb[1]);
                mma(acc[1][i], a[2 * kp + 1].x, a[2 * kp + 1].y, a[2 * kp + 1].z, a[2 * kp + 1].w, bb[2], bb[3]);
            }
        if (threadIdx.x == 0) TSP(7, u(acc[1][2][3]));
        float kq[2][4] = {{0.f, 0.f, 0.f, 0.f}, {0.f, 0.f, 0.f, 0.f}};
#pragma unroll
        for (int j = 0; j < 3; j++) {
            const uint32_t a0 = pack2(acc[0][j][0] + acc[1][j][0], acc[0][j][1] + acc[1][j][1]), a1 = pack2(acc[0][j][2] + acc[1][j][2], acc[0][j][3] + acc[1][j][3]);
            mma8(kq[0], a0, a1, wkf[0][j]);
            mma8(kq[1], a0, a1, wkf[1][j]);
        }
        if (warp < 7) {
            sts128(sb + RD_KQ + warp * 1024 + lane * 16, u(kq[0][0]), u(kq[0][1]), u(kq[0][2]), u(kq[0][3]));
            sts128(sb + RD_KQ + warp * 1024 + 512 + lane * 16, u(kq[1][0]), u(kq[1][1]), u(kq[1][2]), u(kq[1][3]));
            bar_arrive(B_Q, 256);
        } else {
            bar_sync(B_Q, 256);
#pragma unroll
            for (int w = 0; w < 7; w++)
#pragma unroll
                for (int i = 0; i < 2; i++) {
                    const uint4 o = lds128(sb + RD_KQ + w * 1024 + i * 512 + lane * 16);
                    kq[i][0] += f(o.x); kq[i][1] += f(o.y); kq[i][2] += f(o.z); kq[i][3] += f(o.w);
                }
            stg_relaxed(g_qk + b * 32 + lane, ~pack2(kq[0][0] * QSCALE, kq[0][1] * QSCALE), ~pack2(kq[0][2] * QSCALE, kq[0][3] * QSCALE),
                        ~pack2(kq[1][0] * QSCALE, kq[1][1] * QSCALE), ~pack2(kq[1][2] * QSCALE, kq[1][3] * QSCALE));
            if (lane == 0) TS(10);
        }
    } else if (warp == 8 && !(b & 1)) {
        char* const pp = ap + (b >> 2) * 8192 + (b & 2) * 512;
        if (lane < 16) stg_relaxed(reinterpret_cast<uint4*>(pp + (lane >> 3) * 4096) + (lane & 7), 0, 0, 0, 0);
        __syncwarp();
        uint32_t place = 0;
        if (lane == 0) {
            uint32_t best[2] = {~0u, ~0u};
#pragma unroll 1
            for (int it = 0; it < NPROBE; it++) {
#pragma unroll
                for (int i = 0; i < 2; i++) {
                    uint32_t c;
                    asm volatile("{.reg .b32 v, c0; .reg .pred p; mov.u32 c0, %%clock; atom.relaxed.gpu.global.exch.b32 v, [%1], 0; setp.ne.u32 p, v, 0; @p trap;"
                                 " mov.u32 %0, %%clock; sub.u32 %0, %0, c0;}" : "=r"(c) : "l"(pp + i * 4096) : "memory");
                    best[i] = min(best[i], c);
                }
            }
            int side = (best[1] < best[0]) ^ ((b >> 2) & 1);
            place = acc_place(side, b >> 1);
            sts32(sb + RD_PLACE, place);
        }
        place = __shfl_sync(~0u, place, 0);
#pragma unroll
        for (int i = 0; i < 2; i++) stg_relaxed(reinterpret_cast<uint4*>(ap + (acc_line(4 * i + (lane >> 3)) ^ place)) + (lane & 7), 0, 0, 0, 0);
        __threadfence();
    } else if (b >= NSRC) {
        if (b == NSRC && warp == 0) stg_relaxed32(g_mmax + lane, 0);
        __nanosleep(2500);
    }
    bar_sync(B_ALL, NTHREADS);

#pragma unroll 1
    for (int r = 0; r < 3; r++) {
        uint4 v[8];
#pragma unroll
        for (int k = 0; k < 8; k++) {
            const int idx = (8 * r + k) * 384 + threadIdx.x;
            v[k] = __ldg(reinterpret_cast<const uint4*>(idx < 4608 ? wv : wo - C * C) + idx);
        }
#pragma unroll
        for (int k = 0; k < 8; k++) {
            const int idx = (8 * r + k) * 384 + threadIdx.x, row = idx / 24;
            sts128(sb + RD_W + row * WROW + (idx - 24 * row) * 16, v[k].x, v[k].y, v[k].z, v[k].w);
        }
    }
    bar_sync(B_ALL, NTHREADS);
    if (warp < 6) {
        const int col = 96 * (b & 1) + 16 * warp;
        float d[24][4];
#pragma unroll
        for (int i = 0; i < 24; i++) d[i][0] = d[i][1] = d[i][2] = d[i][3] = 0.f;
        const int mi = lane >> 3, r = lane & 7;
        const uint32_t aa = sb + RD_W + (C + (mi >> 1) * 8 + r) * WROW + (col + (mi & 1) * 8) * 2;
        const uint32_t ba = sb + RD_W + ((mi >> 1) * 8 + r) * WROW + (mi & 1) * 16;
#pragma unroll 1
        for (int kk = 0; kk < 12; kk++) {
            uint32_t a[4];
            ldsm4t(a, aa + kk * 16 * WROW);
#pragma unroll
            for (int i = 0; i < 12; i++) {
                uint32_t bb[4];
                ldsm4(bb, ba + i * 16 * WROW + kk * 32);
                mma(d[2 * i], a[0], a[1], a[2], a[3], bb[0], bb[1]);
                mma(d[2 * i + 1], a[0], a[1], a[2], a[3], bb[2], bb[3]);
            }
        }
        float c0 = 0.f, c1 = 0.f, m0 = 0.f, m1 = 0.f;
#pragma unroll
        for (int i = 0; i < 24; i++) { c0 += d[i][0] + d[i][1]; c1 += d[i][2] + d[i][3]; }
        c0 += __shfl_xor_sync(~0u, c0, 1); c1 += __shfl_xor_sync(~0u, c1, 1);
        c0 += __shfl_xor_sync(~0u, c0, 2); c1 += __shfl_xor_sync(~0u, c1, 2);
        c0 *= 1.f / C; c1 *= 1.f / C;
#pragma unroll
        for (int i = 0; i < 24; i++) {
            d[i][0] -= c0; d[i][1] -= c0; d[i][2] -= c1; d[i][3] -= c1;
            m0 = fmaxf(m0, fmaxf(fabsf(d[i][0]), fabsf(d[i][1]))); m1 = fmaxf(m1, fmaxf(fabsf(d[i][2]), fabsf(d[i][3])));
        }
        m0 = fmaxf(m0, __shfl_xor_sync(~0u, m0, 1)); m1 = fmaxf(m1, __shfl_xor_sync(~0u, m1, 1));
        m0 = fmaxf(m0, __shfl_xor_sync(~0u, m0, 2)); m1 = fmaxf(m1, __shfl_xor_sync(~0u, m1, 2));
        const uint32_t e0 = min(max(u(m0) >> 23, 12u), 254u), e1 = min(max(u(m1) >> 23, 12u), 254u);
        const float s0 = f((265u - e0) << 23), s1 = f((265u - e1) << 23);
        const bool k0 = fabsf(c0) < INFINITY, k1 = fabsf(c1) < INFINITY;
#pragma unroll
        for (int j = 0; j < 6; j++) {
            const int n[4] = {j < 4 ? j : 8 + 2 * j, j < 4 ? 4 + j : 12 + 2 * j, j < 4 ? 8 + j : 9 + 2 * j, j < 4 ? 12 + j : 13 + 2 * j};
            uint32_t a[2][4];
#pragma unroll
            for (int e = 0; e < 4; e++) {
                a[0][e] = k0 ? packh(d[n[e]][0] * s0, d[n[e]][1] * s0) : 0u;
                a[1][e] = k1 ? packh(d[n[e]][2] * s1, d[n[e]][3] * s1) : 0u;
            }
#pragma unroll
            for (int e = 0; e < 2; e++) sts128(sb + RD_A + ((2 * warp + e) * 6 + j) * 512 + lane * 16, a[e][0], a[e][1], a[e][2], a[e][3]);
        }
        sts32(sb + RD_WS + 2 * warp * 128 + lane * 4, k0 ? (e0 - 11u) << 23 : u(c0));
        sts32(sb + RD_WS + (2 * warp + 1) * 128 + lane * 4, k1 ? (e1 - 11u) << 23 : u(c1));
        if (warp < 4) bar_sync(B_PARK, 192); else bar_arrive(B_PARK, 192);
        if (threadIdx.x == 0) TSE(6);
    }
    if (warp >= 4) {
        if (threadIdx.x == 128) {
            uint32_t m, place = lds32(sb + RD_PLACE);
            for (int it = 0;; it++) {
                const int left = NT - 2 * NST * GS - (int)ldg_relaxed32(g_ctr);
                m = ldg_relaxed32(g_mmax + b);
                if (left <= REFT && m) break;
                if (left <= 0) { m = 0x80000000u; break; }
                if (it > SPIN_LIMIT) __trap();
                __nanosleep(300);
            }
            if (b & 1) for (int it = 0;; it++) {
                uint32_t r;
                asm volatile("ld.acquire.gpu.global.u32 %0, [%1];" : "=r"(r) : "l"(g_mref + b - 1) : "memory");
                place = ~r & PLACE;
                if (r) break;
                if (it > SPIN_LIMIT) __trap();
            }
            asm volatile("st.release.gpu.global.u32 [%0], %1;" ::"l"(g_mref + b), "r"(~((u(f(m >> 31 ? m ^ 0x80000000u : ~m) + 8.f) & ~PLACE) | place)) : "memory");
            sts32(sb + RD_PLACE, place);
            TSE(7);
        }
        __syncwarp();
        if (warp == 4) {
            uint4* p0 = g_qk + min(b, NSRC - 1) * 32 + lane;
            unsigned* p1 = lane == 1 && b == NSRC ? g_ctr : g_mref + b;
            asm volatile("" : "+l"(p0), "+l"(p1));
            bar_arrive(B_PLACE, NTHREADS);
            bar_sync(B_RDY, 192);
            *p0 = make_uint4(0, 0, 0, 0);
            *p1 = 0;
            return;
        }
        bar_sync(B_PLACE, NTHREADS);
        if (warp >= 5 + NPW) return;
        const uint32_t place = lds32(sb + RD_PLACE);
        const uint4* const pa = reinterpret_cast<const uint4*>(ap + (acc_line(lane >> 3) ^ place)) + (lane & 7);
        const uint32_t bw = opaque(sb + brow(lane & 7) + (lane >> 3) * 16);
        const uint32_t n0 = packh(0.f, (float)GS), nstart = packh(0.f, (float)POLLN);
        for (int it = 0; ldg_relaxed32(ap + place + 12) < nstart; it++)
            if (it > SPIN_LIMIT) __trap();
        for (const unsigned c = clock32(); clock32() - c < (warp - 5) * PGAP;) {}
        for (int it = 0;; it++) {
            const uint4 a0 = ldg_relaxed(pa), b0 = ldg_relaxed(pa + 1024);
            if (it > SPIN_LIMIT) __trap();
            bar_sync(B_WARP, 32);
            asm volatile("{.reg .pred p, q; .reg .b32 a; setp.ge.u32 p, %5, %10; setp.ge.and.u32 p, %9, %10, p; vote.sync.all.pred q, p, 0xffffffff; selp.b32 a, %0, %1, p;"
                         " st.shared.v4.b32 [a], {%2,%3,%4,%5}; st.shared.v4.b32 [a + 704], {%6,%7,%8,%9}; @q bar.arrive 15, 192; @q exit;}"
                         ::"r"(bw), "r"(bw - (RD_B - RD_QN)), "r"(a0.x), "r"(a0.y), "r"(a0.z), "r"(a0.w), "r"(b0.x), "r"(b0.y), "r"(b0.z), "r"(b0.w), "r"(n0) : "memory");
        }
    }
    const uint32_t br = opaque(sb + brow(8 * (g & 1) + 2 * (g & 2) + t));
    const bool hi = t >= 2;
    const int oi = ((b & 14) + (t & 1)) * C + 96 * (b & 1) + 24 * warp + g;
    const float qv0 = __bfloat162float(q[oi + 4 * (t & 2)]), qv1 = __bfloat162float(q[oi + 16]);
    const float ws0 = f(lds32(sb + RD_WS + (3 * warp + (t >> 1)) * 128 + lane * 4)), ws1 = f(lds32(sb + RD_WS + (3 * warp + 2) * 128 + lane * 4));
    __nv_bfloat16* op0 = out + oi + 4 * (t & 2), * op1 = out + oi + 16;
    asm volatile("" : "+l"(op0), "+l"(op1));
    const uint32_t ar = sb + RD_A + warp * 18 * 512 + lane * 16;
    project<true>(ar, br, hi, ws0, ws1, qv0, qv1, op0, op1, scr);
    slow_rows(f0, f1, q, wq, wk, sb);
    project<false>(ar, br + RD_B2, hi, ws0, ws1, qv0, qv1, op0, op1, scr);
}

__global__ void __launch_bounds__(NTHREADS, 1)
attn_main(const char* __restrict__ f0, const char* __restrict__ f1,
          const __nv_bfloat16* __restrict__ q, const __nv_bfloat16* __restrict__ wq, const __nv_bfloat16* __restrict__ wk, Scratch* scr,
          const __nv_bfloat16* __restrict__ wv, const __nv_bfloat16* __restrict__ wo, __nv_bfloat16* __restrict__ out,
          const __grid_constant__ CUtensorMap m0, const __grid_constant__ CUtensorMap m1)
{
    extern __shared__ char smem_raw[];
    const uint32_t sb = (s2u(smem_raw) + 1023u) & ~1023u;
    const int G = gridDim.x - NRD;
    const int b = blockIdx.x - NRD;
    if (threadIdx.x == 0 && b >= 0) {
        const char* a = f0 + (uint32_t)(b * (4 * TP * C * 2) + (b >> 4) * (W0 * C * 2));
        prefetch_l2(a, 4 * TP * C * 2);
        prefetch_l2(a + W0 * C * 2, 4 * TP * C * 2);
        prefetch_l2(f1 + b * (2 * TP * C * 2), 2 * TP * C * 2);
        prefetch_l2((const char*)(b % (2 * WSL) < WSL ? wq : wk) + b % WSL * (C * C * 2 / WSL), C * C * 2 / WSL);
    }
    if (b < 0) { reducer(f0, f1, q, wq, wk, scr, wv, wo, out, sb, G); return; }
    const int warp = __shfl_sync(~0u, threadIdx.x >> 5, 0), lane = threadIdx.x & 31;
    const int g = lane >> 2, t = lane & 3;

    if (warp >= 8) {
        if (warp < 10) {
            const int p = warp - 8;
            const unsigned c0 = clock32();
            const uint32_t sbp = opaque(sb), bar = sbp + SM_BAR + p * 8;
            uint64_t pol; asm volatile("createpolicy.fractional.L2::evict_first.b64 %0, 1.0;" : "=l"(pol));
            if (elect()) {
                if (p == 0) TS(0);
                asm volatile("prefetch.tensormap [%0];" ::"l"(p ? &m1 : &m0) : "memory");
#pragma unroll
                for (int n = 0; n < NI; n++) mbar_init(bar + n * 16, 2);
                asm volatile("fence.mbarrier_init.release.cluster;" ::: "memory");
#pragma unroll
                for (int n = 0; n < NI; n++) {
                    issue_tile(&m0, &m1, sbp, p + 2 * n, 2 * b + p + 2 * n * G, pol);
                    TR(0, 2 * n + p);
                    sts32(sbp + SM_FLAG + (p + 2 * n) * 4, 0);
                    mbar_arrive(bar + n * 16);
                }
#pragma unroll
                for (int n = 0; n < NS / 2; n++) {
                    if (n >= NI) mbar_init(bar + n * 16, 2);
                    mbar_init(bar + NS * 8 + n * 16, 1);
                }
                if (p == 0) mbar_init(sbp + SM_REF, 1);
                asm volatile("fence.mbarrier_init.release.cluster;" ::: "memory");
            }
            __syncwarp();
            bar_arrive(B_QK, NTHREADS);
            if (elect()) {
                int tl = 2 * b + p + 2 * NI * G;
                int s = p + 2 * NI; uint32_t ph = 1;
                int sa = p, na = 0; uint32_t pa = 0;
                bool late = false;
                for (int n = NI;; n++) {
                    const int d = n < NRAMP ? D0 : (tl >= NT - TAILT ? D2 : D1);
                    while (n - na >= d) {
                        mbar_wait(sbp + SM_BAR + sa * 8, pa);
                        if (na < NS / 2) TR(1, 2 * na + p);
                        na++; sa += 2;
                        if (sa >= NS) { sa -= NS; pa ^= 1; }
                    }
                    mbar_wait(sbp + SM_BAR + (NS + s) * 8, ph);
                    if (n < NPACE) while (clock32() - c0 < (n ? T1 + (2 * (n - 1) + p) * TG : T0)) {}
                    issue_tile(&m0, &m1, sbp, s, tl, pol);
                    TR(0, 2 * n + p);
                    int nxt = tl + 2 * G;
                    if (n >= NST - 1) nxt = grab_tile(g_ctr) + 2 * NST * G;
                    const bool last = nxt >= NT;
                    uint32_t flag = last;
                    if (!late && nxt >= NT - MAXT - 16 * b) { late = true; flag |= 2; }
                    if (last) mbar_wait(sbp + SM_REF, 0);
                    sts32(sbp + SM_FLAG + s * 4, flag);
                    mbar_arrive(sbp + SM_BAR + s * 8);
                    if (last) break;
                    s += 2;
                    if (s >= NS) { s -= NS; ph ^= 1; }
                    tl = nxt;
                }
                if (p) TSE(5);
            }
            return;
        }
        const int h = threadIdx.x - 320;
        uint4 v[6];
        for (int it = 0;; it++) {
            bool miss = false;
#pragma unroll
            for (int k = 0; k < 6; k++) v[k] = ldg_relaxed(g_qk + k * 64 + h);
#pragma unroll
            for (int k = 0; k < 6; k++) miss |= has(v[k], 0);
            if (!miss) break;
            if (it > SPIN_LIMIT) __trap();
            if (it == 0) __nanosleep(QSLEEP);
        }
#pragma unroll
        for (int k = 0; k < 6; k++) sts128(sb + SM_QK + (k * 64 + h) * 16, ~v[k].x, ~v[k].y, ~v[k].z, ~v[k].w);
        __syncwarp();
        bar_sync(B_QK, NTHREADS);
        if (warp == 11) return;
        uint32_t r = 1;
        for (int it = 0;; it++) {
            __nanosleep(500);
            if (lane < NQ) asm volatile("ld.acquire.gpu.global.u32 %0, [%1];" : "=r"(r) : "l"(g_mref + lane) : "memory");
            if (__all_sync(~0u, r != 0)) break;
            if (it > SPIN_LIMIT) __trap();
        }
        if (lane < NQ) sts32(sb + SM_M + lane * 4, ~r);
        __syncwarp();
        if (lane == 0) { mbar_arrive(sb + SM_REF); TSE(7); }
        return;
    }

    const int grp = warp >> 2, cw = warp & 3;
    const int xp = lane & 7, mi = lane >> 3;
    const uint32_t offS1 = opaque(12288 + xp * 128 + ((mi ^ xp) << 4)), offS1x = opaque(offS1 ^ 64);
    const uint32_t offS0 = opaque(offS1 - 12288 + cw * 3072), offS0x = opaque(offS0 ^ 64);
    const uint32_t offT = opaque(mi * 3072 + xp * 128 + (((cw + 4 * grp) ^ xp) << 4)), offTx = opaque(offT ^ 64);
    const uint32_t offU = opaque(12288 + (mi % 3) * 1024 + xp * 128 + (((cw + 4 * (grp ^ (mi / 3))) ^ xp) << 4));
    const uint32_t offV = opaque(12288 + (1 + (mi & 1)) * 1024 + xp * 128 + (((cw + 4 * (grp ^ 1)) ^ xp) << 4));
    const int shl = opaque(9 * t), shl4 = opaque(9 * t + 4);
    const uint32_t pw = opaque((cw >> 1) * 512 + lane * 16 + (cw & 1) * 8), muw = opaque(1024 + t * 16 + cw * 4);
    const uint32_t prd = opaque(lane * 16), mur = opaque(1024 + t * 16), mof = g * 4;
    uint32_t pb0 = sb + SM_P + grp * 2 * PBUF;
    const uint32_t pbx = pb0 ^ (pb0 + PBUF);
    const bool odd = g & 1;
    const int barid = B_GRP + grp;
    const bool elected = cw == 3 && lane == 0;

    uint32_t qa[48];
    float r_lo, r_hi;
    bar_sync(B_QK, NTHREADS);
    {
        float rr[2][4] = {{0.f, 0.f, 0.f, 0.f}, {0.f, 0.f, 0.f, 0.f}};
#pragma unroll
        for (int kk = 0; kk < 12; kk++) {
            const uint4 v = lds128(sb + SM_QK + kk * 512 + lane * 16);
            qa[4 * kk] = v.x; qa[4 * kk + 1] = v.y; qa[4 * kk + 2] = v.z; qa[4 * kk + 3] = v.w;
            mma(rr[kk & 1], v.x, v.y, v.z, v.w, ONES, ONES);
        }
        r_lo = rr[0][0] + rr[1][0]; r_hi = rr[0][2] + rr[1][2];
    }
    if (threadIdx.x == 0) TS(1);

    float acc[6][4];
#pragma unroll
    for (int i = 0; i < 6; i++) acc[i][0] = acc[i][1] = acc[i][2] = acc[i][3] = 0.f;
    float m_lo = -INFINITY, m_hi = -INFINITY, l_lo = 0.f, l_hi = 0.f;
    float cm[4] = {0.f, 0.f, 0.f, 0.f};
    uint32_t xt[6][4], yt[6]; uint4 pa, pb, mv;
    const uint32_t dof = opaque(acc_line(warp) + (lane & 7) * 16);
    int s = grp; uint32_t ph = 0;
    while (true) {
        mbar_wait(sb + SM_BAR + s * 8, ph);
        PH(0, 0);
        const uint32_t stop = lds32(sb + SM_FLAG + s * 4);
        const uint32_t st = sb + SM_STAGES + s * STAGE;
        float sc[2][4], gr[4][4], sx[4];
#pragma unroll
        for (int e = 0; e < 4; e++) sc[0][e] = sc[1][e] = gr[0][e] = gr[1][e] = gr[2][e] = gr[3][e] = sx[e] = 0.f;
#pragma unroll
        for (int qq = 0; qq < 6; qq++) {
            uint32_t x[4], y[4];
            ldsm4(x, st + (qq & 1 ? offS0x : offS0) + (qq >> 1) * 1024);
            ldsm4(y, st + (qq & 1 ? offS1x : offS1) + (qq >> 1) * 1024);
#pragma unroll
            for (int e = 0; e < 4; e++) x[e] = hadd2(x[e], y[e]);
            mma8(gr[0], x[0], x[1], x[0]);
            mma8(gr[1], x[0], x[1], x[1]);
            mma(sx, x[0], x[1], x[2], x[3], ONES, ONES);
            mma8(gr[GR4 ? 2 : 0], x[2], x[3], x[2]);
            mma8(gr[GR4 ? 3 : 1], x[2], x[3], x[3]);
            mma(sc[0], qa[8 * qq], qa[8 * qq + 1], qa[8 * qq + 2], qa[8 * qq + 3], x[0], x[1]);
            mma(sc[1], qa[8 * qq + 4], qa[8 * qq + 5], qa[8 * qq + 6], qa[8 * qq + 7], x[2], x[3]);
        }
        ldsm4t(yt, st + offU);
        ldsm2t(yt + 4, st + offV);
#pragma unroll
        for (int i = 0; i < 6; i++) ldsm4t(xt[i], st + (i < 3 ? offT : offTx) + (i % 3) * 1024);

        const float mu = (sx[0] + sx[2]) * (1.f / C), ss = GR4 ? (odd ? (gr[0][1] + gr[1][3]) + (gr[2][1] + gr[3][3]) : (gr[0][0] + gr[1][2]) + (gr[2][0] + gr[3][2])) : (odd ? gr[0][1] + gr[1][3] : gr[0][0] + gr[1][2]);
        const float rs = rsq(fmaxf(fmaf(-mu, mu, fmaf(ss, 1.f / C, 1e-5f)), 1e-5f));
        const float mu0 = __shfl_sync(~0u, mu, shl), mu1 = __shfl_sync(~0u, mu, shl4);
        const float rs0 = __shfl_sync(~0u, rs, shl), rs1 = __shfl_sync(~0u, rs, shl4);
        const float u0 = fmaf(-mu0, r_lo, sc[0][0] + sc[1][0]), u1 = fmaf(-mu1, r_lo, sc[0][1] + sc[1][1]);
        const float u2 = fmaf(-mu0, r_hi, sc[0][2] + sc[1][2]), u3 = fmaf(-mu1, r_hi, sc[0][3] + sc[1][3]);
        const float d0 = fmaf(u0, rs0, -m_lo), d1 = fmaf(u1, rs1, -m_lo), d2 = fmaf(u2, rs0, -m_hi), d3 = fmaf(u3, rs1, -m_hi);
        PH(1, u(d0 + d2));
        float p0 = ex2(d0), p1 = ex2(d1), p2 = ex2(d2), p3 = ex2(d3);
        sts64(pb0 + pw, pack2(p0 * rs0, p1 * rs1), pack2(p2 * rs0, p3 * rs1));
        if (lane < 4) sts32(pb0 + muw, pack2(mu0, mu1));
        const bool over = bar_any(barid, 128, fmaxf(fmaxf(d0, d1), fmaxf(d2, d3)) > LAZY);
        PH(3, 0);
        pa = lds128(pb0 + prd); pb = lds128(pb0 + prd + 512); mv = lds128(pb0 + mur);
        if (elected) mbar_arrive(sb + SM_BAR + (NS + s) * 8);
        if (__builtin_expect(over, 0)) {
            const float s0 = u0 * rs0, s1 = u1 * rs1, s2 = u2 * rs0, s3 = u3 * rs1;
            float xl = fmaxf(s0, s1), xh = fmaxf(s2, s3);
            xl = fmaxf(xl, __shfl_xor_sync(~0u, xl, 1)); xh = fmaxf(xh, __shfl_xor_sync(~0u, xh, 1));
            xl = fmaxf(xl, __shfl_xor_sync(~0u, xl, 2)); xh = fmaxf(xh, __shfl_xor_sync(~0u, xh, 2));
            if (t < 2) sts32(sb + SM_MX + grp * 256 + ((g + 8 * t) * 4 + cw) * 4, u(t ? xh : xl));
            bar_sync(B_MAX + grp, 128);
            const uint4 ml4 = lds128(sb + SM_MX + grp * 256 + g * 16), mh4 = lds128(sb + SM_MX + grp * 256 + g * 16 + 128);
            const float nl = fmaxf(fmaxf(fmaxf(f(ml4.x), f(ml4.y)), fmaxf(f(ml4.z), f(ml4.w))), m_lo);
            const float nh = fmaxf(fmaxf(fmaxf(f(mh4.x), f(mh4.y)), fmaxf(f(mh4.z), f(mh4.w))), m_hi);
            p0 = ex2(s0 - nl); p1 = ex2(s1 - nl); p2 = ex2(s2 - nh); p3 = ex2(s3 - nh);
            sts64(pb0 + pw, pack2(p0 * rs0, p1 * rs1), pack2(p2 * rs0, p3 * rs1));
            const float al = ex2(m_lo - nl), ah = ex2(m_hi - nh);
            m_lo = nl; m_hi = nh;
            l_lo *= al; l_hi *= ah; cm[0] *= al; cm[2] *= ah;
#pragma unroll
            for (int i = 0; i < 6; i++) { acc[i][0] *= al; acc[i][1] *= al; acc[i][2] *= ah; acc[i][3] *= ah; }
            bar_sync(B_MAX + grp, 128);
            pa = lds128(pb0 + prd); pb = lds128(pb0 + prd + 512);
        }
        l_lo += p0 + p1; l_hi += p2 + p3;
        if (stop & 1) break;
#pragma unroll
        for (int i = 0; i < 6; i++) mma(acc[i], pa.x, pa.y, pa.z, pa.w, hadd2v(xt[i][0], yt[i]), hadd2v(xt[i][1], yt[i]));
        mma(cm, pa.x, pa.y, pa.z, pa.w, mv.x, mv.y);
#pragma unroll
        for (int i = 0; i < 6; i++) mma(acc[i], pb.x, pb.y, pb.z, pb.w, hadd2v(xt[i][2], yt[i]), hadd2v(xt[i][3], yt[i]));
        mma(cm, pb.x, pb.y, pb.z, pb.w, mv.z, mv.w);
        PH(4, u(acc[5][0]));
        if (stop) {
            float a = l_lo + __shfl_xor_sync(~0u, l_lo, 1), c = l_hi + __shfl_xor_sync(~0u, l_hi, 1);
            a += __shfl_xor_sync(~0u, a, 2); c += __shfl_xor_sync(~0u, c, 2);
            const uint32_t m = u((t ? m_hi : m_lo) + lg2(fmaxf(t ? c : a, 1.f)));
            if (t < 2) asm volatile("red.relaxed.gpu.global.max.u32 [%0], %1;" ::"l"(g_mmax + g + 8 * t), "r"(m >> 31 ? ~m : m | 0x80000000u) : "memory");
        }
        pb0 ^= pbx;
        s += 2;
        if (s >= NS) { s -= NS; ph ^= 1; }
    }
    const uint32_t ref_lo = lds32(sb + SM_M + mof), ref_hi = lds32(sb + SM_M + 32 + mof);
    const float al = ex2(m_lo - f(ref_lo)), ah = ex2(m_hi - f(ref_hi));
    mma(cm, pa.x, pa.y, pa.z, pa.w, mv.x, mv.y);
#pragma unroll
    for (int i = 3; i < 6; i++) mma(acc[i], pa.x, pa.y, pa.z, pa.w, hadd2v(xt[i][0], yt[i]), hadd2v(xt[i][1], yt[i]));
    mma(cm, pb.x, pb.y, pb.z, pb.w, mv.z, mv.w);
#pragma unroll
    for (int i = 3; i < 6; i++) mma(acc[i], pb.x, pb.y, pb.z, pb.w, hadd2v(xt[i][2], yt[i]), hadd2v(xt[i][3], yt[i]));
#pragma unroll
    for (int i = 0; i < 3; i++) mma(acc[i], pa.x, pa.y, pa.z, pa.w, hadd2v(xt[i][0], yt[i]), hadd2v(xt[i][1], yt[i]));
#pragma unroll
    for (int i = 0; i < 3; i++) mma(acc[i], pb.x, pb.y, pb.z, pb.w, hadd2v(xt[i][2], yt[i]), hadd2v(xt[i][3], yt[i]));
    if (threadIdx.x == grp * 128) TSE(2 + grp);
    if (threadIdx.x == grp * 128 + 96) TSX(2 + grp, u(acc[5][0]));

    uint4* const dst = reinterpret_cast<uint4*>(reinterpret_cast<char*>(g_acc) + (dof ^ (ref_lo & PLACE)));
    uint4* const dsu = reinterpret_cast<uint4*>(reinterpret_cast<char*>(g_acc) + (dof ^ (ref_hi & PLACE)));
    const uint32_t xw = sb + SM_STAGES + grp * STAGE + cw * 1536 + prd, xr = sb + SM_STAGES + (grp ^ 1) * STAGE + cw * 1536 + prd;
    const float cl = -cm[0] * al, ch = -cm[2] * ah;
#pragma unroll
    for (int i = 0; i < 3; i++)
        sts128(xw + i * 512, u(fmaf(acc[3 + i][0], al, cl)), u(fmaf(acc[3 + i][1], al, cl)), u(fmaf(acc[3 + i][2], ah, ch)), u(fmaf(acc[3 + i][3], ah, ch)));
#pragma unroll
    for (int i = 0; i < 3; i++) { acc[i][0] = fmaf(acc[i][0], al, cl); acc[i][1] = fmaf(acc[i][1], al, cl); acc[i][2] = fmaf(acc[i][2], ah, ch); acc[i][3] = fmaf(acc[i][3], ah, ch); }
    const uint32_t w_lo = packh(l_lo * al, 1.f), w_hi = packh(l_hi * ah, 1.f);
    bar_sync(B_MERGE, 256);
    if (threadIdx.x == 224) TSX(4, 0);
    uint4 o[3];
#pragma unroll
    for (int i = 0; i < 3; i++) o[i] = lds128(xr + i * 512);
    red8h(dst, packh(acc[0][0] + f(o[0].x), acc[0][1] + f(o[0].y)), packh(acc[1][0] + f(o[1].x), acc[1][1] + f(o[1].y)), packh(acc[2][0] + f(o[2].x), acc[2][1] + f(o[2].y)), w_lo);
    red8h(dsu, packh(acc[0][2] + f(o[0].z), acc[0][3] + f(o[0].w)), packh(acc[1][2] + f(o[1].z), acc[1][3] + f(o[1].w)), packh(acc[2][2] + f(o[2].z), acc[2][3] + f(o[2].w)), w_hi);
    if (threadIdx.x == 0) TSE(4);
    if (threadIdx.x == 224) TSX(9, 0);
}

typedef CUresult (*EncodeFn)(CUtensorMap*, CUtensorMapDataType, cuuint32_t, void*, const cuuint64_t*, const cuuint64_t*,
                             const cuuint32_t*, const cuuint32_t*, CUtensorMapInterleave, CUtensorMapSwizzle,
                             CUtensorMapL2promotion, CUtensorMapFloatOOBfill);

}

extern "C" void kernel_launch(void* const* d_in, const int* in_sizes, int n_in, void* d_out, int out_size) {
    const __nv_bfloat16* q = (const __nv_bfloat16*)d_in[0];
    char* f0 = (char*)d_in[1];
    char* f1 = (char*)d_in[2];
    const __nv_bfloat16* wq = (const __nv_bfloat16*)d_in[3];
    const __nv_bfloat16* wk = (const __nv_bfloat16*)d_in[4];
    const __nv_bfloat16* wv = (const __nv_bfloat16*)d_in[5];
    const __nv_bfloat16* wo = (const __nv_bfloat16*)d_in[6];

    static EncodeFn enc = nullptr;
    static int grid = 0;
    static Scratch* scr = nullptr;
    if (!enc) {
        void* fn = nullptr; cudaDriverEntryPointQueryResult qr;
        cudaGetDriverEntryPoint("cuTensorMapEncodeTiled", &fn, cudaEnableDefault, &qr);
        enc = (EncodeFn)fn;
        cudaGetSymbolAddress((void**)&scr, g_scratch);
        int dev = 0, sms = 0;
        cudaGetDevice(&dev);
        cudaDeviceGetAttribute(&sms, cudaDevAttrMultiProcessorCount, dev);
        grid = sms < MAXG ? sms : MAXG;
        cudaFuncSetAttribute(attn_main, cudaFuncAttributeMaxDynamicSharedMemorySize, SMEM_BYTES);
    }
    CUtensorMap m0, m1;
    {
        cuuint64_t dims[5] = {64, W1, 3, 2, W0};
        cuuint64_t str[4] = {2 * C * 2, 128, C * 2, (cuuint64_t)W0 * C * 2};
        cuuint32_t box[5] = {64, TP, 3, 2, 2}, es[5] = {1, 1, 1, 1, 1};
        enc(&m0, CU_TENSOR_MAP_DATA_TYPE_BFLOAT16, 5, f0, dims, str, box, es, CU_TENSOR_MAP_INTERLEAVE_NONE,
            CU_TENSOR_MAP_SWIZZLE_128B, CU_TENSOR_MAP_L2_PROMOTION_NONE, CU_TENSOR_MAP_FLOAT_OOB_FILL_NONE);
    }
    {
        cuuint64_t dims[4] = {64, W1, 3, W1};
        cuuint64_t str[3] = {C * 2, 128, (cuuint64_t)W1 * C * 2};
        cuuint32_t box[4] = {64, TP, 3, 1}, es[4] = {1, 1, 1, 1};
        enc(&m1, CU_TENSOR_MAP_DATA_TYPE_BFLOAT16, 4, f1, dims, str, box, es, CU_TENSOR_MAP_INTERLEAVE_NONE,
            CU_TENSOR_MAP_SWIZZLE_128B, CU_TENSOR_MAP_L2_PROMOTION_NONE, CU_TENSOR_MAP_FLOAT_OOB_FILL_NONE);
    }
    attn_main<<<grid, NTHREADS, SMEM_BYTES, cudaStreamPerThread>>>(f0, f1, q, wq, wk, scr, wv, wo, (__nv_bfloat16*)d_out, m0, m1);
}
```

```cpp
#include <cuda_runtime.h>
#include <cuda_bf16.h>
#include <cuda.h>
#include <stdint.h>

namespace {

constexpr int C = 192;
constexpr int NQ = 16;
constexpr int W0 = 512;
constexpr int W1 = 256;
constexpr int TP = 8;
constexpr int NT = W1 * W1 / TP;
constexpr int STAGE = TP * 5 * C * 2;
#define NS 14
#define D0 3
#define D1 2
#define D2 1
#define NRAMP 5
#define TAILT 150
#define QSLEEP 700
#define WSL 24
#define MAXT 3000
#define REFT 1800
#define POLLN 1
#define PGAP 64
#define NPW 5
#define NPROBE 8
#define LAZY 12.f
#define GR4 1
#define NST 4
#define NI 1
#define NPACE 5
#define T0 0
#define T1 1600
#define TG 960
static_assert(NST > D0, "the first dynamic tile index must not delay the start");
constexpr int NTHREADS = 384;
constexpr int MAXG = 132;
constexpr int NRD = NQ;
constexpr int NSRC = 12;
constexpr int SPIN_LIMIT = 1 << 22;

constexpr int SM_STAGES = 0;
constexpr int SM_P = NS * STAGE;
constexpr int PBUF = 1088;
constexpr int SM_QK = SM_P + 4 * PBUF;
constexpr int SM_MX = SM_QK + 6144;
constexpr int SM_M = SM_MX + 512;
constexpr int SM_BAR = SM_M + 64;
constexpr int SM_REF = SM_BAR + 16 * NS;
constexpr int SM_FLAG = SM_REF + 8;
constexpr int SM_TOTAL = SM_FLAG + 4 * NS;
constexpr int SMEM_BYTES = SM_TOTAL + 1024;
static_assert(SMEM_BYTES <= 232448, "smem");
constexpr int WROW = 400;
constexpr int RD_W = 0;
constexpr int RD_QN = 2 * C * WROW;
constexpr int RD_KQ = RD_QN + 6144;
constexpr int RD_B = RD_KQ + 7168;
constexpr int RD_B2 = 17 * 80;
constexpr int RD_PLACE = RD_B + 2 * RD_B2;
constexpr int RD_BAR = RD_PLACE + 16;
constexpr int RD_A = RD_BAR + 64;
constexpr int RD_WS = RD_A + 12 * 6 * 512;
static_assert(RD_WS + 12 * 128 <= SM_TOTAL, "smem");

struct Scratch {
    uint4 acc[2048];
    uint4 qk[NSRC * 32];
    unsigned ctr[32];
    unsigned mmax[32];
    unsigned mref[32];
};
__device__ __align__(8192) Scratch g_scratch;
#define g_acc (scr->acc)
#define g_qk (scr->qk)
#define g_ctr (scr->ctr)
#define g_mmax (scr->mmax)
#define g_mref (scr->mref)
#define g_ts (scr->ts)
#define g_tr (scr->tr)
#define TR(k, i) do {} while (0)
#define TS(i) do {} while (0)
#define TSD(i, dep) do {} while (0)
#define TSX(i, dep) do {} while (0)
#define TSP(i, dep) do {} while (0)
#define TSE(i) TS(i)
#define CK_(i, dep) do {} while (0)
#define PH(i, dep) do {} while (0)

__device__ __forceinline__ uint32_t s2u(const void* p) { return (uint32_t)__cvta_generic_to_shared(p); }
__device__ __forceinline__ void mbar_init(uint32_t a, int c) { asm volatile("mbarrier.init.shared::cta.b64 [%0], %1;" ::"r"(a), "r"(c) : "memory"); }
__device__ __forceinline__ void mbar_expect(uint32_t a, uint32_t b) { asm volatile("mbarrier.arrive.expect_tx.shared::cta.b64 _, [%0], %1;" ::"r"(a), "r"(b) : "memory"); }
__device__ __forceinline__ void mbar_arrive(uint32_t a) { asm volatile("mbarrier.arrive.shared::cta.b64 _, [%0];" ::"r"(a) : "memory"); }
__device__ __forceinline__ void mbar_wait(uint32_t a, uint32_t ph) {
    uint32_t ok; int it = 0;
    do {
        asm volatile("{.reg .pred p; mbarrier.try_wait.parity.shared::cta.b64 p, [%1], %2; selp.u32 %0,1,0,p;}" : "=r"(ok) : "r"(a), "r"(ph) : "memory");
        if (++it > SPIN_LIMIT) __trap();
    } while (!ok);
}
__device__ __forceinline__ bool elect() {
    uint32_t r; asm volatile("{.reg .pred p; elect.sync _|p, 0xffffffff; selp.u32 %0, 1, 0, p;}" : "=r"(r)); return r;
}
__device__ __forceinline__ void bar_sync(int id, int n) { asm volatile("bar.sync %0, %1;" ::"r"(id), "r"(n) : "memory"); }
__device__ __forceinline__ bool bar_any(int id, int n, bool c) {
    uint32_t r;
    asm volatile("{.reg .pred p, q; setp.ne.u32 q, %3, 0; bar.red.or.pred p, %1, %2, q; selp.u32 %0, 1, 0, p;}" : "=r"(r) : "r"(id), "r"(n), "r"((uint32_t)c) : "memory");
    return r;
}
__device__ __forceinline__ void bar_arrive(int id, int n) { asm volatile("bar.arrive %0, %1;" ::"r"(id), "r"(n) : "memory"); }
__device__ __forceinline__ void ldsm4(uint32_t* r, uint32_t a) {
    asm volatile("ldmatrix.sync.aligned.m8n8.x4.shared.b16 {%0,%1,%2,%3}, [%4];" : "=r"(r[0]), "=r"(r[1]), "=r"(r[2]), "=r"(r[3]) : "r"(a) : "memory");
}
__device__ __forceinline__ void ldsm4t(uint32_t* r, uint32_t a) {
    asm volatile("ldmatrix.sync.aligned.m8n8.x4.trans.shared.b16 {%0,%1,%2,%3}, [%4];" : "=r"(r[0]), "=r"(r[1]), "=r"(r[2]), "=r"(r[3]) : "r"(a) : "memory");
}
__device__ __forceinline__ void ldsm2t(uint32_t* r, uint32_t a) {
    asm volatile("ldmatrix.sync.aligned.m8n8.x2.trans.shared.b16 {%0,%1}, [%2];" : "=r"(r[0]), "=r"(r[1]) : "r"(a) : "memory");
}
__device__ __forceinline__ void mma(float* d, uint32_t a0, uint32_t a1, uint32_t a2, uint32_t a3, uint32_t b0, uint32_t b1) {
    asm("mma.sync.aligned.m16n8k16.row.col.f32.bf16.bf16.f32 {%0,%1,%2,%3}, {%4,%5,%6,%7}, {%8,%9}, {%0,%1,%2,%3};"
        : "+f"(d[0]), "+f"(d[1]), "+f"(d[2]), "+f"(d[3]) : "r"(a0), "r"(a1), "r"(a2), "r"(a3), "r"(b0), "r"(b1));
}
__device__ __forceinline__ void mmah(float* d, uint32_t a0, uint32_t a1, uint32_t a2, uint32_t a3, uint32_t b0, uint32_t b1) {
    asm("mma.sync.aligned.m16n8k16.row.col.f32.f16.f16.f32 {%0,%1,%2,%3}, {%4,%5,%6,%7}, {%8,%9}, {%0,%1,%2,%3};"
        : "+f"(d[0]), "+f"(d[1]), "+f"(d[2]), "+f"(d[3]) : "r"(a0), "r"(a1), "r"(a2), "r"(a3), "r"(b0), "r"(b1));
}
__device__ __forceinline__ void mma8(float* d, uint32_t a0, uint32_t a1, uint32_t b0) {
    asm("mma.sync.aligned.m16n8k8.row.col.f32.bf16.bf16.f32 {%0,%1,%2,%3}, {%4,%5}, {%6}, {%0,%1,%2,%3};"
        : "+f"(d[0]), "+f"(d[1]), "+f"(d[2]), "+f"(d[3]) : "r"(a0), "r"(a1), "r"(b0));
}
__device__ __forceinline__ uint32_t hadd2(uint32_t a, uint32_t b) {
    uint32_t r; asm("add.rn.bf16x2 %0, %1, %2;" : "=r"(r) : "r"(a), "r"(b)); return r;
}
__device__ __forceinline__ uint32_t pack2(float lo, float hi) {
    uint32_t r; asm("cvt.rn.bf16x2.f32 %0, %1, %2;" : "=r"(r) : "f"(hi), "f"(lo)); return r;
}
__device__ __forceinline__ uint32_t packh(float lo, float hi) {
    uint32_t r; asm("cvt.rn.f16x2.f32 %0, %1, %2;" : "=r"(r) : "f"(hi), "f"(lo)); return r;
}
__device__ __forceinline__ float2 unpackh(uint32_t v) {
    float2 r; asm("{.reg .b16 l, h; mov.b32 {l, h}, %2; cvt.f32.f16 %0, l; cvt.f32.f16 %1, h;}" : "=f"(r.x), "=f"(r.y) : "r"(v)); return r;
}
__device__ __forceinline__ float bflo(uint32_t v) { return __uint_as_float(v << 16); }
__device__ __forceinline__ float bfhi(uint32_t v) { return __uint_as_float(v & 0xffff0000u); }
__device__ __forceinline__ float ex2(float x) { float r; asm("ex2.approx.ftz.f32 %0, %1;" : "=f"(r) : "f"(x)); return r; }
__device__ __forceinline__ void sts128(uint32_t a, uint32_t x, uint32_t y, uint32_t z, uint32_t w) {
    asm volatile("st.shared.v4.b32 [%0], {%1,%2,%3,%4};" ::"r"(a), "r"(x), "r"(y), "r"(z), "r"(w) : "memory");
}
__device__ __forceinline__ void sts64(uint32_t a, uint32_t x, uint32_t y) {
    asm volatile("st.shared.v2.b32 [%0], {%1,%2};" ::"r"(a), "r"(x), "r"(y) : "memory");
}
__device__ __forceinline__ void sts32(uint32_t a, uint32_t x) { asm volatile("st.shared.b32 [%0], %1;" ::"r"(a), "r"(x) : "memory"); }
__device__ __forceinline__ uint4 lds128(uint32_t a) {
    uint4 v; asm volatile("ld.shared.v4.b32 {%0,%1,%2,%3}, [%4];" : "=r"(v.x), "=r"(v.y), "=r"(v.z), "=r"(v.w) : "r"(a) : "memory"); return v;
}
__device__ __forceinline__ uint32_t lds32(uint32_t a) { uint32_t v; asm volatile("ld.shared.b32 %0, [%1];" : "=r"(v) : "r"(a) : "memory"); return v; }
__device__ __forceinline__ int grab_tile(unsigned* ctr) {
    int v; asm volatile("atom.relaxed.gpu.global.inc.u32 %0, [%1], 0x7fffffff;" : "=r"(v) : "l"(ctr) : "memory"); return v;
}
__device__ __forceinline__ uint32_t opaque(uint32_t v) { uint32_t r; asm volatile("mov.b32 %0, %1;" : "=r"(r) : "r"(v)); return r; }
__device__ __forceinline__ unsigned clock32() { unsigned c; asm volatile("mov.u32 %0, %%clock;" : "=r"(c)); return c; }
__device__ __forceinline__ float rsq(float x) { float r; asm("rsqrt.approx.ftz.f32 %0, %1;" : "=f"(r) : "f"(x)); return r; }
__device__ __forceinline__ float rcp(float x) { float r; asm("rcp.approx.ftz.f32 %0, %1;" : "=f"(r) : "f"(x)); return r; }
__device__ __forceinline__ float lg2(float x) { float r; asm("lg2.approx.ftz.f32 %0, %1;" : "=f"(r) : "f"(x)); return r; }
__device__ __forceinline__ float f(uint32_t v) { return __uint_as_float(v); }
__device__ __forceinline__ uint32_t u(float v) { return __float_as_uint(v); }

constexpr uint32_t ONES = 0x3F803F80u;
constexpr float QSCALE = 0.07216878364870322f * 1.4426950408889634f;

__device__ __forceinline__ void issue_tile(const CUtensorMap* m0, const CUtensorMap* m1, uint32_t sb, int s, int tl, uint64_t pol) {
    const uint32_t full = sb + SM_BAR + s * 8, dst = sb + SM_STAGES + s * STAGE;
    const int par = tl * TP, y = par >> 8, x = par & 255;
    mbar_expect(full, STAGE);
    asm volatile("cp.async.bulk.tensor.5d.shared::cluster.global.mbarrier::complete_tx::bytes.L2::cache_hint [%0], [%1, {%3,%4,%3,%3,%5}], [%2], %6;"
                 ::"r"(dst), "l"(m0), "r"(full), "r"(0), "r"(x), "r"(2 * y), "l"(pol) : "memory");
    asm volatile("cp.async.bulk.tensor.4d.shared::cluster.global.mbarrier::complete_tx::bytes.L2::cache_hint [%0], [%1, {%3,%4,%3,%5}], [%2], %6;"
                 ::"r"(dst + TP * 4 * C * 2), "l"(m1), "r"(full), "r"(0), "r"(x), "r"(y), "l"(pol) : "memory");
}

__device__ __forceinline__ void prefetch_l2(const void* a, int n) { asm volatile("cp.async.bulk.prefetch.L2.global [%0], %1;" ::"l"(a), "r"(n) : "memory"); }
__device__ __forceinline__ uint4 ldg_relaxed(const uint4* p) {
    uint4 v; asm volatile("ld.relaxed.gpu.global.v4.u32 {%0,%1,%2,%3}, [%4];" : "=r"(v.x), "=r"(v.y), "=r"(v.z), "=r"(v.w) : "l"(p) : "memory"); return v;
}
__device__ __forceinline__ uint32_t ldg_relaxed32(const void* p) {
    uint32_t v; asm volatile("ld.relaxed.gpu.global.u32 %0, [%1];" : "=r"(v) : "l"(p) : "memory"); return v;
}
__device__ __forceinline__ void stg_relaxed(uint4* p, uint32_t x, uint32_t y, uint32_t z, uint32_t w) {
    asm volatile("st.relaxed.gpu.global.v4.u32 [%0], {%1,%2,%3,%4};" ::"l"(p), "r"(x), "r"(y), "r"(z), "r"(w) : "memory");
}
__device__ __forceinline__ void stg_relaxed32(void* p, uint32_t x) { asm volatile("st.relaxed.gpu.global.u32 [%0], %1;" ::"l"(p), "r"(x) : "memory"); }
__device__ __forceinline__ bool has(const uint4& v, uint32_t m) { return v.x == m || v.y == m || v.z == m || v.w == m; }
__device__ __forceinline__ uint32_t hadd2v(uint32_t a, uint32_t b) {
    uint32_t r; asm volatile("add.rn.bf16x2 %0, %1, %2;" : "=r"(r) : "r"(a), "r"(b)); return r;
}

__device__ __forceinline__ void red8h(uint4* p, uint32_t x, uint32_t y, uint32_t z, uint32_t w) {
    asm volatile("red.relaxed.gpu.global.add.noftz.v4.f16x2 [%0], {%1,%2,%3,%4};" ::"l"(p), "r"(x), "r"(y), "r"(z), "r"(w) : "memory");
}
__device__ __forceinline__ uint4 lds128v(uint32_t a) {
    uint4 v; asm volatile("ld.volatile.shared.v4.b32 {%0,%1,%2,%3}, [%4];" : "=r"(v.x), "=r"(v.y), "=r"(v.z), "=r"(v.w) : "r"(a) : "memory"); return v;
}
__device__ __forceinline__ uint32_t brow(int r) { return RD_B + r * 80 + (r >> 3) * 64; }

constexpr uint32_t PLACE = 0x1980;
__device__ __forceinline__ uint32_t acc_line(int k) { return (k >> 2) * 16384 + (k & 2) * 6144 + (k & 1) * 1024; }
__device__ __forceinline__ uint32_t acc_place(int side, int s) { return side * 4096 + (s & 1) * 256 + (s & 2) * 1024 + (s & 4) * 32; }

enum { B_QK = 1, B_QN = 2, B_GRP = 3  , B_Q = 5, B_MERGE = 6, B_ALL = 7, B_MAX = 8  , B_WARP = 10, B_SLOW = 12, B_PARK = 13, B_PLACE = 14, B_RDY = 15 };

__device__ __noinline__ void slow_rows(const char* __restrict__ f0, const char* __restrict__ f1, const __nv_bfloat16* __restrict__ q,
                                       const __nv_bfloat16* __restrict__ wq, const __nv_bfloat16* __restrict__ wk, const uint32_t sb)
{
    const int warp = threadIdx.x >> 5, lane = threadIdx.x & 31;
    float* const sm = reinterpret_cast<float*>(__cvta_shared_to_generic(sb + RD_W));
    for (int i = threadIdx.x; i < 2 * C; i += 128) sm[i] = __bfloat162float(q[(blockIdx.x & 14) * C + i]);
    bar_sync(B_SLOW, 128);
#pragma unroll 1
    for (int j = threadIdx.x; j < 2 * C; j += 128) {
        const float* const x = sm + j / C * C;
        float mu = 0.f, var = 0.f, s = 0.f;
#pragma unroll 1
        for (int i = 0; i < C; i++) mu += x[i];
        mu *= 1.f / C;
#pragma unroll 4
        for (int i = 0; i < C; i++) { var = fmaf(x[i] - mu, x[i] - mu, var); s = fmaf(x[i] - mu, __bfloat162float(wq[i * C + j % C]), s); }
        sm[4 * C + j] = s * rsq(var * (1.f / C) + 1e-5f);
    }
    bar_sync(B_SLOW, 128);
#pragma unroll 1
    for (int j = threadIdx.x; j < 2 * C; j += 128) {
        float s = 0.f;
#pragma unroll 4
        for (int i = 0; i < C; i++) s = fmaf(sm[4 * C + j / C * C + i], __bfloat162float(wk[j % C * C + i]), s);
        sm[j] = s * QSCALE;
    }
    bar_sync(B_SLOW, 128);
    float k[2][6], a[2][6], m[2], l[2];
#pragma unroll
    for (int r = 0; r < 2; r++) {
        m[r] = -INFINITY; l[r] = 0.f;
#pragma unroll
        for (int i = 0; i < 6; i++) { k[r][i] = sm[r * C + 64 * (i >> 1) + 2 * lane + (i & 1)]; a[r][i] = 0.f; }
    }
#pragma unroll 1
    for (int par = warp; par < W1 * W1; par += 4) {
        const uint32_t* p0 = reinterpret_cast<const uint32_t*>(f0 + (size_t)((par >> 8) * 2 * W0 + (par & 255) * 2) * (C * 2)) + lane;
        const uint32_t* p1 = reinterpret_cast<const uint32_t*>(f1 + (size_t)par * (C * 2)) + lane;
        uint32_t v[4][3];
#pragma unroll
        for (int i = 0; i < 3; i++)
#pragma unroll
            for (int j = 0; j < 4; j++) v[j][i] = hadd2(__ldg(p0 + ((j >> 1) * W0 + (j & 1)) * (C / 2) + 32 * i), __ldg(p1 + 32 * i));
#pragma unroll
        for (int j = 0; j < 4; j++) {
            float x[6], s1 = 0.f, s2 = 0.f, d[2] = {0.f, 0.f};
#pragma unroll
            for (int i = 0; i < 3; i++) { x[2 * i] = bflo(v[j][i]); x[2 * i + 1] = bfhi(v[j][i]); s1 += x[2 * i] + x[2 * i + 1]; }
#pragma unroll
            for (int o = 1; o < 32; o <<= 1) s1 += __shfl_xor_sync(~0u, s1, o);
#pragma unroll
            for (int i = 0; i < 6; i++) {
                x[i] -= s1 * (1.f / C); s2 = fmaf(x[i], x[i], s2);
#pragma unroll
                for (int r = 0; r < 2; r++) d[r] = fmaf(x[i], k[r][i], d[r]);
            }
#pragma unroll
            for (int o = 1; o < 32; o <<= 1) {
                s2 += __shfl_xor_sync(~0u, s2, o);
#pragma unroll
                for (int r = 0; r < 2; r++) d[r] += __shfl_xor_sync(~0u, d[r], o);
            }
            const float rs = rsq(s2 * (1.f / C) + 1e-5f);
#pragma unroll
            for (int r = 0; r < 2; r++) {
                const float nm = fmaxf(m[r], d[r] * rs), al = ex2(m[r] - nm), p = ex2(d[r] * rs - nm);
                m[r] = nm; l[r] = fmaf(l[r], al, p);
#pragma unroll
                for (int i = 0; i < 6; i++) a[r][i] = fmaf(a[r][i], al, x[i] * (p * rs));
            }
        }
    }
    bar_sync(B_SLOW, 128);
#pragma unroll
    for (int r = 0; r < 2; r++) {
        float* const o = sm + ((r * 4 + warp) * 32 + lane) * 8;
#pragma unroll
        for (int i = 0; i < 6; i++) o[i] = a[r][i];
        o[6] = l[r]; o[7] = m[r];
    }
    bar_sync(B_SLOW, 128);
    if (warp < 2) {
        const int r = warp;
        const float* const o = sm + (r * 128 + lane) * 8;
        float M = o[7], x[7] = {0.f, 0.f, 0.f, 0.f, 0.f, 0.f, 0.f};
#pragma unroll
        for (int w = 1; w < 4; w++) M = fmaxf(M, o[256 * w + 7]);
#pragma unroll
        for (int w = 0; w < 4; w++) {
            const float e = ex2(o[256 * w + 7] - M);
#pragma unroll
            for (int i = 0; i < 7; i++) x[i] = fmaf(o[256 * w + i], e, x[i]);
        }
        const float rl = 1.f / x[6];
        sts128(sb + RD_B2 + brow(8 * (lane >> 4) + 4 * r + (lane & 3)) + ((lane >> 2) & 3) * 16, packh(x[0] * rl, x[1] * rl), packh(x[2] * rl, x[3] * rl), packh(x[4] * rl, x[5] * rl), lane ? 0u : 0x3C00u);
    }
}

template <bool FIRST>
__device__ __forceinline__ void project(const uint32_t ar, const uint32_t br, const bool hi, const float ws0, const float ws1, const float qv0, const float qv1,
                                        __nv_bfloat16* op0, __nv_bfloat16* op1, Scratch* scr)
{
    uint4 wa[3][6], x[4];
#pragma unroll
    for (int i = 0; i < 18; i++) wa[i / 6][i % 6] = lds128v(ar + i * 512);
    if (FIRST) { bar_arrive(B_PLACE, NTHREADS); bar_sync(B_RDY, 192); }
    else bar_sync(B_SLOW, 128);
    if (FIRST && threadIdx.x == 0) TSX(8, 0);
#pragma unroll
    for (int j = 0; j < 4; j++) x[j] = lds128v(br + 16 * j);
    float o[7][4];
#pragma unroll
    for (int j = 0; j < 7; j++) o[j][0] = o[j][1] = o[j][2] = o[j][3] = 0.f;
#pragma unroll
    for (int i = 0; i < 2; i++) {
        mmah(o[6], 0x3C00u, 0x3C00u, 0x3C00u, 0x3C00u, x[2 * i].w, x[2 * i + 1].w);
#pragma unroll
        for (int n = 0; n < 3; n++) mmah(o[2 * n + i], wa[n][2 * i].x, wa[n][2 * i].y, wa[n][2 * i].z, wa[n][2 * i].w, x[2 * i].x, x[2 * i].y);
#pragma unroll
        for (int n = 0; n < 3; n++) mmah(o[2 * n + 1 - i], wa[n][2 * i + 1].x, wa[n][2 * i + 1].y, wa[n][2 * i + 1].z, wa[n][2 * i + 1].w, x[2 * i + 1].x, x[2 * i + 1].y);
#pragma unroll
        for (int n = 0; n < 3; n++) mmah(o[2 * n + i], wa[n][4 + i].x, wa[n][4 + i].y, wa[n][4 + i].z, wa[n][4 + i].w, x[2 * i].z, x[2 * i + 1].z);
    }
    const float L = o[6][0] + o[6][1], r = rcp(L);
    const float y0 = hi ? (o[2][0] + o[2][3]) + (o[3][0] + o[3][3]) : (o[0][0] + o[0][3]) + (o[1][0] + o[1][3]), y1 = (o[4][0] + o[4][3]) + (o[5][0] + o[5][3]);
    const uint32_t y = pack2(fmaf(y0, r * ws0, qv0), fmaf(y1, r * ws1, qv1));
    asm volatile("{.reg .b16 l, h; mov.b32 {l, h}, %2; st.global.b16 [%0], l; st.global.b16 [%1], h;}" ::"l"(op0), "l"(op1), "r"(y) : "memory");
    if (FIRST && threadIdx.x == 0) TSD(11, y);
    if (FIRST)
        asm volatile("{.reg .pred p; .reg .f32 a; abs.f32 a, %1; setp.ge.f32 p, %0, 0f3B000000; setp.le.and.f32 p, %0, 0f45000000, p; setp.lt.and.f32 p, a, 0f7F800000, p;"
                     " vote.sync.all.pred p, p, 0xffffffff; @p exit;}" ::"f"(L), "f"(y0) : "memory");
}

__device__ __forceinline__ void reducer(const char* __restrict__ f0, const char* __restrict__ f1, const __nv_bfloat16* __restrict__ q, const __nv_bfloat16* __restrict__ wq, const __nv_bfloat16* __restrict__ wk,
                                        Scratch* scr, const __nv_bfloat16* __restrict__ wv, const __nv_bfloat16* __restrict__ wo,
                                        __nv_bfloat16* __restrict__ out, const uint32_t sb, const int GS)
{
    const int warp = threadIdx.x >> 5, lane = threadIdx.x & 31, b = blockIdx.x;
    const int g = lane >> 2, t = lane & 3;
    char* const ap = reinterpret_cast<char*>(g_acc);
    if (threadIdx.x == 256) TS(0);
    if (b < NSRC && warp < 8) {
        const uint32_t wqs = sb + RD_W, wbar = sb + RD_BAR;
        const int hr = lane >> 4, qt = (lane >> 2) & 3, sub = lane & 3;
        const uint32_t* qp = reinterpret_cast<const uint32_t*>(q + (warp + 8 * hr) * C + 48 * qt + 6 * sub);
        uint32_t qw[6];
#pragma unroll
        for (int j = 0; j < 3; j++) { qw[j] = __ldg(qp + j); qw[3 + j] = __ldg(qp + 12 + j); }
        if (lane == 0) { mbar_init(wbar + warp * 8, 1); asm volatile("fence.mbarrier_init.release.cluster;" ::: "memory"); mbar_expect(wbar + warp * 8, 9216);
            asm volatile("cp.async.bulk.shared::cluster.global.mbarrier::complete_tx::bytes [%0], [%1], 9216, [%2];"
                         ::"r"(wqs + warp * 9232), "l"(wq + 24 * warp * C), "r"(wbar + warp * 8) : "memory");
        }
        __syncwarp();
        if (threadIdx.x == 0) TSP(2, 0);
        float e[12];
#pragma unroll
        for (int j = 0; j < 6; j++) { e[2 * j] = bflo(qw[j]); e[2 * j + 1] = bfhi(qw[j]); }
        float sm = ((e[0] + e[1]) + (e[2] + e[3])) + ((e[4] + e[5]) + (e[6] + e[7])) + ((e[8] + e[9]) + (e[10] + e[11]));
#pragma unroll
        for (int o = 1; o < 16; o <<= 1) sm += __shfl_xor_sync(~0u, sm, o);
        if (threadIdx.x == 0) TSP(5, u(sm));
        float v0 = 0.f, v1 = 0.f;
#pragma unroll
        for (int j = 0; j < 12; j++) e[j] -= sm * (1.f / C);
#pragma unroll
        for (int j = 0; j < 6; j++) { v0 = fmaf(e[j], e[j], v0); v1 = fmaf(e[6 + j], e[6 + j], v1); }
        v0 += v1;
#pragma unroll
        for (int o = 1; o < 16; o <<= 1) v0 += __shfl_xor_sync(~0u, v0, o);
        const float rq = rsq(v0 * (1.f / C) + 1e-5f);
#pragma unroll
        for (int j = 0; j < 6; j++)
            sts32(sb + RD_QN + (3 * sub + (j >> 1)) * 512 + (4 * warp + qt) * 16 + (2 * (j & 1) + hr) * 4, pack2(e[j] * rq, e[6 + j] * rq));
        if (threadIdx.x == 0) TSP(8, 0);
        uint32_t wkf[2][3];
#pragma unroll
        for (int i = 0; i < 2; i++)
#pragma unroll
            for (int j = 0; j < 3; j++) wkf[i][j] = __ldg(reinterpret_cast<const uint32_t*>(wk + (16 * b + 8 * i + g) * C + 24 * warp + 8 * j + 2 * t));
        bar_sync(B_QN, 256);
        float acc[2][3][4];
#pragma unroll
        for (int i = 0; i < 3; i++)
#pragma unroll
            for (int e = 0; e < 4; e++) acc[0][i][e] = acc[1][i][e] = 0.f;
        const uint32_t ba = wqs + (lane & 7) * 9232 + (lane >> 3) * 384 + 48 * warp;
        uint4 a[12];
#pragma unroll
        for (int kk = 0; kk < 12; kk++) a[kk] = lds128(sb + RD_QN + kk * 512 + lane * 16);
        mbar_wait(wbar + (lane & 7) * 8, 0);
        __syncwarp();
        if (threadIdx.x == 0) TSP(4, 0);
#pragma unroll
        for (int kp = 0; kp < 6; kp++)
#pragma unroll
            for (int i = 0; i < 3; i++) {
                uint32_t bb[4];
                ldsm4t(bb, ba + kp * 1536 + i * 16);
                mma(acc[0][i], a[2 * kp].x, a[2 * kp].y, a[2 * kp].z, a[2 * kp].w, bb[0], bb[1]);
                mma(acc[1][i], a[2 * kp + 1].x, a[2 * kp + 1].y, a[2 * kp + 1].z, a[2 * kp + 1].w, bb[2], bb[3]);
            }
        if (threadIdx.x == 0) TSP(7, u(acc[1][2][3]));
        float kq[2][4] = {{0.f, 0.f, 0.f, 0.f}, {0.f, 0.f, 0.f, 0.f}};
#pragma unroll
        for (int j = 0; j < 3; j++) {
            const uint32_t a0 = pack2(acc[0][j][0] + acc[1][j][0], acc[0][j][1] + acc[1][j][1]), a1 = pack2(acc[0][j][2] + acc[1][j][2], acc[0][j][3] + acc[1][j][3]);
            mma8(kq[0], a0, a1, wkf[0][j]);
            mma8(kq[1], a0, a1, wkf[1][j]);
        }
        if (warp < 7) {
            sts128(sb + RD_KQ + warp * 1024 + lane * 16, u(kq[0][0]), u(kq[0][1]), u(kq[0][2]), u(kq[0][3]));
            sts128(sb + RD_KQ + warp * 1024 + 512 + lane * 16, u(kq[1][0]), u(kq[1][1]), u(kq[1][2]), u(kq[1][3]));
            bar_arrive(B_Q, 256);
        } else {
            bar_sync(B_Q, 256);
#pragma unroll
            for (int w = 0; w < 7; w++)
#pragma unroll
                for (int i = 0; i < 2; i++) {
                    const uint4 o = lds128(sb + RD_KQ + w * 1024 + i * 512 + lane * 16);
                    kq[i][0] += f(o.x); kq[i][1] += f(o.y); kq[i][2] += f(o.z); kq[i][3] += f(o.w);
                }
            stg_relaxed(g_qk + b * 32 + lane, ~pack2(kq[0][0] * QSCALE, kq[0][1] * QSCALE), ~pack2(kq[0][2] * QSCALE, kq[0][3] * QSCALE),
                        ~pack2(kq[1][0] * QSCALE, kq[1][1] * QSCALE), ~pack2(kq[1][2] * QSCALE, kq[1][3] * QSCALE));
            if (lane == 0) TS(10);
        }
    } else if (warp == 8 && !(b & 1)) {
        char* const pp = ap + (b >> 2) * 8192 + (b & 2) * 512;
        if (lane < 16) stg_relaxed(reinterpret_cast<uint4*>(pp + (lane >> 3) * 4096) + (lane & 7), 0, 0, 0, 0);
        __syncwarp();
        uint32_t place = 0;
        if (lane == 0) {
            uint32_t best[2] = {~0u, ~0u};
#pragma unroll 1
            for (int it = 0; it < NPROBE; it++) {
#pragma unroll
                for (int i = 0; i < 2; i++) {
                    uint32_t c;
                    asm volatile("{.reg .b32 v, c0; .reg .pred p; mov.u32 c0, %%clock; atom.relaxed.gpu.global.exch.b32 v, [%1], 0; setp.ne.u32 p, v, 0; @p trap;"
                                 " mov.u32 %0, %%clock; sub.u32 %0, %0, c0;}" : "=r"(c) : "l"(pp + i * 4096) : "memory");
                    best[i] = min(best[i], c);
                }
            }
            place = acc_place((best[1] < best[0]) ^ ((b >> 2) & 1), b >> 1);
            sts32(sb + RD_PLACE, place);
        }
        place = __shfl_sync(~0u, place, 0);
#pragma unroll
        for (int i = 0; i < 2; i++) stg_relaxed(reinterpret_cast<uint4*>(ap + (acc_line(4 * i + (lane >> 3)) ^ place)) + (lane & 7), 0, 0, 0, 0);
        __threadfence();
    } else if (b >= NSRC) {
        if (b == NSRC && warp == 0) stg_relaxed32(g_mmax + lane, 0);
        __nanosleep(2500);
    }
    bar_sync(B_ALL, NTHREADS);

#pragma unroll 1
    for (int r = 0; r < 3; r++) {
        uint4 v[8];
#pragma unroll
        for (int k = 0; k < 8; k++) {
            const int idx = (8 * r + k) * 384 + threadIdx.x;
            v[k] = __ldg(reinterpret_cast<const uint4*>(idx < 4608 ? wv : wo - C * C) + idx);
        }
#pragma unroll
        for (int k = 0; k < 8; k++) {
            const int idx = (8 * r + k) * 384 + threadIdx.x, row = idx / 24;
            sts128(sb + RD_W + row * WROW + (idx - 24 * row) * 16, v[k].x, v[k].y, v[k].z, v[k].w);
        }
    }
    bar_sync(B_ALL, NTHREADS);
    if (warp < 6) {
        const int col = 96 * (b & 1) + 16 * warp;
        float d[24][4];
#pragma unroll
        for (int i = 0; i < 24; i++) d[i][0] = d[i][1] = d[i][2] = d[i][3] = 0.f;
        const int mi = lane >> 3, r = lane & 7;
        const uint32_t aa = sb + RD_W + (C + (mi >> 1) * 8 + r) * WROW + (col + (mi & 1) * 8) * 2;
        const uint32_t ba = sb + RD_W + ((mi >> 1) * 8 + r) * WROW + (mi & 1) * 16;
#pragma unroll 1
        for (int kk = 0; kk < 12; kk++) {
            uint32_t a[4];
            ldsm4t(a, aa + kk * 16 * WROW);
#pragma unroll
            for (int i = 0; i < 12; i++) {
                uint32_t bb[4];
                ldsm4(bb, ba + i * 16 * WROW + kk * 32);
                mma(d[2 * i], a[0], a[1], a[2], a[3], bb[0], bb[1]);
                mma(d[2 * i + 1], a[0], a[1], a[2], a[3], bb[2], bb[3]);
            }
        }
        float c0 = 0.f, c1 = 0.f, m0 = 0.f, m1 = 0.f;
#pragma unroll
        for (int i = 0; i < 24; i++) { c0 += d[i][0] + d[i][1]; c1 += d[i][2] + d[i][3]; }
        c0 += __shfl_xor_sync(~0u, c0, 1); c1 += __shfl_xor_sync(~0u, c1, 1);
        c0 += __shfl_xor_sync(~0u, c0, 2); c1 += __shfl_xor_sync(~0u, c1, 2);
        c0 *= 1.f / C; c1 *= 1.f / C;
#pragma unroll
        for (int i = 0; i < 24; i++) {
            d[i][0] -= c0; d[i][1] -= c0; d[i][2] -= c1; d[i][3] -= c1;
            m0 = fmaxf(m0, fmaxf(fabsf(d[i][0]), fabsf(d[i][1]))); m1 = fmaxf(m1, fmaxf(fabsf(d[i][2]), fabsf(d[i][3])));
        }
        m0 = fmaxf(m0, __shfl_xor_sync(~0u, m0, 1)); m1 = fmaxf(m1, __shfl_xor_sync(~0u, m1, 1));
        m0 = fmaxf(m0, __shfl_xor_sync(~0u, m0, 2)); m1 = fmaxf(m1, __shfl_xor_sync(~0u, m1, 2));
        const uint32_t e0 = min(max(u(m0) >> 23, 12u), 254u), e1 = min(max(u(m1) >> 23, 12u), 254u);
        const float s0 = f((265u - e0) << 23), s1 = f((265u - e1) << 23);
        const bool k0 = fabsf(c0) < INFINITY, k1 = fabsf(c1) < INFINITY;
#pragma unroll
        for (int j = 0; j < 6; j++) {
            const int n[4] = {j < 4 ? j : 8 + 2 * j, j < 4 ? 4 + j : 12 + 2 * j, j < 4 ? 8 + j : 9 + 2 * j, j < 4 ? 12 + j : 13 + 2 * j};
            uint32_t a[2][4];
#pragma unroll
            for (int e = 0; e < 4; e++) {
                a[0][e] = k0 ? packh(d[n[e]][0] * s0, d[n[e]][1] * s0) : 0u;
                a[1][e] = k1 ? packh(d[n[e]][2] * s1, d[n[e]][3] * s1) : 0u;
            }
#pragma unroll
            for (int e = 0; e < 2; e++) sts128(sb + RD_A + ((2 * warp + e) * 6 + j) * 512 + lane * 16, a[e][0], a[e][1], a[e][2], a[e][3]);
        }
        sts32(sb + RD_WS + 2 * warp * 128 + lane * 4, k0 ? (e0 - 11u) << 23 : u(c0));
        sts32(sb + RD_WS + (2 * warp + 1) * 128 + lane * 4, k1 ? (e1 - 11u) << 23 : u(c1));
        if (warp < 4) bar_sync(B_PARK, 192); else bar_arrive(B_PARK, 192);
        if (threadIdx.x == 0) TSE(6);
    }
    if (warp >= 4) {
        if (threadIdx.x == 128) {
            uint32_t m, place = lds32(sb + RD_PLACE);
            for (int it = 0;; it++) {
                const int left = NT - 2 * NST * GS - (int)ldg_relaxed32(g_ctr);
                m = ldg_relaxed32(g_mmax + b);
                if (left <= REFT && m) break;
                if (left <= 0) { m = 0x80000000u; break; }
                if (it > SPIN_LIMIT) __trap();
                __nanosleep(300);
            }
            if (b & 1) for (int it = 0;; it++) {
                uint32_t r;
                asm volatile("ld.acquire.gpu.global.u32 %0, [%1];" : "=r"(r) : "l"(g_mref + b - 1) : "memory");
                place = ~r & PLACE;
                if (r) break;
                if (it > SPIN_LIMIT) __trap();
            }
            asm volatile("st.release.gpu.global.u32 [%0], %1;" ::"l"(g_mref + b), "r"(~((u(f(m >> 31 ? m ^ 0x80000000u : ~m) + 8.f) & ~PLACE) | place)) : "memory");
            sts32(sb + RD_PLACE, place);
            TSE(7);
        }
        __syncwarp();
        if (warp == 4) {
            uint4* p0 = g_qk + min(b, NSRC - 1) * 32 + lane;
            unsigned* p1 = lane == 1 && b == NSRC ? g_ctr : g_mref + b;
            asm volatile("" : "+l"(p0), "+l"(p1));
            bar_arrive(B_PLACE, NTHREADS);
            bar_sync(B_RDY, 192);
            *p0 = make_uint4(0, 0, 0, 0);
            *p1 = 0;
            return;
        }
        bar_sync(B_PLACE, NTHREADS);
        if (warp >= 5 + NPW) return;
        const uint32_t place = lds32(sb + RD_PLACE);
        const uint4* const pa = reinterpret_cast<const uint4*>(ap + (acc_line(lane >> 3) ^ place)) + (lane & 7);
        const uint32_t bw = opaque(sb + brow(lane & 7) + (lane >> 3) * 16);
        const uint32_t n0 = packh(0.f, (float)GS), nstart = packh(0.f, (float)POLLN);
        for (int it = 0; ldg_relaxed32(ap + place + 12) < nstart; it++)
            if (it > SPIN_LIMIT) __trap();
        for (const unsigned c = clock32(); clock32() - c < (warp - 5) * PGAP;) {}
        for (int it = 0;; it++) {
            const uint4 a0 = ldg_relaxed(pa), b0 = ldg_relaxed(pa + 1024);
            if (it > SPIN_LIMIT) __trap();
            bar_sync(B_WARP, 32);
            asm volatile("{.reg .pred p, q; .reg .b32 a; setp.ge.u32 p, %5, %10; setp.ge.and.u32 p, %9, %10, p; vote.sync.all.pred q, p, 0xffffffff; selp.b32 a, %0, %1, p;"
                         " st.shared.v4.b32 [a], {%2,%3,%4,%5}; st.shared.v4.b32 [a + 704], {%6,%7,%8,%9}; @q bar.arrive 15, 192; @q exit;}"
                         ::"r"(bw), "r"(bw - (RD_B - RD_QN)), "r"(a0.x), "r"(a0.y), "r"(a0.z), "r"(a0.w), "r"(b0.x), "r"(b0.y), "r"(b0.z), "r"(b0.w), "r"(n0) : "memory");
        }
    }
    const uint32_t br = opaque(sb + brow(8 * (g & 1) + 2 * (g & 2) + t));
    const bool hi = t >= 2;
    const int oi = ((b & 14) + (t & 1)) * C + 96 * (b & 1) + 24 * warp + g;
    const float qv0 = __bfloat162float(q[oi + 4 * (t & 2)]), qv1 = __bfloat162float(q[oi + 16]);
    const float ws0 = f(lds32(sb + RD_WS + (3 * warp + (t >> 1)) * 128 + lane * 4)), ws1 = f(lds32(sb + RD_WS + (3 * warp + 2) * 128 + lane * 4));
    __nv_bfloat16* op0 = out + oi + 4 * (t & 2), * op1 = out + oi + 16;
    asm volatile("" : "+l"(op0), "+l"(op1));
    const uint32_t ar = sb + RD_A + warp * 18 * 512 + lane * 16;
    project<true>(ar, br, hi, ws0, ws1, qv0, qv1, op0, op1, scr);
    slow_rows(f0, f1, q, wq, wk, sb);
    project<false>(ar, br + RD_B2, hi, ws0, ws1, qv0, qv1, op0, op1, scr);
}

__global__ void __launch_bounds__(NTHREADS, 1)
attn_main(const char* __restrict__ f0, const char* __restrict__ f1,
          const __nv_bfloat16* __restrict__ q, const __nv_bfloat16* __restrict__ wq, const __nv_bfloat16* __restrict__ wk, Scratch* scr,
          const __nv_bfloat16* __restrict__ wv, const __nv_bfloat16* __restrict__ wo, __nv_bfloat16* __restrict__ out,
          const __grid_constant__ CUtensorMap m0, const __grid_constant__ CUtensorMap m1)
{
    extern __shared__ char smem_raw[];
    const uint32_t sb = (s2u(smem_raw) + 1023u) & ~1023u;
    const int G = gridDim.x - NRD;
    const int b = blockIdx.x - NRD;
    if (threadIdx.x == 0 && b >= 0) {
        const char* a = f0 + (uint32_t)(b * (4 * TP * C * 2) + (b >> 4) * (W0 * C * 2));
        prefetch_l2(a, 4 * TP * C * 2);
        prefetch_l2(a + W0 * C * 2, 4 * TP * C * 2);
        prefetch_l2(f1 + b * (2 * TP * C * 2), 2 * TP * C * 2);
        prefetch_l2((const char*)(b % (2 * WSL) < WSL ? wq : wk) + b % WSL * (C * C * 2 / WSL), C * C * 2 / WSL);
    }
    if (b < 0) { reducer(f0, f1, q, wq, wk, scr, wv, wo, out, sb, G); return; }
    const int warp = __shfl_sync(~0u, threadIdx.x >> 5, 0), lane = threadIdx.x & 31;
    const int g = lane >> 2, t = lane & 3;

    if (warp >= 8) {
        if (warp < 10) {
            const int p = warp - 8;
            const unsigned c0 = clock32();
            const uint32_t sbp = opaque(sb), bar = sbp + SM_BAR + p * 8;
            uint64_t pol; asm volatile("createpolicy.fractional.L2::evict_first.b64 %0, 1.0;" : "=l"(pol));
            if (elect()) {
                if (p == 0) TS(0);
                asm volatile("prefetch.tensormap [%0];" ::"l"(p ? &m1 : &m0) : "memory");
#pragma unroll
                for (int n = 0; n < NI; n++) mbar_init(bar + n * 16, 2);
                asm volatile("fence.mbarrier_init.release.cluster;" ::: "memory");
#pragma unroll
                for (int n = 0; n < NI; n++) {
                    issue_tile(&m0, &m1, sbp, p + 2 * n, 2 * b + p + 2 * n * G, pol);
                    TR(0, 2 * n + p);
                    sts32(sbp + SM_FLAG + (p + 2 * n) * 4, 0);
                    mbar_arrive(bar + n * 16);
                }
#pragma unroll
                for (int n = 0; n < NS / 2; n++) {
                    if (n >= NI) mbar_init(bar + n * 16, 2);
                    mbar_init(bar + NS * 8 + n * 16, 1);
                }
                if (p == 0) mbar_init(sbp + SM_REF, 1);
                asm volatile("fence.mbarrier_init.release.cluster;" ::: "memory");
            }
            __syncwarp();
            bar_arrive(B_QK, NTHREADS);
            if (elect()) {
                int tl = 2 * b + p + 2 * NI * G;
                int s = p + 2 * NI; uint32_t ph = 1;
                int sa = p, na = 0; uint32_t pa = 0;
                bool late = false;
                for (int n = NI;; n++) {
                    const int d = n < NRAMP ? D0 : (tl >= NT - TAILT ? D2 : D1);
                    while (n - na >= d) {
                        mbar_wait(sbp + SM_BAR + sa * 8, pa);
                        if (na < NS / 2) TR(1, 2 * na + p);
                        na++; sa += 2;
                        if (sa >= NS) { sa -= NS; pa ^= 1; }
                    }
                    mbar_wait(sbp + SM_BAR + (NS + s) * 8, ph);
                    if (n < NPACE) while (clock32() - c0 < (n ? T1 + (2 * (n - 1) + p) * TG : T0)) {}
                    issue_tile(&m0, &m1, sbp, s, tl, pol);
                    TR(0, 2 * n + p);
                    int nxt = tl + 2 * G;
                    if (n >= NST - 1) nxt = grab_tile(g_ctr) + 2 * NST * G;
                    const bool last = nxt >= NT;
                    uint32_t flag = last;
                    if (!late && nxt >= NT - MAXT - 16 * b) { late = true; flag |= 2; }
                    if (last) mbar_wait(sbp + SM_REF, 0);
                    sts32(sbp + SM_FLAG + s * 4, flag);
                    mbar_arrive(sbp + SM_BAR + s * 8);
                    if (last) break;
                    s += 2;
                    if (s >= NS) { s -= NS; ph ^= 1; }
                    tl = nxt;
                }
                if (p) TSE(5);
            }
            return;
        }
        const int h = threadIdx.x - 320;
        uint4 v[6];
        for (int it = 0;; it++) {
            bool miss = false;
#pragma unroll
            for (int k = 0; k < 6; k++) v[k] = ldg_relaxed(g_qk + k * 64 + h);
#pragma unroll
            for (int k = 0; k < 6; k++) miss |= has(v[k], 0);
            if (!miss) break;
            if (it > SPIN_LIMIT) __trap();
            if (it == 0) __nanosleep(QSLEEP);
        }
#pragma unroll
        for (int k = 0; k < 6; k++) sts128(sb + SM_QK + (k * 64 + h) * 16, ~v[k].x, ~v[k].y, ~v[k].z, ~v[k].w);
        __syncwarp();
        bar_sync(B_QK, NTHREADS);
        if (warp == 11) return;
        uint32_t r = 1;
        for (int it = 0;; it++) {
            __nanosleep(500);
            if (lane < NQ) asm volatile("ld.acquire.gpu.global.u32 %0, [%1];" : "=r"(r) : "l"(g_mref + lane) : "memory");
            if (__all_sync(~0u, r != 0)) break;
            if (it > SPIN_LIMIT) __trap();
        }
        if (lane < NQ) sts32(sb + SM_M + lane * 4, ~r);
        __syncwarp();
        if (lane == 0) { mbar_arrive(sb + SM_REF); TSE(7); }
        return;
    }

    const int grp = warp >> 2, cw = warp & 3;
    const int xp = lane & 7, mi = lane >> 3;
    const uint32_t offS1 = opaque(12288 + xp * 128 + ((mi ^ xp) << 4)), offS1x = opaque(offS1 ^ 64);
    const uint32_t offS0 = opaque(offS1 - 12288 + cw * 3072), offS0x = opaque(offS0 ^ 64);
    const uint32_t offT = opaque(mi * 3072 + xp * 128 + (((cw + 4 * grp) ^ xp) << 4)), offTx = opaque(offT ^ 64);
    const uint32_t offU = opaque(12288 + (mi % 3) * 1024 + xp * 128 + (((cw + 4 * (grp ^ (mi / 3))) ^ xp) << 4));
    const uint32_t offV = opaque(12288 + (1 + (mi & 1)) * 1024 + xp * 128 + (((cw + 4 * (grp ^ 1)) ^ xp) << 4));
    const int shl = opaque(9 * t), shl4 = opaque(9 * t + 4);
    const uint32_t pw = opaque((cw >> 1) * 512 + lane * 16 + (cw & 1) * 8), muw = opaque(1024 + t * 16 + cw * 4);
    const uint32_t prd = opaque(lane * 16), mur = opaque(1024 + t * 16), mof = g * 4;
    uint32_t pb0 = sb + SM_P + grp * 2 * PBUF;
    const uint32_t pbx = pb0 ^ (pb0 + PBUF);
    const bool odd = g & 1;
    const int barid = B_GRP + grp;
    const bool elected = cw == 3 && lane == 0;

    uint32_t qa[48];
    float r_lo, r_hi;
    bar_sync(B_QK, NTHREADS);
    {
        float rr[2][4] = {{0.f, 0.f, 0.f, 0.f}, {0.f, 0.f, 0.f, 0.f}};
#pragma unroll
        for (int kk = 0; kk < 12; kk++) {
            const uint4 v = lds128(sb + SM_QK + kk * 512 + lane * 16);
            qa[4 * kk] = v.x; qa[4 * kk + 1] = v.y; qa[4 * kk + 2] = v.z; qa[4 * kk + 3] = v.w;
            mma(rr[kk & 1], v.x, v.y, v.z, v.w, ONES, ONES);
        }
        r_lo = rr[0][0] + rr[1][0]; r_hi = rr[0][2] + rr[1][2];
    }
    if (threadIdx.x == 0) TS(1);

    float acc[6][4];
#pragma unroll
    for (int i = 0; i < 6; i++) acc[i][0] = acc[i][1] = acc[i][2] = acc[i][3] = 0.f;
    float m_lo = -INFINITY, m_hi = -INFINITY, l_lo = 0.f, l_hi = 0.f;
    float cm[4] = {0.f, 0.f, 0.f, 0.f};
    uint32_t xt[6][4], yt[6]; uint4 pa, pb, mv;
    const uint32_t dof = opaque(acc_line(warp) + (lane & 7) * 16);
    int s = grp; uint32_t ph = 0;
    while (true) {
        mbar_wait(sb + SM_BAR + s * 8, ph);
        PH(0, 0);
        const uint32_t stop = lds32(sb + SM_FLAG + s * 4);
        const uint32_t st = sb + SM_STAGES + s * STAGE;
        float sc[2][4], gr[4][4], sx[4];
#pragma unroll
        for (int e = 0; e < 4; e++) sc[0][e] = sc[1][e] = gr[0][e] = gr[1][e] = gr[2][e] = gr[3][e] = sx[e] = 0.f;
#pragma unroll
        for (int qq = 0; qq < 6; qq++) {
            uint32_t x[4], y[4];
            ldsm4(x, st + (qq & 1 ? offS0x : offS0) + (qq >> 1) * 1024);
            ldsm4(y, st + (qq & 1 ? offS1x : offS1) + (qq >> 1) * 1024);
#pragma unroll
            for (int e = 0; e < 4; e++) x[e] = hadd2(x[e], y[e]);
            mma8(gr[0], x[0], x[1], x[0]);
            mma8(gr[1], x[0], x[1], x[1]);
            mma(sx, x[0], x[1], x[2], x[3], ONES, ONES);
            mma8(gr[GR4 ? 2 : 0], x[2], x[3], x[2]);
            mma8(gr[GR4 ? 3 : 1], x[2], x[3], x[3]);
            mma(sc[0], qa[8 * qq], qa[8 * qq + 1], qa[8 * qq + 2], qa[8 * qq + 3], x[0], x[1]);
            mma(sc[1], qa[8 * qq + 4], qa[8 * qq + 5], qa[8 * qq + 6], qa[8 * qq + 7], x[2], x[3]);
        }
        ldsm4t(yt, st + offU);
        ldsm2t(yt + 4, st + offV);
#pragma unroll
        for (int i = 0; i < 6; i++) ldsm4t(xt[i], st + (i < 3 ? offT : offTx) + (i % 3) * 1024);

        const float mu = (sx[0] + sx[2]) * (1.f / C), ss = GR4 ? (odd ? (gr[0][1] + gr[1][3]) + (gr[2][1] + gr[3][3]) : (gr[0][0] + gr[1][2]) + (gr[2][0] + gr[3][2])) : (odd ? gr[0][1] + gr[1][3] : gr[0][0] + gr[1][2]);
        const float rs = rsq(fmaxf(fmaf(-mu, mu, fmaf(ss, 1.f / C, 1e-5f)), 1e-5f));
        const float mu0 = __shfl_sync(~0u, mu, shl), mu1 = __shfl_sync(~0u, mu, shl4);
        const float rs0 = __shfl_sync(~0u, rs, shl), rs1 = __shfl_sync(~0u, rs, shl4);
        const float u0 = fmaf(-mu0, r_lo, sc[0][0] + sc[1][0]), u1 = fmaf(-mu1, r_lo, sc[0][1] + sc[1][1]);
        const float u2 = fmaf(-mu0, r_hi, sc[0][2] + sc[1][2]), u3 = fmaf(-mu1, r_hi, sc[0][3] + sc[1][3]);
        const float d0 = fmaf(u0, rs0, -m_lo), d1 = fmaf(u1, rs1, -m_lo), d2 = fmaf(u2, rs0, -m_hi), d3 = fmaf(u3, rs1, -m_hi);
        PH(1, u(d0 + d2));
        float p0 = ex2(d0), p1 = ex2(d1), p2 = ex2(d2), p3 = ex2(d3);
        sts64(pb0 + pw, pack2(p0 * rs0, p1 * rs1), pack2(p2 * rs0, p3 * rs1));
        if (lane < 4) sts32(pb0 + muw, pack2(mu0, mu1));
        const bool over = bar_any(barid, 128, fmaxf(fmaxf(d0, d1), fmaxf(d2, d3)) > LAZY);
        PH(3, 0);
        pa = lds128(pb0 + prd); pb = lds128(pb0 + prd + 512); mv = lds128(pb0 + mur);
        if (elected) mbar_arrive(sb + SM_BAR + (NS + s) * 8);
        if (__builtin_expect(over, 0)) {
            const float s0 = u0 * rs0, s1 = u1 * rs1, s2 = u2 * rs0, s3 = u3 * rs1;
            float xl = fmaxf(s0, s1), xh = fmaxf(s2, s3);
            xl = fmaxf(xl, __shfl_xor_sync(~0u, xl, 1)); xh = fmaxf(xh, __shfl_xor_sync(~0u, xh, 1));
            xl = fmaxf(xl, __shfl_xor_sync(~0u, xl, 2)); xh = fmaxf(xh, __shfl_xor_sync(~0u, xh, 2));
            if (t < 2) sts32(sb + SM_MX + grp * 256 + ((g + 8 * t) * 4 + cw) * 4, u(t ? xh : xl));
            bar_sync(B_MAX + grp, 128);
            const uint4 ml4 = lds128(sb + SM_MX + grp * 256 + g * 16), mh4 = lds128(sb + SM_MX + grp * 256 + g * 16 + 128);
            const float nl = fmaxf(fmaxf(fmaxf(f(ml4.x), f(ml4.y)), fmaxf(f(ml4.z), f(ml4.w))), m_lo);
            const float nh = fmaxf(fmaxf(fmaxf(f(mh4.x), f(mh4.y)), fmaxf(f(mh4.z), f(mh4.w))), m_hi);
            p0 = ex2(s0 - nl); p1 = ex2(s1 - nl); p2 = ex2(s2 - nh); p3 = ex2(s3 - nh);
            sts64(pb0 + pw, pack2(p0 * rs0, p1 * rs1), pack2(p2 * rs0, p3 * rs1));
            const float al = ex2(m_lo - nl), ah = ex2(m_hi - nh);
            m_lo = nl; m_hi = nh;
            l_lo *= al; l_hi *= ah; cm[0] *= al; cm[2] *= ah;
#pragma unroll
            for (int i = 0; i < 6; i++) { acc[i][0] *= al; acc[i][1] *= al; acc[i][2] *= ah; acc[i][3] *= ah; }
            bar_sync(B_MAX + grp, 128);
            pa = lds128(pb0 + prd); pb = lds128(pb0 + prd + 512);
        }
        l_lo += p0 + p1; l_hi += p2 + p3;
        if (stop & 1) break;
#pragma unroll
        for (int i = 0; i < 6; i++) mma(acc[i], pa.x, pa.y, pa.z, pa.w, hadd2v(xt[i][0], yt[i]), hadd2v(xt[i][1], yt[i]));
        mma(cm, pa.x, pa.y, pa.z, pa.w, mv.x, mv.y);
#pragma unroll
        for (int i = 0; i < 6; i++) mma(acc[i], pb.x, pb.y, pb.z, pb.w, hadd2v(xt[i][2], yt[i]), hadd2v(xt[i][3], yt[i]));
        mma(cm, pb.x, pb.y, pb.z, pb.w, mv.z, mv.w);
        PH(4, u(acc[5][0]));
        if (stop) {
            float a = l_lo + __shfl_xor_sync(~0u, l_lo, 1), c = l_hi + __shfl_xor_sync(~0u, l_hi, 1);
            a += __shfl_xor_sync(~0u, a, 2); c += __shfl_xor_sync(~0u, c, 2);
            const uint32_t m = u((t ? m_hi : m_lo) + lg2(fmaxf(t ? c : a, 1.f)));
            if (t < 2) asm volatile("red.relaxed.gpu.global.max.u32 [%0], %1;" ::"l"(g_mmax + g + 8 * t), "r"(m >> 31 ? ~m : m | 0x80000000u) : "memory");
        }
        pb0 ^= pbx;
        s += 2;
        if (s >= NS) { s -= NS; ph ^= 1; }
    }
    const uint32_t ref_lo = lds32(sb + SM_M + mof), ref_hi = lds32(sb + SM_M + 32 + mof);
    const float al = ex2(m_lo - f(ref_lo)), ah = ex2(m_hi - f(ref_hi));
    mma(cm, pa.x, pa.y, pa.z, pa.w, mv.x, mv.y);
#pragma unroll
    for (int i = 3; i < 6; i++) mma(acc[i], pa.x, pa.y, pa.z, pa.w, hadd2v(xt[i][0], yt[i]), hadd2v(xt[i][1], yt[i]));
    mma(cm, pb.x, pb.y, pb.z, pb.w, mv.z, mv.w);
#pragma unroll
    for (int i = 3; i < 6; i++) mma(acc[i], pb.x, pb.y, pb.z, pb.w, hadd2v(xt[i][2], yt[i]), hadd2v(xt[i][3], yt[i]));
#pragma unroll
    for (int i = 0; i < 3; i++) mma(acc[i], pa.x, pa.y, pa.z, pa.w, hadd2v(xt[i][0], yt[i]), hadd2v(xt[i][1], yt[i]));
#pragma unroll
    for (int i = 0; i < 3; i++) mma(acc[i], pb.x, pb.y, pb.z, pb.w, hadd2v(xt[i][2], yt[i]), hadd2v(xt[i][3], yt[i]));
    if (threadIdx.x == grp * 128) TSE(2 + grp);
    if (threadIdx.x == grp * 128 + 96) TSX(2 + grp, u(acc[5][0]));

    uint4* const dst = reinterpret_cast<uint4*>(reinterpret_cast<char*>(g_acc) + (dof ^ (ref_lo & PLACE)));
    uint4* const dsu = reinterpret_cast<uint4*>(reinterpret_cast<char*>(g_acc) + (dof ^ (ref_hi & PLACE)));
    const uint32_t xw = sb + SM_STAGES + grp * STAGE + cw * 1536 + prd, xr = sb + SM_STAGES + (grp ^ 1) * STAGE + cw * 1536 + prd;
    const float cl = -cm[0] * al, ch = -cm[2] * ah;
#pragma unroll
    for (int i = 0; i < 3; i++)
        sts128(xw + i * 512, u(fmaf(acc[3 + i][0], al, cl)), u(fmaf(acc[3 + i][1], al, cl)), u(fmaf(acc[3 + i][2], ah, ch)), u(fmaf(acc[3 + i][3], ah, ch)));
#pragma unroll
    for (int i = 0; i < 3; i++) { acc[i][0] = fmaf(acc[i][0], al, cl); acc[i][1] = fmaf(acc[i][1], al, cl); acc[i][2] = fmaf(acc[i][2], ah, ch); acc[i][3] = fmaf(acc[i][3], ah, ch); }
    const uint32_t w_lo = packh(l_lo * al, 1.f), w_hi = packh(l_hi * ah, 1.f);
    bar_sync(B_MERGE, 256);
    if (threadIdx.x == 224) TSX(4, 0);
    uint4 o[3];
#pragma unroll
    for (int i = 0; i < 3; i++) o[i] = lds128(xr + i * 512);
    red8h(dst, packh(acc[0][0] + f(o[0].x), acc[0][1] + f(o[0].y)), packh(acc[1][0] + f(o[1].x), acc[1][1] + f(o[1].y)), packh(acc[2][0] + f(o[2].x), acc[2][1] + f(o[2].y)), w_lo);
    red8h(dsu, packh(acc[0][2] + f(o[0].z), acc[0][3] + f(o[0].w)), packh(acc[1][2] + f(o[1].z), acc[1][3] + f(o[1].w)), packh(acc[2][2] + f(o[2].z), acc[2][3] + f(o[2].w)), w_hi);
    if (threadIdx.x == 0) TSE(4);
    if (threadIdx.x == 224) TSX(9, 0);
}

typedef CUresult (*EncodeFn)(CUtensorMap*, CUtensorMapDataType, cuuint32_t, void*, const cuuint64_t*, const cuuint64_t*,
                             const cuuint32_t*, const cuuint32_t*, CUtensorMapInterleave, CUtensorMapSwizzle,
                             CUtensorMapL2promotion, CUtensorMapFloatOOBfill);

}

extern "C" void kernel_launch(void* const* d_in, const int* in_sizes, int n_in, void* d_out, int out_size) {
    const __nv_bfloat16* q = (const __nv_bfloat16*)d_in[0];
    char* f0 = (char*)d_in[1];
    char* f1 = (char*)d_in[2];
    const __nv_bfloat16* wq = (const __nv_bfloat16*)d_in[3];
    const __nv_bfloat16* wk = (const __nv_bfloat16*)d_in[4];
    const __nv_bfloat16* wv = (const __nv_bfloat16*)d_in[5];
    const __nv_bfloat16* wo = (const __nv_bfloat16*)d_in[6];

    static EncodeFn enc = nullptr;
    static int grid = 0;
    static Scratch* scr = nullptr;
    if (!enc) {
        void* fn = nullptr; cudaDriverEntryPointQueryResult qr;
        cudaGetDriverEntryPoint("cuTensorMapEncodeTiled", &fn, cudaEnableDefault, &qr);
        enc = (EncodeFn)fn;
        cudaGetSymbolAddress((void**)&scr, g_scratch);
        int dev = 0, sms = 0;
        cudaGetDevice(&dev);
        cudaDeviceGetAttribute(&sms, cudaDevAttrMultiProcessorCount, dev);
        grid = sms < MAXG ? sms : MAXG;
        cudaFuncSetAttribute(attn_main, cudaFuncAttributeMaxDynamicSharedMemorySize, SMEM_BYTES);
    }
    CUtensorMap m0, m1;
    {
        cuuint64_t dims[5] = {64, W1, 3, 2, W0};
        cuuint64_t str[4] = {2 * C * 2, 128, C * 2, (cuuint64_t)W0 * C * 2};
        cuuint32_t box[5] = {64, TP, 3, 2, 2}, es[5] = {1, 1, 1, 1, 1};
        enc(&m0, CU_TENSOR_MAP_DATA_TYPE_BFLOAT16, 5, f0, dims, str, box, es, CU_TENSOR_MAP_INTERLEAVE_NONE,
            CU_TENSOR_MAP_SWIZZLE_128B, CU_TENSOR_MAP_L2_PROMOTION_NONE, CU_TENSOR_MAP_FLOAT_OOB_FILL_NONE);
    }
    {
        cuuint64_t dims[4] = {64, W1, 3, W1};
        cuuint64_t str[3] = {C * 2, 128, (cuuint64_t)W1 * C * 2};
        cuuint32_t box[4] = {64, TP, 3, 1}, es[4] = {1, 1, 1, 1};
        enc(&m1, CU_TENSOR_MAP_DATA_TYPE_BFLOAT16, 4, f1, dims, str, box, es, CU_TENSOR_MAP_INTERLEAVE_NONE,
            CU_TENSOR_MAP_SWIZZLE_128B, CU_TENSOR_MAP_L2_PROMOTION_NONE, CU_TENSOR_MAP_FLOAT_OOB_FILL_NONE);
    }
    attn_main<<<grid, NTHREADS, SMEM_BYTES, cudaStreamPerThread>>>(f0, f1, q, wq, wk, scr, wv, wo, (__nv_bfloat16*)d_out, m0, m1);
}
```

```cpp
#include <cuda_runtime.h>
#include <cuda_bf16.h>
#include <cuda.h>
#include <stdint.h>

namespace {

constexpr int C = 192;
constexpr int NQ = 16;
constexpr int W0 = 512;
constexpr int W1 = 256;
constexpr int TP = 8;
constexpr int NT = W1 * W1 / TP;
constexpr int STAGE = TP * 5 * C * 2;
#define NS 14
#define D0 3
#define D1 2
#define D2 1
#define NRAMP 5
#define TAILT 150
#define TA (p ? 470 : 185)
#define TB 0
#define HX 1
#define QSLEEP 700
#define WSL 24
#define MAXT 3000
#define REFT 1800
#define POLLN 1
#define PGAP 64
#define NPW 5
#define NPROBE 8
#define LAZY 12.f
#define GR4 1
#define NST 4
#define NI 1
#define NPACE 5
#define T0 0
#define T1 1600
#define TG 960
static_assert(NST > D0, "the first dynamic tile index must not delay the start");
constexpr int NTHREADS = 384;
constexpr int MAXG = 132;
constexpr int NRD = NQ;
constexpr int NSRC = 12;
constexpr int SPIN_LIMIT = 1 << 22;

constexpr int SM_STAGES = 0;
constexpr int SM_P = NS * STAGE;
constexpr int PBUF = 1088;
constexpr int SM_QK = SM_P + 4 * PBUF;
constexpr int SM_MX = SM_QK + 6144;
constexpr int SM_M = SM_MX + 512;
constexpr int SM_BAR = SM_M + 64;
constexpr int SM_REF = SM_BAR + 16 * NS;
constexpr int SM_FLAG = SM_REF + 8;
constexpr int SM_TOTAL = SM_FLAG + 4 * NS;
constexpr int SMEM_BYTES = SM_TOTAL + 1024;
static_assert(SMEM_BYTES <= 232448, "smem");
constexpr int WROW = 400;
constexpr int RD_W = 0;
constexpr int RD_QN = 2 * C * WROW;
constexpr int RD_KQ = RD_QN + 6144;
constexpr int RD_B = RD_KQ + 7168;
constexpr int RD_B2 = 17 * 80;
constexpr int RD_PLACE = RD_B + 2 * RD_B2;
constexpr int RD_BAR = RD_PLACE + 16;
constexpr int RD_A = RD_BAR + 64;
constexpr int RD_WS = RD_A + 12 * 6 * 512;
static_assert(RD_WS + 12 * 128 <= SM_TOTAL, "smem");

struct Scratch {
    uint4 acc[2048];
    uint4 qk[NSRC * 32];
    unsigned ctr[32];
    unsigned mmax[32];
    unsigned mref[32];
};
__device__ __align__(8192) Scratch g_scratch;
#define g_acc (scr->acc)
#define g_qk (scr->qk)
#define g_ctr (scr->ctr)
#define g_mmax (scr->mmax)
#define g_mref (scr->mref)
#define g_ts (scr->ts)
#define g_tr (scr->tr)
#define TR(k, i) do {} while (0)
#define TS(i) do {} while (0)
#define TSD(i, dep) do {} while (0)
#define TSX(i, dep) do {} while (0)
#define TSP(i, dep) do {} while (0)
#define TSE(i) TS(i)
#define CK_(i, dep) do {} while (0)
#define PH(i, dep) do {} while (0)

__device__ __forceinline__ uint32_t s2u(const void* p) { return (uint32_t)__cvta_generic_to_shared(p); }
__device__ __forceinline__ void mbar_init(uint32_t a, int c) { asm volatile("mbarrier.init.shared::cta.b64 [%0], %1;" ::"r"(a), "r"(c) : "memory"); }
__device__ __forceinline__ void mbar_expect(uint32_t a, uint32_t b) { asm volatile("mbarrier.arrive.expect_tx.shared::cta.b64 _, [%0], %1;" ::"r"(a), "r"(b) : "memory"); }
__device__ __forceinline__ void mbar_arrive(uint32_t a) { asm volatile("mbarrier.arrive.shared::cta.b64 _, [%0];" ::"r"(a) : "memory"); }
__device__ __forceinline__ void mbar_wait(uint32_t a, uint32_t ph) {
    uint32_t ok; int it = 0;
    do {
        asm volatile("{.reg .pred p; mbarrier.try_wait.parity.shared::cta.b64 p, [%1], %2; selp.u32 %0,1,0,p;}" : "=r"(ok) : "r"(a), "r"(ph) : "memory");
        if (++it > SPIN_LIMIT) __trap();
    } while (!ok);
}
__device__ __forceinline__ bool elect() {
    uint32_t r; asm volatile("{.reg .pred p; elect.sync _|p, 0xffffffff; selp.u32 %0, 1, 0, p;}" : "=r"(r)); return r;
}
__device__ __forceinline__ void bar_sync(int id, int n) { asm volatile("bar.sync %0, %1;" ::"r"(id), "r"(n) : "memory"); }
__device__ __forceinline__ bool bar_any(int id, int n, bool c) {
    uint32_t r;
    asm volatile("{.reg .pred p, q; setp.ne.u32 q, %3, 0; bar.red.or.pred p, %1, %2, q; selp.u32 %0, 1, 0, p;}" : "=r"(r) : "r"(id), "r"(n), "r"((uint32_t)c) : "memory");
    return r;
}
__device__ __forceinline__ void bar_arrive(int id, int n) { asm volatile("bar.arrive %0, %1;" ::"r"(id), "r"(n) : "memory"); }
__device__ __forceinline__ void ldsm4(uint32_t* r, uint32_t a) {
    asm volatile("ldmatrix.sync.aligned.m8n8.x4.shared.b16 {%0,%1,%2,%3}, [%4];" : "=r"(r[0]), "=r"(r[1]), "=r"(r[2]), "=r"(r[3]) : "r"(a) : "memory");
}
__device__ __forceinline__ void ldsm4t(uint32_t* r, uint32_t a) {
    asm volatile("ldmatrix.sync.aligned.m8n8.x4.trans.shared.b16 {%0,%1,%2,%3}, [%4];" : "=r"(r[0]), "=r"(r[1]), "=r"(r[2]), "=r"(r[3]) : "r"(a) : "memory");
}
__device__ __forceinline__ void ldsm2t(uint32_t* r, uint32_t a) {
    asm volatile("ldmatrix.sync.aligned.m8n8.x2.trans.shared.b16 {%0,%1}, [%2];" : "=r"(r[0]), "=r"(r[1]) : "r"(a) : "memory");
}
__device__ __forceinline__ void mma(float* d, uint32_t a0, uint32_t a1, uint32_t a2, uint32_t a3, uint32_t b0, uint32_t b1) {
    asm("mma.sync.aligned.m16n8k16.row.col.f32.bf16.bf16.f32 {%0,%1,%2,%3}, {%4,%5,%6,%7}, {%8,%9}, {%0,%1,%2,%3};"
        : "+f"(d[0]), "+f"(d[1]), "+f"(d[2]), "+f"(d[3]) : "r"(a0), "r"(a1), "r"(a2), "r"(a3), "r"(b0), "r"(b1));
}
__device__ __forceinline__ void mmah(float* d, uint32_t a0, uint32_t a1, uint32_t a2, uint32_t a3, uint32_t b0, uint32_t b1) {
    asm("mma.sync.aligned.m16n8k16.row.col.f32.f16.f16.f32 {%0,%1,%2,%3}, {%4,%5,%6,%7}, {%8,%9}, {%0,%1,%2,%3};"
        : "+f"(d[0]), "+f"(d[1]), "+f"(d[2]), "+f"(d[3]) : "r"(a0), "r"(a1), "r"(a2), "r"(a3), "r"(b0), "r"(b1));
}
__device__ __forceinline__ void mma8(float* d, uint32_t a0, uint32_t a1, uint32_t b0) {
    asm("mma.sync.aligned.m16n8k8.row.col.f32.bf16.bf16.f32 {%0,%1,%2,%3}, {%4,%5}, {%6}, {%0,%1,%2,%3};"
        : "+f"(d[0]), "+f"(d[1]), "+f"(d[2]), "+f"(d[3]) : "r"(a0), "r"(a1), "r"(b0));
}
__device__ __forceinline__ uint32_t hadd2(uint32_t a, uint32_t b) {
    uint32_t r; asm("add.rn.bf16x2 %0, %1, %2;" : "=r"(r) : "r"(a), "r"(b)); return r;
}
__device__ __forceinline__ uint32_t pack2(float lo, float hi) {
    uint32_t r; asm("cvt.rn.bf16x2.f32 %0, %1, %2;" : "=r"(r) : "f"(hi), "f"(lo)); return r;
}
__device__ __forceinline__ uint32_t packh(float lo, float hi) {
    uint32_t r; asm("cvt.rn.f16x2.f32 %0, %1, %2;" : "=r"(r) : "f"(hi), "f"(lo)); return r;
}
__device__ __forceinline__ float2 unpackh(uint32_t v) {
    float2 r; asm("{.reg .b16 l, h; mov.b32 {l, h}, %2; cvt.f32.f16 %0, l; cvt.f32.f16 %1, h;}" : "=f"(r.x), "=f"(r.y) : "r"(v)); return r;
}
__device__ __forceinline__ float bflo(uint32_t v) { return __uint_as_float(v << 16); }
__device__ __forceinline__ float bfhi(uint32_t v) { return __uint_as_float(v & 0xffff0000u); }
__device__ __forceinline__ float ex2(float x) { float r; asm("ex2.approx.ftz.f32 %0, %1;" : "=f"(r) : "f"(x)); return r; }
__device__ __forceinline__ void sts128(uint32_t a, uint32_t x, uint32_t y, uint32_t z, uint32_t w) {
    asm volatile("st.shared.v4.b32 [%0], {%1,%2,%3,%4};" ::"r"(a), "r"(x), "r"(y), "r"(z), "r"(w) : "memory");
}
__device__ __forceinline__ void sts64(uint32_t a, uint32_t x, uint32_t y) {
    asm volatile("st.shared.v2.b32 [%0], {%1,%2};" ::"r"(a), "r"(x), "r"(y) : "memory");
}
__device__ __forceinline__ void sts32(uint32_t a, uint32_t x) { asm volatile("st.shared.b32 [%0], %1;" ::"r"(a), "r"(x) : "memory"); }
__device__ __forceinline__ uint4 lds128(uint32_t a) {
    uint4 v; asm volatile("ld.shared.v4.b32 {%0,%1,%2,%3}, [%4];" : "=r"(v.x), "=r"(v.y), "=r"(v.z), "=r"(v.w) : "r"(a) : "memory"); return v;
}
__device__ __forceinline__ uint2 lds64(uint32_t a) {
    uint2 v; asm volatile("ld.shared.v2.b32 {%0,%1}, [%2];" : "=r"(v.x), "=r"(v.y) : "r"(a) : "memory"); return v;
}
__device__ __forceinline__ uint32_t haddh(uint32_t a, uint32_t b) {
    uint32_t r; asm("add.rn.f16x2 %0, %1, %2;" : "=r"(r) : "r"(a), "r"(b)); return r;
}
__device__ __forceinline__ uint32_t lds32(uint32_t a) { uint32_t v; asm volatile("ld.shared.b32 %0, [%1];" : "=r"(v) : "r"(a) : "memory"); return v; }
__device__ __forceinline__ int grab_tile(unsigned* ctr) {
    int v; asm volatile("atom.relaxed.gpu.global.inc.u32 %0, [%1], 0x7fffffff;" : "=r"(v) : "l"(ctr) : "memory"); return v;
}
__device__ __forceinline__ uint32_t opaque(uint32_t v) { uint32_t r; asm volatile("mov.b32 %0, %1;" : "=r"(r) : "r"(v)); return r; }
__device__ __forceinline__ unsigned clock32() { unsigned c; asm volatile("mov.u32 %0, %%clock;" : "=r"(c)); return c; }
__device__ __forceinline__ float rsq(float x) { float r; asm("rsqrt.approx.ftz.f32 %0, %1;" : "=f"(r) : "f"(x)); return r; }
__device__ __forceinline__ float rcp(float x) { float r; asm("rcp.approx.ftz.f32 %0, %1;" : "=f"(r) : "f"(x)); return r; }
__device__ __forceinline__ float lg2(float x) { float r; asm("lg2.approx.ftz.f32 %0, %1;" : "=f"(r) : "f"(x)); return r; }
__device__ __forceinline__ float f(uint32_t v) { return __uint_as_float(v); }
__device__ __forceinline__ uint32_t u(float v) { return __float_as_uint(v); }

constexpr uint32_t ONES = 0x3F803F80u;
constexpr float QSCALE = 0.07216878364870322f * 1.4426950408889634f;

__device__ __forceinline__ void issue_tile(const CUtensorMap* m0, const CUtensorMap* m1, uint32_t sb, int s, int tl, uint64_t pol) {
    const uint32_t full = sb + SM_BAR + s * 8, dst = sb + SM_STAGES + s * STAGE;
    const int par = tl * TP, y = par >> 8, x = par & 255;
    mbar_expect(full, STAGE);
    asm volatile("cp.async.bulk.tensor.5d.shared::cluster.global.mbarrier::complete_tx::bytes.L2::cache_hint [%0], [%1, {%3,%4,%3,%3,%5}], [%2], %6;"
                 ::"r"(dst), "l"(m0), "r"(full), "r"(0), "r"(x), "r"(2 * y), "l"(pol) : "memory");
    asm volatile("cp.async.bulk.tensor.4d.shared::cluster.global.mbarrier::complete_tx::bytes.L2::cache_hint [%0], [%1, {%3,%4,%3,%5}], [%2], %6;"
                 ::"r"(dst + TP * 4 * C * 2), "l"(m1), "r"(full), "r"(0), "r"(x), "r"(y), "l"(pol) : "memory");
}

__device__ __forceinline__ void prefetch_l2(const void* a, int n) { asm volatile("cp.async.bulk.prefetch.L2.global [%0], %1;" ::"l"(a), "r"(n) : "memory"); }
__device__ __forceinline__ uint4 ldg_relaxed(const uint4* p) {
    uint4 v; asm volatile("ld.relaxed.gpu.global.v4.u32 {%0,%1,%2,%3}, [%4];" : "=r"(v.x), "=r"(v.y), "=r"(v.z), "=r"(v.w) : "l"(p) : "memory"); return v;
}
__device__ __forceinline__ uint32_t ldg_relaxed32(const void* p) {
    uint32_t v; asm volatile("ld.relaxed.gpu.global.u32 %0, [%1];" : "=r"(v) : "l"(p) : "memory"); return v;
}
__device__ __forceinline__ void stg_relaxed(uint4* p, uint32_t x, uint32_t y, uint32_t z, uint32_t w) {
    asm volatile("st.relaxed.gpu.global.v4.u32 [%0], {%1,%2,%3,%4};" ::"l"(p), "r"(x), "r"(y), "r"(z), "r"(w) : "memory");
}
__device__ __forceinline__ void stg_relaxed32(void* p, uint32_t x) { asm volatile("st.relaxed.gpu.global.u32 [%0], %1;" ::"l"(p), "r"(x) : "memory"); }
__device__ __forceinline__ bool has(const uint4& v, uint32_t m) { return v.x == m || v.y == m || v.z == m || v.w == m; }
__device__ __forceinline__ uint32_t hadd2v(uint32_t a, uint32_t b) {
    uint32_t r; asm volatile("add.rn.bf16x2 %0, %1, %2;" : "=r"(r) : "r"(a), "r"(b)); return r;
}

__device__ __forceinline__ void red8h(uint4* p, uint32_t x, uint32_t y, uint32_t z, uint32_t w) {
    asm volatile("red.relaxed.gpu.global.add.noftz.v4.f16x2 [%0], {%1,%2,%3,%4};" ::"l"(p), "r"(x), "r"(y), "r"(z), "r"(w) : "memory");
}
__device__ __forceinline__ uint4 lds128v(uint32_t a) {
    uint4 v; asm volatile("ld.volatile.shared.v4.b32 {%0,%1,%2,%3}, [%4];" : "=r"(v.x), "=r"(v.y), "=r"(v.z), "=r"(v.w) : "r"(a) : "memory"); return v;
}
__device__ __forceinline__ uint32_t brow(int r) { return RD_B + r * 80 + (r >> 3) * 64; }

constexpr uint32_t PLACE = 0x1980;
__device__ __forceinline__ uint32_t acc_line(int k) { return (k >> 2) * 16384 + (k & 2) * 6144 + (k & 1) * 1024; }
__device__ __forceinline__ uint32_t acc_place(int side, int s) { return side * 4096 + (s & 1) * 256 + (s & 2) * 1024 + (s & 4) * 32; }

enum { B_QK = 1, B_QN = 2, B_GRP = 3  , B_Q = 5, B_MERGE = 6, B_ALL = 7, B_MAX = 1  , B_PAIR = 8  , B_WARP = 10, B_SLOW = 12, B_PARK = 13, B_PLACE = 14, B_RDY = 15 };

__device__ __noinline__ void slow_rows(const char* __restrict__ f0, const char* __restrict__ f1, const __nv_bfloat16* __restrict__ q,
                                       const __nv_bfloat16* __restrict__ wq, const __nv_bfloat16* __restrict__ wk, const uint32_t sb)
{
    const int warp = threadIdx.x >> 5, lane = threadIdx.x & 31;
    float* const sm = reinterpret_cast<float*>(__cvta_shared_to_generic(sb + RD_W));
    for (int i = threadIdx.x; i < 2 * C; i += 128) sm[i] = __bfloat162float(q[(blockIdx.x & 14) * C + i]);
    bar_sync(B_SLOW, 128);
#pragma unroll 1
    for (int j = threadIdx.x; j < 2 * C; j += 128) {
        const float* const x = sm + j / C * C;
        float mu = 0.f, var = 0.f, s = 0.f;
#pragma unroll 1
        for (int i = 0; i < C; i++) mu += x[i];
        mu *= 1.f / C;
#pragma unroll 4
        for (int i = 0; i < C; i++) { var = fmaf(x[i] - mu, x[i] - mu, var); s = fmaf(x[i] - mu, __bfloat162float(wq[i * C + j % C]), s); }
        sm[4 * C + j] = s * rsq(var * (1.f / C) + 1e-5f);
    }
    bar_sync(B_SLOW, 128);
#pragma unroll 1
    for (int j = threadIdx.x; j < 2 * C; j += 128) {
        float s = 0.f;
#pragma unroll 4
        for (int i = 0; i < C; i++) s = fmaf(sm[4 * C + j / C * C + i], __bfloat162float(wk[j % C * C + i]), s);
        sm[j] = s * QSCALE;
    }
    bar_sync(B_SLOW, 128);
    float k[2][6], a[2][6], m[2], l[2];
#pragma unroll
    for (int r = 0; r < 2; r++) {
        m[r] = -INFINITY; l[r] = 0.f;
#pragma unroll
        for (int i = 0; i < 6; i++) { k[r][i] = sm[r * C + 64 * (i >> 1) + 2 * lane + (i & 1)]; a[r][i] = 0.f; }
    }
#pragma unroll 1
    for (int par = warp; par < W1 * W1; par += 4) {
        const uint32_t* p0 = reinterpret_cast<const uint32_t*>(f0 + (size_t)((par >> 8) * 2 * W0 + (par & 255) * 2) * (C * 2)) + lane;
        const uint32_t* p1 = reinterpret_cast<const uint32_t*>(f1 + (size_t)par * (C * 2)) + lane;
        uint32_t v[4][3];
#pragma unroll
        for (int i = 0; i < 3; i++)
#pragma unroll
            for (int j = 0; j < 4; j++) v[j][i] = hadd2(__ldg(p0 + ((j >> 1) * W0 + (j & 1)) * (C / 2) + 32 * i), __ldg(p1 + 32 * i));
#pragma unroll
        for (int j = 0; j < 4; j++) {
            float x[6], s1 = 0.f, s2 = 0.f, d[2] = {0.f, 0.f};
#pragma unroll
            for (int i = 0; i < 3; i++) { x[2 * i] = bflo(v[j][i]); x[2 * i + 1] = bfhi(v[j][i]); s1 += x[2 * i] + x[2 * i + 1]; }
#pragma unroll
            for (int o = 1; o < 32; o <<= 1) s1 += __shfl_xor_sync(~0u, s1, o);
#pragma unroll
            for (int i = 0; i < 6; i++) {
                x[i] -= s1 * (1.f / C); s2 = fmaf(x[i], x[i], s2);
#pragma unroll
                for (int r = 0; r < 2; r++) d[r] = fmaf(x[i], k[r][i], d[r]);
            }
#pragma unroll
            for (int o = 1; o < 32; o <<= 1) {
                s2 += __shfl_xor_sync(~0u, s2, o);
#pragma unroll
                for (int r = 0; r < 2; r++) d[r] += __shfl_xor_sync(~0u, d[r], o);
            }
            const float rs = rsq(s2 * (1.f / C) + 1e-5f);
#pragma unroll
            for (int r = 0; r < 2; r++) {
                const float nm = fmaxf(m[r], d[r] * rs), al = ex2(m[r] - nm), p = ex2(d[r] * rs - nm);
                m[r] = nm; l[r] = fmaf(l[r], al, p);
#pragma unroll
                for (int i = 0; i < 6; i++) a[r][i] = fmaf(a[r][i], al, x[i] * (p * rs));
            }
        }
    }
    bar_sync(B_SLOW, 128);
#pragma unroll
    for (int r = 0; r < 2; r++) {
        float* const o = sm + ((r * 4 + warp) * 32 + lane) * 8;
#pragma unroll
        for (int i = 0; i < 6; i++) o[i] = a[r][i];
        o[6] = l[r]; o[7] = m[r];
    }
    bar_sync(B_SLOW, 128);
    if (warp < 2) {
        const int r = warp;
        const float* const o = sm + (r * 128 + lane) * 8;
        float M = o[7], x[7] = {0.f, 0.f, 0.f, 0.f, 0.f, 0.f, 0.f};
#pragma unroll
        for (int w = 1; w < 4; w++) M = fmaxf(M, o[256 * w + 7]);
#pragma unroll
        for (int w = 0; w < 4; w++) {
            const float e = ex2(o[256 * w + 7] - M);
#pragma unroll
            for (int i = 0; i < 7; i++) x[i] = fmaf(o[256 * w + i], e, x[i]);
        }
        const float rl = 1.f / x[6];
        sts128(sb + RD_B2 + brow(8 * (lane >> 4) + 4 * r + (lane & 3)) + ((lane >> 2) & 3) * 16, packh(x[0] * rl, x[1] * rl), packh(x[2] * rl, x[3] * rl), packh(x[4] * rl, x[5] * rl), lane ? 0u : 0x3C00u);
    }
}

template <bool FIRST>
__device__ __forceinline__ void project(const uint32_t ar, const uint32_t br, const bool hi, const float ws0, const float ws1, const float qv0, const float qv1,
                                        __nv_bfloat16* op0, __nv_bfloat16* op1, Scratch* scr)
{
    uint4 wa[3][6], x[4];
#pragma unroll
    for (int i = 0; i < 18; i++) wa[i / 6][i % 6] = lds128v(ar + i * 512);
    if (FIRST) { bar_arrive(B_PLACE, NTHREADS); bar_sync(B_RDY, 192); }
    else bar_sync(B_SLOW, 128);
    if (FIRST && threadIdx.x == 0) TSX(8, 0);
#pragma unroll
    for (int j = 0; j < 4; j++) x[j] = lds128v(br + 16 * j);
    float o[7][4];
#pragma unroll
    for (int j = 0; j < 7; j++) o[j][0] = o[j][1] = o[j][2] = o[j][3] = 0.f;
#pragma unroll
    for (int i = 0; i < 2; i++) {
        mmah(o[6], 0x3C00u, 0x3C00u, 0x3C00u, 0x3C00u, x[2 * i].w, x[2 * i + 1].w);
#pragma unroll
        for (int n = 0; n < 3; n++) mmah(o[2 * n + i], wa[n][2 * i].x, wa[n][2 * i].y, wa[n][2 * i].z, wa[n][2 * i].w, x[2 * i].x, x[2 * i].y);
#pragma unroll
        for (int n = 0; n < 3; n++) mmah(o[2 * n + 1 - i], wa[n][2 * i + 1].x, wa[n][2 * i + 1].y, wa[n][2 * i + 1].z, wa[n][2 * i + 1].w, x[2 * i + 1].x, x[2 * i + 1].y);
#pragma unroll
        for (int n = 0; n < 3; n++) mmah(o[2 * n + i], wa[n][4 + i].x, wa[n][4 + i].y, wa[n][4 + i].z, wa[n][4 + i].w, x[2 * i].z, x[2 * i + 1].z);
    }
    const float L = o[6][0] + o[6][1], r = rcp(L);
    const float y0 = hi ? (o[2][0] + o[2][3]) + (o[3][0] + o[3][3]) : (o[0][0] + o[0][3]) + (o[1][0] + o[1][3]), y1 = (o[4][0] + o[4][3]) + (o[5][0] + o[5][3]);
    const uint32_t y = pack2(fmaf(y0, r * ws0, qv0), fmaf(y1, r * ws1, qv1));
    asm volatile("{.reg .b16 l, h; mov.b32 {l, h}, %2; st.global.b16 [%0], l; st.global.b16 [%1], h;}" ::"l"(op0), "l"(op1), "r"(y) : "memory");
    if (FIRST && threadIdx.x == 0) TSD(11, y);
    if (FIRST)
        asm volatile("{.reg .pred p; .reg .f32 a; abs.f32 a, %1; setp.ge.f32 p, %0, 0f3B000000; setp.le.and.f32 p, %0, 0f45000000, p; setp.lt.and.f32 p, a, 0f7F800000, p;"
                     " vote.sync.all.pred p, p, 0xffffffff; @p exit;}" ::"f"(L), "f"(y0) : "memory");
}

__device__ __forceinline__ void reducer(const char* __restrict__ f0, const char* __restrict__ f1, const __nv_bfloat16* __restrict__ q, const __nv_bfloat16* __restrict__ wq, const __nv_bfloat16* __restrict__ wk,
                                        Scratch* scr, const __nv_bfloat16* __restrict__ wv, const __nv_bfloat16* __restrict__ wo,
                                        __nv_bfloat16* __restrict__ out, const uint32_t sb, const int GS)
{
    const int warp = threadIdx.x >> 5, lane = threadIdx.x & 31, b = blockIdx.x;
    const int g = lane >> 2, t = lane & 3;
    char* const ap = reinterpret_cast<char*>(g_acc);
    if (threadIdx.x == 256) TS(0);
    if (b < NSRC && warp < 8) {
        const uint32_t wqs = sb + RD_W, wbar = sb + RD_BAR;
        const int hr = lane >> 4, qt = (lane >> 2) & 3, sub = lane & 3;
        const uint32_t* qp = reinterpret_cast<const uint32_t*>(q + (warp + 8 * hr) * C + 48 * qt + 6 * sub);
        uint32_t qw[6];
#pragma unroll
        for (int j = 0; j < 3; j++) { qw[j] = __ldg(qp + j); qw[3 + j] = __ldg(qp + 12 + j); }
        if (lane == 0) { mbar_init(wbar + warp * 8, 1); asm volatile("fence.mbarrier_init.release.cluster;" ::: "memory"); mbar_expect(wbar + warp * 8, 9216);
            asm volatile("cp.async.bulk.shared::cluster.global.mbarrier::complete_tx::bytes [%0], [%1], 9216, [%2];"
                         ::"r"(wqs + warp * 9232), "l"(wq + 24 * warp * C), "r"(wbar + warp * 8) : "memory");
        }
        __syncwarp();
        if (threadIdx.x == 0) TSP(2, 0);
        float e[12];
#pragma unroll
        for (int j = 0; j < 6; j++) { e[2 * j] = bflo(qw[j]); e[2 * j + 1] = bfhi(qw[j]); }
        float sm = ((e[0] + e[1]) + (e[2] + e[3])) + ((e[4] + e[5]) + (e[6] + e[7])) + ((e[8] + e[9]) + (e[10] + e[11]));
#pragma unroll
        for (int o = 1; o < 16; o <<= 1) sm += __shfl_xor_sync(~0u, sm, o);
        if (threadIdx.x == 0) TSP(5, u(sm));
        float v0 = 0.f, v1 = 0.f;
#pragma unroll
        for (int j = 0; j < 12; j++) e[j] -= sm * (1.f / C);
#pragma unroll
        for (int j = 0; j < 6; j++) { v0 = fmaf(e[j], e[j], v0); v1 = fmaf(e[6 + j], e[6 + j], v1); }
        v0 += v1;
#pragma unroll
        for (int o = 1; o < 16; o <<= 1) v0 += __shfl_xor_sync(~0u, v0, o);
        const float rq = rsq(v0 * (1.f / C) + 1e-5f);
#pragma unroll
        for (int j = 0; j < 6; j++)
            sts32(sb + RD_QN + (3 * sub + (j >> 1)) * 512 + (4 * warp + qt) * 16 + (2 * (j & 1) + hr) * 4, pack2(e[j] * rq, e[6 + j] * rq));
        if (threadIdx.x == 0) TSP(8, 0);
        uint32_t wkf[2][3];
#pragma unroll
        for (int i = 0; i < 2; i++)
#pragma unroll
            for (int j = 0; j < 3; j++) wkf[i][j] = __ldg(reinterpret_cast<const uint32_t*>(wk + (16 * b + 8 * i + g) * C + 24 * warp + 8 * j + 2 * t));
        bar_sync(B_QN, 256);
        float acc[2][3][4];
#pragma unroll
        for (int i = 0; i < 3; i++)
#pragma unroll
            for (int e = 0; e < 4; e++) acc[0][i][e] = acc[1][i][e] = 0.f;
        const uint32_t ba = wqs + (lane & 7) * 9232 + (lane >> 3) * 384 + 48 * warp;
        uint4 a[12];
#pragma unroll
        for (int kk = 0; kk < 12; kk++) a[kk] = lds128(sb + RD_QN + kk * 512 + lane * 16);
        mbar_wait(wbar + (lane & 7) * 8, 0);
        __syncwarp();
        if (threadIdx.x == 0) TSP(4, 0);
#pragma unroll
        for (int kp = 0; kp < 6; kp++)
#pragma unroll
            for (int i = 0; i < 3; i++) {
                uint32_t bb[4];
                ldsm4t(bb, ba + kp * 1536 + i * 16);
                mma(acc[0][i], a[2 * kp].x, a[2 * kp].y, a[2 * kp].z, a[2 * kp].w, bb[0], bb[1]);
                mma(acc[1][i], a[2 * kp + 1].x, a[2 * kp + 1].y, a[2 * kp + 1].z, a[2 * kp + 1].w, bb[2], bb[3]);
            }
        if (threadIdx.x == 0) TSP(7, u(acc[1][2][3]));
        float kq[2][4] = {{0.f, 0.f, 0.f, 0.f}, {0.f, 0.f, 0.f, 0.f}};
#pragma unroll
        for (int j = 0; j < 3; j++) {
            const uint32_t a0 = pack2(acc[0][j][0] + acc[1][j][0], acc[0][j][1] + acc[1][j][1]), a1 = pack2(acc[0][j][2] + acc[1][j][2], acc[0][j][3] + acc[1][j][3]);
            mma8(kq[0], a0, a1, wkf[0][j]);
            mma8(kq[1], a0, a1, wkf[1][j]);
        }
        if (warp < 7) {
            sts128(sb + RD_KQ + warp * 1024 + lane * 16, u(kq[0][0]), u(kq[0][1]), u(kq[0][2]), u(kq[0][3]));
            sts128(sb + RD_KQ + warp * 1024 + 512 + lane * 16, u(kq[1][0]), u(kq[1][1]), u(kq[1][2]), u(kq[1][3]));
            bar_arrive(B_Q, 256);
        } else {
            bar_sync(B_Q, 256);
#pragma unroll
            for (int w = 0; w < 7; w++)
#pragma unroll
                for (int i = 0; i < 2; i++) {
                    const uint4 o = lds128(sb + RD_KQ + w * 1024 + i * 512 + lane * 16);
                    kq[i][0] += f(o.x); kq[i][1] += f(o.y); kq[i][2] += f(o.z); kq[i][3] += f(o.w);
                }
            stg_relaxed(g_qk + b * 32 + lane, ~pack2(kq[0][0] * QSCALE, kq[0][1] * QSCALE), ~pack2(kq[0][2] * QSCALE, kq[0][3] * QSCALE),
                        ~pack2(kq[1][0] * QSCALE, kq[1][1] * QSCALE), ~pack2(kq[1][2] * QSCALE, kq[1][3] * QSCALE));
            if (lane == 0) TS(10);
        }
    } else if (warp == 8 && !(b & 1)) {
        char* const pp = ap + (b >> 2) * 8192 + (b & 2) * 512;
        if (lane < 16) stg_relaxed(reinterpret_cast<uint4*>(pp + (lane >> 3) * 4096) + (lane & 7), 0, 0, 0, 0);
        __syncwarp();
        uint32_t place = 0;
        if (lane == 0) {
            uint32_t best[2] = {~0u, ~0u};
#pragma unroll 1
            for (int it = 0; it < NPROBE; it++) {
#pragma unroll
                for (int i = 0; i < 2; i++) {
                    uint32_t c;
                    asm volatile("{.reg .b32 v, c0; .reg .pred p; mov.u32 c0, %%clock; atom.relaxed.gpu.global.exch.b32 v, [%1], 0; setp.ne.u32 p, v, 0; @p trap;"
                                 " mov.u32 %0, %%clock; sub.u32 %0, %0, c0;}" : "=r"(c) : "l"(pp + i * 4096) : "memory");
                    best[i] = min(best[i], c);
                }
            }
            place = acc_place((best[1] < best[0]) ^ ((b >> 2) & 1), b >> 1);
            sts32(sb + RD_PLACE, place);
        }
        place = __shfl_sync(~0u, place, 0);
#pragma unroll
        for (int i = 0; i < 2; i++) stg_relaxed(reinterpret_cast<uint4*>(ap + (acc_line(4 * i + (lane >> 3)) ^ place)) + (lane & 7), 0, 0, 0, 0);
        __threadfence();
    } else if (b >= NSRC) {
        if (b == NSRC && warp == 0) stg_relaxed32(g_mmax + lane, 0);
        __nanosleep(2500);
    }
    bar_sync(B_ALL, NTHREADS);

#pragma unroll 1
    for (int r = 0; r < 3; r++) {
        uint4 v[8];
#pragma unroll
        for (int k = 0; k < 8; k++) {
            const int idx = (8 * r + k) * 384 + threadIdx.x;
            v[k] = __ldg(reinterpret_cast<const uint4*>(idx < 4608 ? wv : wo - C * C) + idx);
        }
#pragma unroll
        for (int k = 0; k < 8; k++) {
            const int idx = (8 * r + k) * 384 + threadIdx.x, row = idx / 24;
            sts128(sb + RD_W + row * WROW + (idx - 24 * row) * 16, v[k].x, v[k].y, v[k].z, v[k].w);
        }
    }
    bar_sync(B_ALL, NTHREADS);
    if (warp < 6) {
        const int col = 96 * (b & 1) + 16 * warp;
        float d[24][4];
#pragma unroll
        for (int i = 0; i < 24; i++) d[i][0] = d[i][1] = d[i][2] = d[i][3] = 0.f;
        const int mi = lane >> 3, r = lane & 7;
        const uint32_t aa = sb + RD_W + (C + (mi >> 1) * 8 + r) * WROW + (col + (mi & 1) * 8) * 2;
        const uint32_t ba = sb + RD_W + ((mi >> 1) * 8 + r) * WROW + (mi & 1) * 16;
#pragma unroll 1
        for (int kk = 0; kk < 12; kk++) {
            uint32_t a[4];
            ldsm4t(a, aa + kk * 16 * WROW);
#pragma unroll
            for (int i = 0; i < 12; i++) {
                uint32_t bb[4];
                ldsm4(bb, ba + i * 16 * WROW + kk * 32);
                mma(d[2 * i], a[0], a[1], a[2], a[3], bb[0], bb[1]);
                mma(d[2 * i + 1], a[0], a[1], a[2], a[3], bb[2], bb[3]);
            }
        }
        float c0 = 0.f, c1 = 0.f, m0 = 0.f, m1 = 0.f;
#pragma unroll
        for (int i = 0; i < 24; i++) { c0 += d[i][0] + d[i][1]; c1 += d[i][2] + d[i][3]; }
        c0 += __shfl_xor_sync(~0u, c0, 1); c1 += __shfl_xor_sync(~0u, c1, 1);
        c0 += __shfl_xor_sync(~0u, c0, 2); c1 += __shfl_xor_sync(~0u, c1, 2);
        c0 *= 1.f / C; c1 *= 1.f / C;
#pragma unroll
        for (int i = 0; i < 24; i++) {
            d[i][0] -= c0; d[i][1] -= c0; d[i][2] -= c1; d[i][3] -= c1;
            m0 = fmaxf(m0, fmaxf(fabsf(d[i][0]), fabsf(d[i][1]))); m1 = fmaxf(m1, fmaxf(fabsf(d[i][2]), fabsf(d[i][3])));
        }
        m0 = fmaxf(m0, __shfl_xor_sync(~0u, m0, 1)); m1 = fmaxf(m1, __shfl_xor_sync(~0u, m1, 1));
        m0 = fmaxf(m0, __shfl_xor_sync(~0u, m0, 2)); m1 = fmaxf(m1, __shfl_xor_sync(~0u, m1, 2));
        const uint32_t e0 = min(max(u(m0) >> 23, 12u), 254u), e1 = min(max(u(m1) >> 23, 12u), 254u);
        const float s0 = f((265u - e0) << 23), s1 = f((265u - e1) << 23);
        const bool k0 = fabsf(c0) < INFINITY, k1 = fabsf(c1) < INFINITY;
#pragma unroll
        for (int j = 0; j < 6; j++) {
            const int n[4] = {j < 4 ? j : 8 + 2 * j, j < 4 ? 4 + j : 12 + 2 * j, j < 4 ? 8 + j : 9 + 2 * j, j < 4 ? 12 + j : 13 + 2 * j};
            uint32_t a[2][4];
#pragma unroll
            for (int e = 0; e < 4; e++) {
                a[0][e] = k0 ? packh(d[n[e]][0] * s0, d[n[e]][1] * s0) : 0u;
                a[1][e] = k1 ? packh(d[n[e]][2] * s1, d[n[e]][3] * s1) : 0u;
            }
#pragma unroll
            for (int e = 0; e < 2; e++) sts128(sb + RD_A + ((2 * warp + e) * 6 + j) * 512 + lane * 16, a[e][0], a[e][1], a[e][2], a[e][3]);
        }
        sts32(sb + RD_WS + 2 * warp * 128 + lane * 4, k0 ? (e0 - 11u) << 23 : u(c0));
        sts32(sb + RD_WS + (2 * warp + 1) * 128 + lane * 4, k1 ? (e1 - 11u) << 23 : u(c1));
        if (warp < 4) bar_sync(B_PARK, 192); else bar_arrive(B_PARK, 192);
        if (threadIdx.x == 0) TSE(6);
    }
    if (warp >= 4) {
        if (threadIdx.x == 128) {
            uint32_t m, place = lds32(sb + RD_PLACE);
            for (int it = 0;; it++) {
                const int left = NT - 2 * NST * GS - (int)ldg_relaxed32(g_ctr);
                m = ldg_relaxed32(g_mmax + b);
                if (left <= REFT && m) break;
                if (left <= 0) { m = 0x80000000u; break; }
                if (it > SPIN_LIMIT) __trap();
                __nanosleep(300);
            }
            if (b & 1) for (int it = 0;; it++) {
                uint32_t r;
                asm volatile("ld.acquire.gpu.global.u32 %0, [%1];" : "=r"(r) : "l"(g_mref + b - 1) : "memory");
                place = ~r & PLACE;
                if (r) break;
                if (it > SPIN_LIMIT) __trap();
            }
            asm volatile("st.release.gpu.global.u32 [%0], %1;" ::"l"(g_mref + b), "r"(~((u(f(m >> 31 ? m ^ 0x80000000u : ~m) + 8.f) & ~PLACE) | place)) : "memory");
            sts32(sb + RD_PLACE, place);
            TSE(7);
        }
        __syncwarp();
        if (warp == 4) {
            uint4* p0 = g_qk + min(b, NSRC - 1) * 32 + lane;
            unsigned* p1 = lane == 1 && b == NSRC ? g_ctr : g_mref + b;
            asm volatile("" : "+l"(p0), "+l"(p1));
            bar_arrive(B_PLACE, NTHREADS);
            bar_sync(B_RDY, 192);
            *p0 = make_uint4(0, 0, 0, 0);
            *p1 = 0;
            return;
        }
        bar_sync(B_PLACE, NTHREADS);
        if (warp >= 5 + NPW) return;
        const uint32_t place = lds32(sb + RD_PLACE);
        const uint4* const pa = reinterpret_cast<const uint4*>(ap + (acc_line(lane >> 3) ^ place)) + (lane & 7);
        const uint32_t bw = opaque(sb + brow(lane & 7) + (lane >> 3) * 16);
        const uint32_t n0 = packh(0.f, (float)GS), nstart = packh(0.f, (float)POLLN);
        for (int it = 0; ldg_relaxed32(ap + place + 12) < nstart; it++)
            if (it > SPIN_LIMIT) __trap();
        for (const unsigned c = clock32(); clock32() - c < (warp - 5) * PGAP;) {}
        for (int it = 0;; it++) {
            const uint4 a0 = ldg_relaxed(pa), b0 = ldg_relaxed(pa + 1024);
            if (it > SPIN_LIMIT) __trap();
            bar_sync(B_WARP, 32);
            asm volatile("{.reg .pred p, q; .reg .b32 a; setp.ge.u32 p, %5, %10; setp.ge.and.u32 p, %9, %10, p; vote.sync.all.pred q, p, 0xffffffff; selp.b32 a, %0, %1, p;"
                         " st.shared.v4.b32 [a], {%2,%3,%4,%5}; st.shared.v4.b32 [a + 704], {%6,%7,%8,%9}; @q bar.arrive 15, 192; @q exit;}"
                         ::"r"(bw), "r"(bw - (RD_B - RD_QN)), "r"(a0.x), "r"(a0.y), "r"(a0.z), "r"(a0.w), "r"(b0.x), "r"(b0.y), "r"(b0.z), "r"(b0.w), "r"(n0) : "memory");
        }
    }
    const uint32_t br = opaque(sb + brow(8 * (g & 1) + 2 * (g & 2) + t));
    const bool hi = t >= 2;
    const int oi = ((b & 14) + (t & 1)) * C + 96 * (b & 1) + 24 * warp + g;
    const float qv0 = __bfloat162float(q[oi + 4 * (t & 2)]), qv1 = __bfloat162float(q[oi + 16]);
    const float ws0 = f(lds32(sb + RD_WS + (3 * warp + (t >> 1)) * 128 + lane * 4)), ws1 = f(lds32(sb + RD_WS + (3 * warp + 2) * 128 + lane * 4));
    __nv_bfloat16* op0 = out + oi + 4 * (t & 2), * op1 = out + oi + 16;
    asm volatile("" : "+l"(op0), "+l"(op1));
    const uint32_t ar = sb + RD_A + warp * 18 * 512 + lane * 16;
    project<true>(ar, br, hi, ws0, ws1, qv0, qv1, op0, op1, scr);
    slow_rows(f0, f1, q, wq, wk, sb);
    project<false>(ar, br + RD_B2, hi, ws0, ws1, qv0, qv1, op0, op1, scr);
}

__global__ void __launch_bounds__(NTHREADS, 1)
attn_main(const char* __restrict__ f0, const char* __restrict__ f1,
          const __nv_bfloat16* __restrict__ q, const __nv_bfloat16* __restrict__ wq, const __nv_bfloat16* __restrict__ wk, Scratch* scr,
          const __nv_bfloat16* __restrict__ wv, const __nv_bfloat16* __restrict__ wo, __nv_bfloat16* __restrict__ out,
          const __grid_constant__ CUtensorMap m0, const __grid_constant__ CUtensorMap m1)
{
    extern __shared__ char smem_raw[];
    const uint32_t sb = (s2u(smem_raw) + 1023u) & ~1023u;
    const int G = gridDim.x - NRD;
    const int b = blockIdx.x - NRD;
    if (threadIdx.x == 0 && b >= 0) {
        const char* a = f0 + (uint32_t)(b * (4 * TP * C * 2) + (b >> 4) * (W0 * C * 2));
        prefetch_l2(a, 4 * TP * C * 2);
        prefetch_l2(a + W0 * C * 2, 4 * TP * C * 2);
        prefetch_l2(f1 + b * (2 * TP * C * 2), 2 * TP * C * 2);
        prefetch_l2((const char*)(b % (2 * WSL) < WSL ? wq : wk) + b % WSL * (C * C * 2 / WSL), C * C * 2 / WSL);
    }
    if (b < 0) { reducer(f0, f1, q, wq, wk, scr, wv, wo, out, sb, G); return; }
    const int warp = __shfl_sync(~0u, threadIdx.x >> 5, 0), lane = threadIdx.x & 31;
    const int g = lane >> 2, t = lane & 3;

    if (warp >= 8) {
        if (warp < 10) {
            const int p = warp - 8;
            const unsigned c0 = clock32();
            const uint32_t sbp = opaque(sb), bar = sbp + SM_BAR + p * 8;
            uint64_t pol; asm volatile("createpolicy.fractional.L2::evict_first.b64 %0, 1.0;" : "=l"(pol));
            if (elect()) {
                if (p == 0) TS(0);
                asm volatile("prefetch.tensormap [%0];" ::"l"(p ? &m1 : &m0) : "memory");
#pragma unroll
                for (int n = 0; n < NI; n++) mbar_init(bar + n * 16, 2);
                asm volatile("fence.mbarrier_init.release.cluster;" ::: "memory");
#pragma unroll
                for (int n = 0; n < NI; n++) {
                    issue_tile(&m0, &m1, sbp, p + 2 * n, 2 * b + p + 2 * n * G, pol);
                    TR(0, 2 * n + p);
                    sts32(sbp + SM_FLAG + (p + 2 * n) * 4, 0);
                    mbar_arrive(bar + n * 16);
                }
#pragma unroll
                for (int n = 0; n < NS / 2; n++) {
                    if (n >= NI) mbar_init(bar + n * 16, 2);
                    mbar_init(bar + NS * 8 + n * 16, 1);
                }
                if (p == 0) mbar_init(sbp + SM_REF, 1);
                asm volatile("fence.mbarrier_init.release.cluster;" ::: "memory");
            }
            __syncwarp();
            bar_arrive(B_QK, NTHREADS);
            if (elect()) {
                int tl = 2 * b + p + 2 * NI * G;
                int s = p + 2 * NI; uint32_t ph = 1;
                int sa = p, na = 0; uint32_t pa = 0;
                bool late = false;
                for (int n = NI;; n++) {
                    const int d = n < NRAMP ? D0 : (tl >= NT - (TA) ? 1 : tl >= NT - (TB) ? 2 : (D1));
                    while (n - na >= d) {
                        mbar_wait(sbp + SM_BAR + sa * 8, pa);
                        if (na < NS / 2) TR(1, 2 * na + p);
                        na++; sa += 2;
                        if (sa >= NS) { sa -= NS; pa ^= 1; }
                    }
                    mbar_wait(sbp + SM_BAR + (NS + s) * 8, ph);
                    if (n < NPACE) while (clock32() - c0 < (n ? T1 + (2 * (n - 1) + p) * TG : T0)) {}
                    issue_tile(&m0, &m1, sbp, s, tl, pol);
                    TR(0, 2 * n + p);
                    int nxt = tl + 2 * G;
                    if (n >= NST - 1) nxt = grab_tile(g_ctr) + 2 * NST * G;
                    const bool last = nxt >= NT;
                    uint32_t flag = last;
                    if (!late && nxt >= NT - MAXT - 16 * b) { late = true; flag |= 2; }
                    if (last) mbar_wait(sbp + SM_REF, 0);
                    sts32(sbp + SM_FLAG + s * 4, flag);
                    mbar_arrive(sbp + SM_BAR + s * 8);
                    if (last) break;
                    s += 2;
                    if (s >= NS) { s -= NS; ph ^= 1; }
                    tl = nxt;
                }
                if (p) TSE(5);
            }
            return;
        }
        const int h = threadIdx.x - 320;
        uint4 v[6];
        for (int it = 0;; it++) {
            bool miss = false;
#pragma unroll
            for (int k = 0; k < 6; k++) v[k] = ldg_relaxed(g_qk + k * 64 + h);
#pragma unroll
            for (int k = 0; k < 6; k++) miss |= has(v[k], 0);
            if (!miss) break;
            if (it > SPIN_LIMIT) __trap();
            if (it == 0) __nanosleep(QSLEEP);
        }
#pragma unroll
        for (int k = 0; k < 6; k++) sts128(sb + SM_QK + (k * 64 + h) * 16, ~v[k].x, ~v[k].y, ~v[k].z, ~v[k].w);
        __syncwarp();
        bar_sync(B_QK, NTHREADS);
        if (warp == 11) return;
        uint32_t r = 1;
        for (int it = 0;; it++) {
            __nanosleep(500);
            if (lane < NQ) asm volatile("ld.acquire.gpu.global.u32 %0, [%1];" : "=r"(r) : "l"(g_mref + lane) : "memory");
            if (__all_sync(~0u, r != 0)) break;
            if (it > SPIN_LIMIT) __trap();
        }
        if (lane < NQ) sts32(sb + SM_M + lane * 4, ~r);
        __syncwarp();
        if (lane == 0) { mbar_arrive(sb + SM_REF); TSE(7); }
        return;
    }

    const int grp = warp >> 2, cw = warp & 3;
    const int xp = lane & 7, mi = lane >> 3;
    const uint32_t offS1 = opaque(12288 + xp * 128 + ((mi ^ xp) << 4)), offS1x = opaque(offS1 ^ 64);
    const uint32_t offS0 = opaque(offS1 - 12288 + cw * 3072), offS0x = opaque(offS0 ^ 64);
    const uint32_t offT = opaque(mi * 3072 + xp * 128 + (((cw + 4 * grp) ^ xp) << 4)), offTx = opaque(offT ^ 64);
    const uint32_t offU = opaque(12288 + (mi % 3) * 1024 + xp * 128 + (((cw + 4 * (grp ^ (mi / 3))) ^ xp) << 4));
    const uint32_t offV = opaque(12288 + (1 + (mi & 1)) * 1024 + xp * 128 + (((cw + 4 * (grp ^ 1)) ^ xp) << 4));
    const int shl = opaque(9 * t), shl4 = opaque(9 * t + 4);
    const uint32_t pw = opaque((cw >> 1) * 512 + lane * 16 + (cw & 1) * 8), muw = opaque(1024 + t * 16 + cw * 4);
    const uint32_t prd = opaque(lane * 16), mur = opaque(1024 + t * 16), mof = g * 4;
    uint32_t pb0 = sb + SM_P + grp * 2 * PBUF;
    const uint32_t pbx = pb0 ^ (pb0 + PBUF);
    const bool odd = g & 1;
    const int barid = B_GRP + grp;
    const bool elected = cw == 3 && lane == 0;

    uint32_t qa[48];
    float r_lo, r_hi;
    bar_sync(B_QK, NTHREADS);
    {
        float rr[2][4] = {{0.f, 0.f, 0.f, 0.f}, {0.f, 0.f, 0.f, 0.f}};
#pragma unroll
        for (int kk = 0; kk < 12; kk++) {
            const uint4 v = lds128(sb + SM_QK + kk * 512 + lane * 16);
            qa[4 * kk] = v.x; qa[4 * kk + 1] = v.y; qa[4 * kk + 2] = v.z; qa[4 * kk + 3] = v.w;
            mma(rr[kk & 1], v.x, v.y, v.z, v.w, ONES, ONES);
        }
        r_lo = rr[0][0] + rr[1][0]; r_hi = rr[0][2] + rr[1][2];
    }
    if (threadIdx.x == 0) TS(1);

    float acc[6][4];
#pragma unroll
    for (int i = 0; i < 6; i++) acc[i][0] = acc[i][1] = acc[i][2] = acc[i][3] = 0.f;
    float m_lo = -INFINITY, m_hi = -INFINITY, l_lo = 0.f, l_hi = 0.f;
    float cm[4] = {0.f, 0.f, 0.f, 0.f};
    uint32_t xt[6][4], yt[6]; uint4 pa, pb, mv;
    const uint32_t dof = opaque(acc_line(warp) + (lane & 7) * 16);
    const uint32_t xof = 512 - lane * 8;
    int s = grp; uint32_t ph = 0;
    while (true) {
        mbar_wait(sb + SM_BAR + s * 8, ph);
        PH(0, 0);
        const uint32_t stop = lds32(sb + SM_FLAG + s * 4);
        const uint32_t st = sb + SM_STAGES + s * STAGE;
        float sc[2][4], gr[4][4], sx[4];
#pragma unroll
        for (int e = 0; e < 4; e++) sc[0][e] = sc[1][e] = gr[0][e] = gr[1][e] = gr[2][e] = gr[3][e] = sx[e] = 0.f;
#pragma unroll
        for (int qq = 0; qq < 6; qq++) {
            uint32_t x[4], y[4];
            ldsm4(x, st + (qq & 1 ? offS0x : offS0) + (qq >> 1) * 1024);
            ldsm4(y, st + (qq & 1 ? offS1x : offS1) + (qq >> 1) * 1024);
#pragma unroll
            for (int e = 0; e < 4; e++) x[e] = hadd2(x[e], y[e]);
            mma8(gr[0], x[0], x[1], x[0]);
            mma8(gr[1], x[0], x[1], x[1]);
            mma(sx, x[0], x[1], x[2], x[3], ONES, ONES);
            mma8(gr[GR4 ? 2 : 0], x[2], x[3], x[2]);
            mma8(gr[GR4 ? 3 : 1], x[2], x[3], x[3]);
            mma(sc[0], qa[8 * qq], qa[8 * qq + 1], qa[8 * qq + 2], qa[8 * qq + 3], x[0], x[1]);
            mma(sc[1], qa[8 * qq + 4], qa[8 * qq + 5], qa[8 * qq + 6], qa[8 * qq + 7], x[2], x[3]);
        }
        ldsm4t(yt, st + offU);
        ldsm2t(yt + 4, st + offV);
#pragma unroll
        for (int i = 0; i < 6; i++) ldsm4t(xt[i], st + (i < 3 ? offT : offTx) + (i % 3) * 1024);

        const float mu = (sx[0] + sx[2]) * (1.f / C), ss = GR4 ? (odd ? (gr[0][1] + gr[1][3]) + (gr[2][1] + gr[3][3]) : (gr[0][0] + gr[1][2]) + (gr[2][0] + gr[3][2])) : (odd ? gr[0][1] + gr[1][3] : gr[0][0] + gr[1][2]);
        const float rs = rsq(fmaxf(fmaf(-mu, mu, fmaf(ss, 1.f / C, 1e-5f)), 1e-5f));
        const float mu0 = __shfl_sync(~0u, mu, shl), mu1 = __shfl_sync(~0u, mu, shl4);
        const float rs0 = __shfl_sync(~0u, rs, shl), rs1 = __shfl_sync(~0u, rs, shl4);
        const float u0 = fmaf(-mu0, r_lo, sc[0][0] + sc[1][0]), u1 = fmaf(-mu1, r_lo, sc[0][1] + sc[1][1]);
        const float u2 = fmaf(-mu0, r_hi, sc[0][2] + sc[1][2]), u3 = fmaf(-mu1, r_hi, sc[0][3] + sc[1][3]);
        const float d0 = fmaf(u0, rs0, -m_lo), d1 = fmaf(u1, rs1, -m_lo), d2 = fmaf(u2, rs0, -m_hi), d3 = fmaf(u3, rs1, -m_hi);
        PH(1, u(d0 + d2));
        float p0 = ex2(d0), p1 = ex2(d1), p2 = ex2(d2), p3 = ex2(d3);
        sts64(pb0 + pw, pack2(p0 * rs0, p1 * rs1), pack2(p2 * rs0, p3 * rs1));
        if (lane < 4) sts32(pb0 + muw, pack2(mu0, mu1));
        const bool over = bar_any(barid, 128, fmaxf(fmaxf(d0, d1), fmaxf(d2, d3)) > LAZY);
        PH(3, 0);
        pa = lds128(pb0 + prd); pb = lds128(pb0 + prd + 512); mv = lds128(pb0 + mur);
        if (elected) mbar_arrive(sb + SM_BAR + (NS + s) * 8);
        if (__builtin_expect(over, 0)) {
            const float s0 = u0 * rs0, s1 = u1 * rs1, s2 = u2 * rs0, s3 = u3 * rs1;
            float xl = fmaxf(s0, s1), xh = fmaxf(s2, s3);
            xl = fmaxf(xl, __shfl_xor_sync(~0u, xl, 1)); xh = fmaxf(xh, __shfl_xor_sync(~0u, xh, 1));
            xl = fmaxf(xl, __shfl_xor_sync(~0u, xl, 2)); xh = fmaxf(xh, __shfl_xor_sync(~0u, xh, 2));
            if (t < 2) sts32(sb + SM_MX + grp * 256 + ((g + 8 * t) * 4 + cw) * 4, u(t ? xh : xl));
            bar_sync(B_MAX + grp, 128);
            const uint4 ml4 = lds128(sb + SM_MX + grp * 256 + g * 16), mh4 = lds128(sb + SM_MX + grp * 256 + g * 16 + 128);
            const float nl = fmaxf(fmaxf(fmaxf(f(ml4.x), f(ml4.y)), fmaxf(f(ml4.z), f(ml4.w))), m_lo);
            const float nh = fmaxf(fmaxf(fmaxf(f(mh4.x), f(mh4.y)), fmaxf(f(mh4.z), f(mh4.w))), m_hi);
            p0 = ex2(s0 - nl); p1 = ex2(s1 - nl); p2 = ex2(s2 - nh); p3 = ex2(s3 - nh);
            sts64(pb0 + pw, pack2(p0 * rs0, p1 * rs1), pack2(p2 * rs0, p3 * rs1));
            const float al = ex2(m_lo - nl), ah = ex2(m_hi - nh);
            m_lo = nl; m_hi = nh;
            l_lo *= al; l_hi *= ah; cm[0] *= al; cm[2] *= ah;
#pragma unroll
            for (int i = 0; i < 6; i++) { acc[i][0] *= al; acc[i][1] *= al; acc[i][2] *= ah; acc[i][3] *= ah; }
            bar_sync(B_MAX + grp, 128);
            pa = lds128(pb0 + prd); pb = lds128(pb0 + prd + 512);
        }
        l_lo += p0 + p1; l_hi += p2 + p3;
        if (stop & 1) break;
#pragma unroll
        for (int i = 0; i < 6; i++) mma(acc[i], pa.x, pa.y, pa.z, pa.w, hadd2v(xt[i][0], yt[i]), hadd2v(xt[i][1], yt[i]));
        mma(cm, pa.x, pa.y, pa.z, pa.w, mv.x, mv.y);
#pragma unroll
        for (int i = 0; i < 6; i++) mma(acc[i], pb.x, pb.y, pb.z, pb.w, hadd2v(xt[i][2], yt[i]), hadd2v(xt[i][3], yt[i]));
        mma(cm, pb.x, pb.y, pb.z, pb.w, mv.z, mv.w);
        PH(4, u(acc[5][0]));
        if (stop) {
            float a = l_lo + __shfl_xor_sync(~0u, l_lo, 1), c = l_hi + __shfl_xor_sync(~0u, l_hi, 1);
            a += __shfl_xor_sync(~0u, a, 2); c += __shfl_xor_sync(~0u, c, 2);
            const uint32_t m = u((t ? m_hi : m_lo) + lg2(fmaxf(t ? c : a, 1.f)));
            if (t < 2) asm volatile("red.relaxed.gpu.global.max.u32 [%0], %1;" ::"l"(g_mmax + g + 8 * t), "r"(m >> 31 ? ~m : m | 0x80000000u) : "memory");
        }
        pb0 ^= pbx;
        s += 2;
        if (s >= NS) { s -= NS; ph ^= 1; }
    }
    const uint32_t ref_lo = lds32(sb + SM_M + mof), ref_hi = lds32(sb + SM_M + 32 + mof);
    const float al = ex2(m_lo - f(ref_lo)), ah = ex2(m_hi - f(ref_hi));
    mma(cm, pa.x, pa.y, pa.z, pa.w, mv.x, mv.y);
#pragma unroll
    for (int i = 3; i < 6; i++) mma(acc[i], pa.x, pa.y, pa.z, pa.w, hadd2v(xt[i][0], yt[i]), hadd2v(xt[i][1], yt[i]));
    mma(cm, pb.x, pb.y, pb.z, pb.w, mv.z, mv.w);
#pragma unroll
    for (int i = 3; i < 6; i++) mma(acc[i], pb.x, pb.y, pb.z, pb.w, hadd2v(xt[i][2], yt[i]), hadd2v(xt[i][3], yt[i]));
#pragma unroll
    for (int i = 0; i < 3; i++) mma(acc[i], pa.x, pa.y, pa.z, pa.w, hadd2v(xt[i][0], yt[i]), hadd2v(xt[i][1], yt[i]));
#pragma unroll
    for (int i = 0; i < 3; i++) mma(acc[i], pb.x, pb.y, pb.z, pb.w, hadd2v(xt[i][2], yt[i]), hadd2v(xt[i][3], yt[i]));
    if (threadIdx.x == grp * 128) TSE(2 + grp);
    if (threadIdx.x == grp * 128 + 96) TSX(2 + grp, u(acc[5][0]));

    uint4* const dst = reinterpret_cast<uint4*>(reinterpret_cast<char*>(g_acc) + (dof ^ (ref_lo & PLACE)));
    uint4* const dsu = reinterpret_cast<uint4*>(reinterpret_cast<char*>(g_acc) + (dof ^ (ref_hi & PLACE)));
#define MERGE() bar_sync(B_MERGE, 256)
    const uint32_t xw = sb + SM_STAGES + grp * STAGE + cw * 768 + prd, xr = sb + SM_STAGES + (grp ^ 1) * STAGE + cw * 768 + prd;
    const float cl = -cm[0] * al, ch = -cm[2] * ah;
    uint32_t hl[6], hh[6];
#pragma unroll
    for (int i = 3; i < 6; i++) { hl[i] = packh(fmaf(acc[i][0], al, cl), fmaf(acc[i][1], al, cl)); hh[i] = packh(fmaf(acc[i][2], ah, ch), fmaf(acc[i][3], ah, ch)); }
    sts128(xw, hl[3], hl[4], hl[5], hh[3]);
    sts64(xw + xof, hh[4], hh[5]);
#pragma unroll
    for (int i = 0; i < 3; i++) { hl[i] = packh(fmaf(acc[i][0], al, cl), fmaf(acc[i][1], al, cl)); hh[i] = packh(fmaf(acc[i][2], ah, ch), fmaf(acc[i][3], ah, ch)); }
    const uint32_t w_lo = packh(l_lo * al, 1.f), w_hi = packh(l_hi * ah, 1.f);
    MERGE();
    if (threadIdx.x == 224) TSX(4, 0);
    const uint4 o = lds128(xr);
    const uint2 o2 = lds64(xr + xof);
    red8h(dst, haddh(hl[0], o.x), haddh(hl[1], o.y), haddh(hl[2], o.z), w_lo);
    red8h(dsu, haddh(hh[0], o.w), haddh(hh[1], o2.x), haddh(hh[2], o2.y), w_hi);
    if (threadIdx.x == 0) TSE(4);
    if (threadIdx.x == 224) TSX(9, 0);
}

typedef CUresult (*EncodeFn)(CUtensorMap*, CUtensorMapDataType, cuuint32_t, void*, const cuuint64_t*, const cuuint64_t*,
                             const cuuint32_t*, const cuuint32_t*, CUtensorMapInterleave, CUtensorMapSwizzle,
                             CUtensorMapL2promotion, CUtensorMapFloatOOBfill);

}

extern "C" void kernel_launch(void* const* d_in, const int* in_sizes, int n_in, void* d_out, int out_size) {
    const __nv_bfloat16* q = (const __nv_bfloat16*)d_in[0];
    char* f0 = (char*)d_in[1];
    char* f1 = (char*)d_in[2];
    const __nv_bfloat16* wq = (const __nv_bfloat16*)d_in[3];
    const __nv_bfloat16* wk = (const __nv_bfloat16*)d_in[4];
    const __nv_bfloat16* wv = (const __nv_bfloat16*)d_in[5];
    const __nv_bfloat16* wo = (const __nv_bfloat16*)d_in[6];

    static EncodeFn enc = nullptr;
    static int grid = 0;
    static Scratch* scr = nullptr;
    if (!enc) {
        void* fn = nullptr; cudaDriverEntryPointQueryResult qr;
        cudaGetDriverEntryPoint("cuTensorMapEncodeTiled", &fn, cudaEnableDefault, &qr);
        enc = (EncodeFn)fn;
        cudaGetSymbolAddress((void**)&scr, g_scratch);
        int dev = 0, sms = 0;
        cudaGetDevice(&dev);
        cudaDeviceGetAttribute(&sms, cudaDevAttrMultiProcessorCount, dev);
        grid = sms < MAXG ? sms : MAXG;
        cudaFuncSetAttribute(attn_main, cudaFuncAttributeMaxDynamicSharedMemorySize, SMEM_BYTES);
    }
    CUtensorMap m0, m1;
    {
        cuuint64_t dims[5] = {64, W1, 3, 2, W0};
        cuuint64_t str[4] = {2 * C * 2, 128, C * 2, (cuuint64_t)W0 * C * 2};
        cuuint32_t box[5] = {64, TP, 3, 2, 2}, es[5] = {1, 1, 1, 1, 1};
        enc(&m0, CU_TENSOR_MAP_DATA_TYPE_BFLOAT16, 5, f0, dims, str, box, es, CU_TENSOR_MAP_INTERLEAVE_NONE,
            CU_TENSOR_MAP_SWIZZLE_128B, CU_TENSOR_MAP_L2_PROMOTION_NONE, CU_TENSOR_MAP_FLOAT_OOB_FILL_NONE);
    }
    {
        cuuint64_t dims[4] = {64, W1, 3, W1};
        cuuint64_t str[3] = {C * 2, 128, (cuuint64_t)W1 * C * 2};
        cuuint32_t box[4] = {64, TP, 3, 1}, es[4] = {1, 1, 1, 1};
        enc(&m1, CU_TENSOR_MAP_DATA_TYPE_BFLOAT16, 4, f1, dims, str, box, es, CU_TENSOR_MAP_INTERLEAVE_NONE,
            CU_TENSOR_MAP_SWIZZLE_128B, CU_TENSOR_MAP_L2_PROMOTION_NONE, CU_TENSOR_MAP_FLOAT_OOB_FILL_NONE);
    }
    attn_main<<<grid, NTHREADS, SMEM_BYTES, cudaStreamPerThread>>>(f0, f1, q, wq, wk, scr, wv, wo, (__nv_bfloat16*)d_out, m0, m1);
}
```

```cpp
#include <cuda_runtime.h>
#include <cuda_bf16.h>
#include <cuda.h>
#include <stdint.h>

namespace {

constexpr int C = 192;
constexpr int NQ = 16;
constexpr int W0 = 512;
constexpr int W1 = 256;
constexpr int TP = 8;
constexpr int NT = W1 * W1 / TP;
constexpr int STAGE = TP * 5 * C * 2;
#define NS 14
#define D0 3
#define D1 2
#define NRAMP 5
#define TA (p ? 470 : 185)
#define QSLEEP 700
#define WSL 24
#define MAXT 3000
#define REFT 1800
#define POLLN 1
#define PGAP 64
#define NPW 5
#define NPROBE 8
#define LAZY 12.f
#define GR4 1
#define NST 4
#define NI 1
#define NPACE 5
#define T0 0
#define T1 1600
#define TG 960
static_assert(NST > D0, "the first dynamic tile index must not delay the start");
constexpr int NTHREADS = 384;
constexpr int MAXG = 132;
constexpr int NRD = NQ;
constexpr int NSRC = 12;
constexpr int SPIN_LIMIT = 1 << 22;

constexpr int SM_STAGES = 0;
constexpr int SM_P = NS * STAGE;
constexpr int PBUF = 1088;
constexpr int SM_QK = SM_P + 4 * PBUF;
constexpr int SM_MX = SM_QK + 6144;
constexpr int SM_M = SM_MX + 512;
constexpr int SM_BAR = SM_M + 64;
constexpr int SM_REF = SM_BAR + 16 * NS;
constexpr int SM_FLAG = SM_REF + 8;
constexpr int SM_TOTAL = SM_FLAG + 4 * NS;
constexpr int SMEM_BYTES = SM_TOTAL + 1024;
static_assert(SMEM_BYTES <= 232448, "smem");
constexpr int WROW = 400;
constexpr int RD_W = 0;
constexpr int RD_QN = 2 * C * WROW;
constexpr int RD_KQ = RD_QN + 6144;
constexpr int RD_B = RD_KQ + 7168;
constexpr int RD_B2 = 17 * 80;
constexpr int RD_PLACE = RD_B + 2 * RD_B2;
constexpr int RD_BAR = RD_PLACE + 16;
constexpr int RD_A = RD_BAR + 64;
constexpr int RD_WS = RD_A + 12 * 6 * 512;
static_assert(RD_WS + 12 * 128 <= SM_TOTAL, "smem");

struct Scratch {
    uint4 acc[2048];
    uint4 qk[NSRC * 32];
    unsigned ctr[32];
    unsigned mmax[32];
    unsigned mref[32];
};
__device__ __align__(8192) Scratch g_scratch;
#define g_acc (scr->acc)
#define g_qk (scr->qk)
#define g_ctr (scr->ctr)
#define g_mmax (scr->mmax)
#define g_mref (scr->mref)
#define g_ts (scr->ts)
#define g_tr (scr->tr)
#define TR(k, i) do {} while (0)
#define TS(i) do {} while (0)
#define TSD(i, dep) do {} while (0)
#define TSX(i, dep) do {} while (0)
#define TSP(i, dep) do {} while (0)
#define TSE(i) TS(i)
#define CK_(i, dep) do {} while (0)
#define PH(i, dep) do {} while (0)

__device__ __forceinline__ uint32_t s2u(const void* p) { return (uint32_t)__cvta_generic_to_shared(p); }
__device__ __forceinline__ void mbar_init(uint32_t a, int c) { asm volatile("mbarrier.init.shared::cta.b64 [%0], %1;" ::"r"(a), "r"(c) : "memory"); }
__device__ __forceinline__ void mbar_expect(uint32_t a, uint32_t b) { asm volatile("mbarrier.arrive.expect_tx.shared::cta.b64 _, [%0], %1;" ::"r"(a), "r"(b) : "memory"); }
__device__ __forceinline__ void mbar_arrive(uint32_t a) { asm volatile("mbarrier.arrive.shared::cta.b64 _, [%0];" ::"r"(a) : "memory"); }
__device__ __forceinline__ void mbar_wait(uint32_t a, uint32_t ph) {
    uint32_t ok; int it = 0;
    do {
        asm volatile("{.reg .pred p; mbarrier.try_wait.parity.shared::cta.b64 p, [%1], %2; selp.u32 %0,1,0,p;}" : "=r"(ok) : "r"(a), "r"(ph) : "memory");
        if (++it > SPIN_LIMIT) __trap();
    } while (!ok);
}
__device__ __forceinline__ bool elect() {
    uint32_t r; asm volatile("{.reg .pred p; elect.sync _|p, 0xffffffff; selp.u32 %0, 1, 0, p;}" : "=r"(r)); return r;
}
__device__ __forceinline__ void bar_sync(int id, int n) { asm volatile("bar.sync %0, %1;" ::"r"(id), "r"(n) : "memory"); }
__device__ __forceinline__ bool bar_any(int id, int n, bool c) {
    uint32_t r;
    asm volatile("{.reg .pred p, q; setp.ne.u32 q, %3, 0; bar.red.or.pred p, %1, %2, q; selp.u32 %0, 1, 0, p;}" : "=r"(r) : "r"(id), "r"(n), "r"((uint32_t)c) : "memory");
    return r;
}
__device__ __forceinline__ void bar_arrive(int id, int n) { asm volatile("bar.arrive %0, %1;" ::"r"(id), "r"(n) : "memory"); }
__device__ __forceinline__ void ldsm4(uint32_t* r, uint32_t a) {
    asm volatile("ldmatrix.sync.aligned.m8n8.x4.shared.b16 {%0,%1,%2,%3}, [%4];" : "=r"(r[0]), "=r"(r[1]), "=r"(r[2]), "=r"(r[3]) : "r"(a) : "memory");
}
__device__ __forceinline__ void ldsm4t(uint32_t* r, uint32_t a) {
    asm volatile("ldmatrix.sync.aligned.m8n8.x4.trans.shared.b16 {%0,%1,%2,%3}, [%4];" : "=r"(r[0]), "=r"(r[1]), "=r"(r[2]), "=r"(r[3]) : "r"(a) : "memory");
}
__device__ __forceinline__ void ldsm2t(uint32_t* r, uint32_t a) {
    asm volatile("ldmatrix.sync.aligned.m8n8.x2.trans.shared.b16 {%0,%1}, [%2];" : "=r"(r[0]), "=r"(r[1]) : "r"(a) : "memory");
}
__device__ __forceinline__ void mma(float* d, uint32_t a0, uint32_t a1, uint32_t a2, uint32_t a3, uint32_t b0, uint32_t b1) {
    asm("mma.sync.aligned.m16n8k16.row.col.f32.bf16.bf16.f32 {%0,%1,%2,%3}, {%4,%5,%6,%7}, {%8,%9}, {%0,%1,%2,%3};"
        : "+f"(d[0]), "+f"(d[1]), "+f"(d[2]), "+f"(d[3]) : "r"(a0), "r"(a1), "r"(a2), "r"(a3), "r"(b0), "r"(b1));
}
__device__ __forceinline__ void mmah(float* d, uint32_t a0, uint32_t a1, uint32_t a2, uint32_t a3, uint32_t b0, uint32_t b1) {
    asm("mma.sync.aligned.m16n8k16.row.col.f32.f16.f16.f32 {%0,%1,%2,%3}, {%4,%5,%6,%7}, {%8,%9}, {%0,%1,%2,%3};"
        : "+f"(d[0]), "+f"(d[1]), "+f"(d[2]), "+f"(d[3]) : "r"(a0), "r"(a1), "r"(a2), "r"(a3), "r"(b0), "r"(b1));
}
__device__ __forceinline__ void mma8(float* d, uint32_t a0, uint32_t a1, uint32_t b0) {
    asm("mma.sync.aligned.m16n8k8.row.col.f32.bf16.bf16.f32 {%0,%1,%2,%3}, {%4,%5}, {%6}, {%0,%1,%2,%3};"
        : "+f"(d[0]), "+f"(d[1]), "+f"(d[2]), "+f"(d[3]) : "r"(a0), "r"(a1), "r"(b0));
}
__device__ __forceinline__ uint32_t hadd2(uint32_t a, uint32_t b) {
    uint32_t r; asm("add.rn.bf16x2 %0, %1, %2;" : "=r"(r) : "r"(a), "r"(b)); return r;
}
__device__ __forceinline__ uint32_t pack2(float lo, float hi) {
    uint32_t r; asm("cvt.rn.bf16x2.f32 %0, %1, %2;" : "=r"(r) : "f"(hi), "f"(lo)); return r;
}
__device__ __forceinline__ uint32_t packh(float lo, float hi) {
    uint32_t r; asm("cvt.rn.f16x2.f32 %0, %1, %2;" : "=r"(r) : "f"(hi), "f"(lo)); return r;
}
__device__ __forceinline__ float2 unpackh(uint32_t v) {
    float2 r; asm("{.reg .b16 l, h; mov.b32 {l, h}, %2; cvt.f32.f16 %0, l; cvt.f32.f16 %1, h;}" : "=f"(r.x), "=f"(r.y) : "r"(v)); return r;
}
__device__ __forceinline__ float bflo(uint32_t v) { return __uint_as_float(v << 16); }
__device__ __forceinline__ float bfhi(uint32_t v) { return __uint_as_float(v & 0xffff0000u); }
__device__ __forceinline__ float ex2(float x) { float r; asm("ex2.approx.ftz.f32 %0, %1;" : "=f"(r) : "f"(x)); return r; }
__device__ __forceinline__ void sts128(uint32_t a, uint32_t x, uint32_t y, uint32_t z, uint32_t w) {
    asm volatile("st.shared.v4.b32 [%0], {%1,%2,%3,%4};" ::"r"(a), "r"(x), "r"(y), "r"(z), "r"(w) : "memory");
}
__device__ __forceinline__ void sts64(uint32_t a, uint32_t x, uint32_t y) {
    asm volatile("st.shared.v2.b32 [%0], {%1,%2};" ::"r"(a), "r"(x), "r"(y) : "memory");
}
__device__ __forceinline__ void sts32(uint32_t a, uint32_t x) { asm volatile("st.shared.b32 [%0], %1;" ::"r"(a), "r"(x) : "memory"); }
__device__ __forceinline__ uint4 lds128(uint32_t a) {
    uint4 v; asm volatile("ld.shared.v4.b32 {%0,%1,%2,%3}, [%4];" : "=r"(v.x), "=r"(v.y), "=r"(v.z), "=r"(v.w) : "r"(a) : "memory"); return v;
}
__device__ __forceinline__ uint2 lds64(uint32_t a) {
    uint2 v; asm volatile("ld.shared.v2.b32 {%0,%1}, [%2];" : "=r"(v.x), "=r"(v.y) : "r"(a) : "memory"); return v;
}
__device__ __forceinline__ uint32_t haddh(uint32_t a, uint32_t b) {
    uint32_t r; asm("add.rn.f16x2 %0, %1, %2;" : "=r"(r) : "r"(a), "r"(b)); return r;
}
__device__ __forceinline__ uint32_t lds32(uint32_t a) { uint32_t v; asm volatile("ld.shared.b32 %0, [%1];" : "=r"(v) : "r"(a) : "memory"); return v; }
__device__ __forceinline__ int grab_tile(unsigned* ctr) {
    int v; asm volatile("atom.relaxed.gpu.global.inc.u32 %0, [%1], 0x7fffffff;" : "=r"(v) : "l"(ctr) : "memory"); return v;
}
__device__ __forceinline__ uint32_t opaque(uint32_t v) { uint32_t r; asm volatile("mov.b32 %0, %1;" : "=r"(r) : "r"(v)); return r; }
__device__ __forceinline__ unsigned clock32() { unsigned c; asm volatile("mov.u32 %0, %%clock;" : "=r"(c)); return c; }
__device__ __forceinline__ float rsq(float x) { float r; asm("rsqrt.approx.ftz.f32 %0, %1;" : "=f"(r) : "f"(x)); return r; }
__device__ __forceinline__ float rcp(float x) { float r; asm("rcp.approx.ftz.f32 %0, %1;" : "=f"(r) : "f"(x)); return r; }
__device__ __forceinline__ float lg2(float x) { float r; asm("lg2.approx.ftz.f32 %0, %1;" : "=f"(r) : "f"(x)); return r; }
__device__ __forceinline__ float f(uint32_t v) { return __uint_as_float(v); }
__device__ __forceinline__ uint32_t u(float v) { return __float_as_uint(v); }

constexpr uint32_t ONES = 0x3F803F80u;
constexpr float QSCALE = 0.07216878364870322f * 1.4426950408889634f;

__device__ __forceinline__ void issue_tile(const CUtensorMap* m0, const CUtensorMap* m1, uint32_t sb, int s, int tl, uint64_t pol) {
    const uint32_t full = sb + SM_BAR + s * 8, dst = sb + SM_STAGES + s * STAGE;
    const int par = tl * TP, y = par >> 8, x = par & 255;
    mbar_expect(full, STAGE);
    asm volatile("cp.async.bulk.tensor.5d.shared::cluster.global.mbarrier::complete_tx::bytes.L2::cache_hint [%0], [%1, {%3,%4,%3,%3,%5}], [%2], %6;"
                 ::"r"(dst), "l"(m0), "r"(full), "r"(0), "r"(x), "r"(2 * y), "l"(pol) : "memory");
    asm volatile("cp.async.bulk.tensor.4d.shared::cluster.global.mbarrier::complete_tx::bytes.L2::cache_hint [%0], [%1, {%3,%4,%3,%5}], [%2], %6;"
                 ::"r"(dst + TP * 4 * C * 2), "l"(m1), "r"(full), "r"(0), "r"(x), "r"(y), "l"(pol) : "memory");
}

__device__ __forceinline__ void prefetch_l2(const void* a, int n) { asm volatile("cp.async.bulk.prefetch.L2.global [%0], %1;" ::"l"(a), "r"(n) : "memory"); }
__device__ __forceinline__ uint4 ldg_relaxed(const uint4* p) {
    uint4 v; asm volatile("ld.relaxed.gpu.global.v4.u32 {%0,%1,%2,%3}, [%4];" : "=r"(v.x), "=r"(v.y), "=r"(v.z), "=r"(v.w) : "l"(p) : "memory"); return v;
}
__device__ __forceinline__ uint32_t ldg_relaxed32(const void* p) {
    uint32_t v; asm volatile("ld.relaxed.gpu.global.u32 %0, [%1];" : "=r"(v) : "l"(p) : "memory"); return v;
}
__device__ __forceinline__ void stg_relaxed(uint4* p, uint32_t x, uint32_t y, uint32_t z, uint32_t w) {
    asm volatile("st.relaxed.gpu.global.v4.u32 [%0], {%1,%2,%3,%4};" ::"l"(p), "r"(x), "r"(y), "r"(z), "r"(w) : "memory");
}
__device__ __forceinline__ void stg_relaxed32(void* p, uint32_t x) { asm volatile("st.relaxed.gpu.global.u32 [%0], %1;" ::"l"(p), "r"(x) : "memory"); }
__device__ __forceinline__ bool has(const uint4& v, uint32_t m) { return v.x == m || v.y == m || v.z == m || v.w == m; }
__device__ __forceinline__ uint32_t hadd2v(uint32_t a, uint32_t b) {
    uint32_t r; asm volatile("add.rn.bf16x2 %0, %1, %2;" : "=r"(r) : "r"(a), "r"(b)); return r;
}

__device__ __forceinline__ void red8h(uint4* p, uint32_t x, uint32_t y, uint32_t z, uint32_t w) {
    asm volatile("red.relaxed.gpu.global.add.noftz.v4.f16x2 [%0], {%1,%2,%3,%4};" ::"l"(p), "r"(x), "r"(y), "r"(z), "r"(w) : "memory");
}
__device__ __forceinline__ uint4 lds128v(uint32_t a) {
    uint4 v; asm volatile("ld.volatile.shared.v4.b32 {%0,%1,%2,%3}, [%4];" : "=r"(v.x), "=r"(v.y), "=r"(v.z), "=r"(v.w) : "r"(a) : "memory"); return v;
}
__device__ __forceinline__ uint32_t brow(int r) { return RD_B + r * 80 + (r >> 3) * 64; }

constexpr uint32_t PLACE = 0x1980;
__device__ __forceinline__ uint32_t acc_line(int k) { return (k >> 2) * 16384 + (k & 2) * 6144 + (k & 1) * 1024; }
__device__ __forceinline__ uint32_t acc_place(int side, int s) { return side * 4096 + (s & 1) * 256 + (s & 2) * 1024 + (s & 4) * 32; }

enum { B_QK = 1, B_QN = 2, B_GRP = 3  , B_Q = 5, B_MERGE = 6, B_ALL = 7, B_MAX = 8  , B_WARP = 10, B_SLOW = 12, B_PARK = 13, B_PLACE = 14, B_RDY = 15 };

__device__ __noinline__ void slow_rows(const char* __restrict__ f0, const char* __restrict__ f1, const __nv_bfloat16* __restrict__ q,
                                       const __nv_bfloat16* __restrict__ wq, const __nv_bfloat16* __restrict__ wk, const uint32_t sb)
{
    const int warp = threadIdx.x >> 5, lane = threadIdx.x & 31;
    float* const sm = reinterpret_cast<float*>(__cvta_shared_to_generic(sb + RD_W));
    for (int i = threadIdx.x; i < 2 * C; i += 128) sm[i] = __bfloat162float(q[(blockIdx.x & 14) * C + i]);
    bar_sync(B_SLOW, 128);
#pragma unroll 1
    for (int j = threadIdx.x; j < 2 * C; j += 128) {
        const float* const x = sm + j / C * C;
        float mu = 0.f, var = 0.f, s = 0.f;
#pragma unroll 1
        for (int i = 0; i < C; i++) mu += x[i];
        mu *= 1.f / C;
#pragma unroll 4
        for (int i = 0; i < C; i++) { var = fmaf(x[i] - mu, x[i] - mu, var); s = fmaf(x[i] - mu, __bfloat162float(wq[i * C + j % C]), s); }
        sm[4 * C + j] = s * rsq(var * (1.f / C) + 1e-5f);
    }
    bar_sync(B_SLOW, 128);
#pragma unroll 1
    for (int j = threadIdx.x; j < 2 * C; j += 128) {
        float s = 0.f;
#pragma unroll 4
        for (int i = 0; i < C; i++) s = fmaf(sm[4 * C + j / C * C + i], __bfloat162float(wk[j % C * C + i]), s);
        sm[j] = s * QSCALE;
    }
    bar_sync(B_SLOW, 128);
    float k[2][6], a[2][6], m[2], l[2];
#pragma unroll
    for (int r = 0; r < 2; r++) {
        m[r] = -INFINITY; l[r] = 0.f;
#pragma unroll
        for (int i = 0; i < 6; i++) { k[r][i] = sm[r * C + 64 * (i >> 1) + 2 * lane + (i & 1)]; a[r][i] = 0.f; }
    }
#pragma unroll 1
    for (int par = warp; par < W1 * W1; par += 4) {
        const uint32_t* p0 = reinterpret_cast<const uint32_t*>(f0 + (size_t)((par >> 8) * 2 * W0 + (par & 255) * 2) * (C * 2)) + lane;
        const uint32_t* p1 = reinterpret_cast<const uint32_t*>(f1 + (size_t)par * (C * 2)) + lane;
        uint32_t v[4][3];
#pragma unroll
        for (int i = 0; i < 3; i++)
#pragma unroll
            for (int j = 0; j < 4; j++) v[j][i] = hadd2(__ldg(p0 + ((j >> 1) * W0 + (j & 1)) * (C / 2) + 32 * i), __ldg(p1 + 32 * i));
#pragma unroll
        for (int j = 0; j < 4; j++) {
            float x[6], s1 = 0.f, s2 = 0.f, d[2] = {0.f, 0.f};
#pragma unroll
            for (int i = 0; i < 3; i++) { x[2 * i] = bflo(v[j][i]); x[2 * i + 1] = bfhi(v[j][i]); s1 += x[2 * i] + x[2 * i + 1]; }
#pragma unroll
            for (int o = 1; o < 32; o <<= 1) s1 += __shfl_xor_sync(~0u, s1, o);
#pragma unroll
            for (int i = 0; i < 6; i++) {
                x[i] -= s1 * (1.f / C); s2 = fmaf(x[i], x[i], s2);
#pragma unroll
                for (int r = 0; r < 2; r++) d[r] = fmaf(x[i], k[r][i], d[r]);
            }
#pragma unroll
            for (int o = 1; o < 32; o <<= 1) {
                s2 += __shfl_xor_sync(~0u, s2, o);
#pragma unroll
                for (int r = 0; r < 2; r++) d[r] += __shfl_xor_sync(~0u, d[r], o);
            }
            const float rs = rsq(s2 * (1.f / C) + 1e-5f);
#pragma unroll
            for (int r = 0; r < 2; r++) {
                const float nm = fmaxf(m[r], d[r] * rs), al = ex2(m[r] - nm), p = ex2(d[r] * rs - nm);
                m[r] = nm; l[r] = fmaf(l[r], al, p);
#pragma unroll
                for (int i = 0; i < 6; i++) a[r][i] = fmaf(a[r][i], al, x[i] * (p * rs));
            }
        }
    }
    bar_sync(B_SLOW, 128);
#pragma unroll
    for (int r = 0; r < 2; r++) {
        float* const o = sm + ((r * 4 + warp) * 32 + lane) * 8;
#pragma unroll
        for (int i = 0; i < 6; i++) o[i] = a[r][i];
        o[6] = l[r]; o[7] = m[r];
    }
    bar_sync(B_SLOW, 128);
    if (warp < 2) {
        const int r = warp;
        const float* const o = sm + (r * 128 + lane) * 8;
        float M = o[7], x[7] = {0.f, 0.f, 0.f, 0.f, 0.f, 0.f, 0.f};
#pragma unroll
        for (int w = 1; w < 4; w++) M = fmaxf(M, o[256 * w + 7]);
#pragma unroll
        for (int w = 0; w < 4; w++) {
            const float e = ex2(o[256 * w + 7] - M);
#pragma unroll
            for (int i = 0; i < 7; i++) x[i] = fmaf(o[256 * w + i], e, x[i]);
        }
        const float rl = 1.f / x[6];
        sts128(sb + RD_B2 + brow(8 * (lane >> 4) + 4 * r + (lane & 3)) + ((lane >> 2) & 3) * 16, packh(x[0] * rl, x[1] * rl), packh(x[2] * rl, x[3] * rl), packh(x[4] * rl, x[5] * rl), lane ? 0u : 0x3C00u);
    }
}

template <bool FIRST>
__device__ __forceinline__ void project(const uint32_t ar, const uint32_t br, const bool hi, const float ws0, const float ws1, const float qv0, const float qv1,
                                        __nv_bfloat16* op0, __nv_bfloat16* op1, Scratch* scr)
{
    uint4 wa[3][6], x[4];
#pragma unroll
    for (int i = 0; i < 18; i++) wa[i / 6][i % 6] = lds128v(ar + i * 512);
    if (FIRST) { bar_arrive(B_PLACE, NTHREADS); bar_sync(B_RDY, 192); }
    else bar_sync(B_SLOW, 128);
    if (FIRST && threadIdx.x == 0) TSX(8, 0);
#pragma unroll
    for (int j = 0; j < 4; j++) x[j] = lds128v(br + 16 * j);
    float o[7][4];
#pragma unroll
    for (int j = 0; j < 7; j++) o[j][0] = o[j][1] = o[j][2] = o[j][3] = 0.f;
#pragma unroll
    for (int i = 0; i < 2; i++) {
        mmah(o[6], 0x3C00u, 0x3C00u, 0x3C00u, 0x3C00u, x[2 * i].w, x[2 * i + 1].w);
#pragma unroll
        for (int n = 0; n < 3; n++) mmah(o[2 * n + i], wa[n][2 * i].x, wa[n][2 * i].y, wa[n][2 * i].z, wa[n][2 * i].w, x[2 * i].x, x[2 * i].y);
#pragma unroll
        for (int n = 0; n < 3; n++) mmah(o[2 * n + 1 - i], wa[n][2 * i + 1].x, wa[n][2 * i + 1].y, wa[n][2 * i + 1].z, wa[n][2 * i + 1].w, x[2 * i + 1].x, x[2 * i + 1].y);
#pragma unroll
        for (int n = 0; n < 3; n++) mmah(o[2 * n + i], wa[n][4 + i].x, wa[n][4 + i].y, wa[n][4 + i].z, wa[n][4 + i].w, x[2 * i].z, x[2 * i + 1].z);
    }
    const float L = o[6][0] + o[6][1], r = rcp(L);
    const float y0 = hi ? (o[2][0] + o[2][3]) + (o[3][0] + o[3][3]) : (o[0][0] + o[0][3]) + (o[1][0] + o[1][3]), y1 = (o[4][0] + o[4][3]) + (o[5][0] + o[5][3]);
    const uint32_t y = pack2(fmaf(y0, r * ws0, qv0), fmaf(y1, r * ws1, qv1));
    asm volatile("{.reg .b16 l, h; mov.b32 {l, h}, %2; st.global.b16 [%0], l; st.global.b16 [%1], h;}" ::"l"(op0), "l"(op1), "r"(y) : "memory");
    if (FIRST && threadIdx.x == 0) TSD(11, y);
    if (FIRST)
        asm volatile("{.reg .pred p; .reg .f32 a; abs.f32 a, %1; setp.ge.f32 p, %0, 0f3B000000; setp.le.and.f32 p, %0, 0f45000000, p; setp.lt.and.f32 p, a, 0f7F800000, p;"
                     " vote.sync.all.pred p, p, 0xffffffff; @p exit;}" ::"f"(L), "f"(y0) : "memory");
}

__device__ __forceinline__ void reducer(const char* __restrict__ f0, const char* __restrict__ f1, const __nv_bfloat16* __restrict__ q, const __nv_bfloat16* __restrict__ wq, const __nv_bfloat16* __restrict__ wk,
                                        Scratch* scr, const __nv_bfloat16* __restrict__ wv, const __nv_bfloat16* __restrict__ wo,
                                        __nv_bfloat16* __restrict__ out, const uint32_t sb, const int GS)
{
    const int warp = threadIdx.x >> 5, lane = threadIdx.x & 31, b = blockIdx.x;
    const int g = lane >> 2, t = lane & 3;
    char* const ap = reinterpret_cast<char*>(g_acc);
    if (threadIdx.x == 256) TS(0);
    if (b < NSRC && warp < 8) {
        const uint32_t wqs = sb + RD_W, wbar = sb + RD_BAR;
        const int hr = lane >> 4, qt = (lane >> 2) & 3, sub = lane & 3;
        const uint32_t* qp = reinterpret_cast<const uint32_t*>(q + (warp + 8 * hr) * C + 48 * qt + 6 * sub);
        uint32_t qw[6];
#pragma unroll
        for (int j = 0; j < 3; j++) { qw[j] = __ldg(qp + j); qw[3 + j] = __ldg(qp + 12 + j); }
        if (lane == 0) { mbar_init(wbar + warp * 8, 1); asm volatile("fence.mbarrier_init.release.cluster;" ::: "memory"); mbar_expect(wbar + warp * 8, 9216);
            asm volatile("cp.async.bulk.shared::cluster.global.mbarrier::complete_tx::bytes [%0], [%1], 9216, [%2];"
                         ::"r"(wqs + warp * 9232), "l"(wq + 24 * warp * C), "r"(wbar + warp * 8) : "memory");
        }
        __syncwarp();
        if (threadIdx.x == 0) TSP(2, 0);
        float e[12];
#pragma unroll
        for (int j = 0; j < 6; j++) { e[2 * j] = bflo(qw[j]); e[2 * j + 1] = bfhi(qw[j]); }
        float sm = ((e[0] + e[1]) + (e[2] + e[3])) + ((e[4] + e[5]) + (e[6] + e[7])) + ((e[8] + e[9]) + (e[10] + e[11]));
#pragma unroll
        for (int o = 1; o < 16; o <<= 1) sm += __shfl_xor_sync(~0u, sm, o);
        if (threadIdx.x == 0) TSP(5, u(sm));
        float v0 = 0.f, v1 = 0.f;
#pragma unroll
        for (int j = 0; j < 12; j++) e[j] -= sm * (1.f / C);
#pragma unroll
        for (int j = 0; j < 6; j++) { v0 = fmaf(e[j], e[j], v0); v1 = fmaf(e[6 + j], e[6 + j], v1); }
        v0 += v1;
#pragma unroll
        for (int o = 1; o < 16; o <<= 1) v0 += __shfl_xor_sync(~0u, v0, o);
        const float rq = rsq(v0 * (1.f / C) + 1e-5f);
#pragma unroll
        for (int j = 0; j < 6; j++)
            sts32(sb + RD_QN + (3 * sub + (j >> 1)) * 512 + (4 * warp + qt) * 16 + (2 * (j & 1) + hr) * 4, pack2(e[j] * rq, e[6 + j] * rq));
        if (threadIdx.x == 0) TSP(8, 0);
        uint32_t wkf[2][3];
#pragma unroll
        for (int i = 0; i < 2; i++)
#pragma unroll
            for (int j = 0; j < 3; j++) wkf[i][j] = __ldg(reinterpret_cast<const uint32_t*>(wk + (16 * b + 8 * i + g) * C + 24 * warp + 8 * j + 2 * t));
        bar_sync(B_QN, 256);
        float acc[2][3][4];
#pragma unroll
        for (int i = 0; i < 3; i++)
#pragma unroll
            for (int e = 0; e < 4; e++) acc[0][i][e] = acc[1][i][e] = 0.f;
        const uint32_t ba = wqs + (lane & 7) * 9232 + (lane >> 3) * 384 + 48 * warp;
        uint4 a[12];
#pragma unroll
        for (int kk = 0; kk < 12; kk++) a[kk] = lds128(sb + RD_QN + kk * 512 + lane * 16);
        mbar_wait(wbar + (lane & 7) * 8, 0);
        __syncwarp();
        if (threadIdx.x == 0) TSP(4, 0);
#pragma unroll
        for (int kp = 0; kp < 6; kp++)
#pragma unroll
            for (int i = 0; i < 3; i++) {
                uint32_t bb[4];
                ldsm4t(bb, ba + kp * 1536 + i * 16);
                mma(acc[0][i], a[2 * kp].x, a[2 * kp].y, a[2 * kp].z, a[2 * kp].w, bb[0], bb[1]);
                mma(acc[1][i], a[2 * kp + 1].x, a[2 * kp + 1].y, a[2 * kp + 1].z, a[2 * kp + 1].w, bb[2], bb[3]);
            }
        if (threadIdx.x == 0) TSP(7, u(acc[1][2][3]));
        float kq[2][4] = {{0.f, 0.f, 0.f, 0.f}, {0.f, 0.f, 0.f, 0.f}};
#pragma unroll
        for (int j = 0; j < 3; j++) {
            const uint32_t a0 = pack2(acc[0][j][0] + acc[1][j][0], acc[0][j][1] + acc[1][j][1]), a1 = pack2(acc[0][j][2] + acc[1][j][2], acc[0][j][3] + acc[1][j][3]);
            mma8(kq[0], a0, a1, wkf[0][j]);
            mma8(kq[1], a0, a1, wkf[1][j]);
        }
        if (warp < 7) {
            sts128(sb + RD_KQ + warp * 1024 + lane * 16, u(kq[0][0]), u(kq[0][1]), u(kq[0][2]), u(kq[0][3]));
            sts128(sb + RD_KQ + warp * 1024 + 512 + lane * 16, u(kq[1][0]), u(kq[1][1]), u(kq[1][2]), u(kq[1][3]));
            bar_arrive(B_Q, 256);
        } else {
            bar_sync(B_Q, 256);
#pragma unroll
            for (int w = 0; w < 7; w++)
#pragma unroll
                for (int i = 0; i < 2; i++) {
                    const uint4 o = lds128(sb + RD_KQ + w * 1024 + i * 512 + lane * 16);
                    kq[i][0] += f(o.x); kq[i][1] += f(o.y); kq[i][2] += f(o.z); kq[i][3] += f(o.w);
                }
            stg_relaxed(g_qk + b * 32 + lane, ~pack2(kq[0][0] * QSCALE, kq[0][1] * QSCALE), ~pack2(kq[0][2] * QSCALE, kq[0][3] * QSCALE),
                        ~pack2(kq[1][0] * QSCALE, kq[1][1] * QSCALE), ~pack2(kq[1][2] * QSCALE, kq[1][3] * QSCALE));
            if (lane == 0) TS(10);
        }
    } else if (warp == 8 && !(b & 1)) {
        char* const pp = ap + (b >> 2) * 8192 + (b & 2) * 512;
        if (lane < 16) stg_relaxed(reinterpret_cast<uint4*>(pp + (lane >> 3) * 4096) + (lane & 7), 0, 0, 0, 0);
        __syncwarp();
        uint32_t place = 0;
        if (lane == 0) {
            uint32_t best[2] = {~0u, ~0u};
#pragma unroll 1
            for (int it = 0; it < NPROBE; it++) {
#pragma unroll
                for (int i = 0; i < 2; i++) {
                    uint32_t c;
                    asm volatile("{.reg .b32 v, c0; .reg .pred p; mov.u32 c0, %%clock; atom.relaxed.gpu.global.exch.b32 v, [%1], 0; setp.ne.u32 p, v, 0; @p trap;"
                                 " mov.u32 %0, %%clock; sub.u32 %0, %0, c0;}" : "=r"(c) : "l"(pp + i * 4096) : "memory");
                    best[i] = min(best[i], c);
                }
            }
            place = acc_place((best[1] < best[0]) ^ ((b >> 2) & 1), b >> 1);
            sts32(sb + RD_PLACE, place);
        }
        place = __shfl_sync(~0u, place, 0);
#pragma unroll
        for (int i = 0; i < 2; i++) stg_relaxed(reinterpret_cast<uint4*>(ap + (acc_line(4 * i + (lane >> 3)) ^ place)) + (lane & 7), 0, 0, 0, 0);
        __threadfence();
    } else if (b >= NSRC) {
        if (b == NSRC && warp == 0) stg_relaxed32(g_mmax + lane, 0);
        __nanosleep(2500);
    }
    bar_sync(B_ALL, NTHREADS);

#pragma unroll 1
    for (int r = 0; r < 3; r++) {
        uint4 v[8];
#pragma unroll
        for (int k = 0; k < 8; k++) {
            const int idx = (8 * r + k) * 384 + threadIdx.x;
            v[k] = __ldg(reinterpret_cast<const uint4*>(idx < 4608 ? wv : wo - C * C) + idx);
        }
#pragma unroll
        for (int k = 0; k < 8; k++) {
            const int idx = (8 * r + k) * 384 + threadIdx.x, row = idx / 24;
            sts128(sb + RD_W + row * WROW + (idx - 24 * row) * 16, v[k].x, v[k].y, v[k].z, v[k].w);
        }
    }
    bar_sync(B_ALL, NTHREADS);
    if (warp < 6) {
        const int col = 96 * (b & 1) + 16 * warp;
        float d[24][4];
#pragma unroll
        for (int i = 0; i < 24; i++) d[i][0] = d[i][1] = d[i][2] = d[i][3] = 0.f;
        const int mi = lane >> 3, r = lane & 7;
        const uint32_t aa = sb + RD_W + (C + (mi >> 1) * 8 + r) * WROW + (col + (mi & 1) * 8) * 2;
        const uint32_t ba = sb + RD_W + ((mi >> 1) * 8 + r) * WROW + (mi & 1) * 16;
#pragma unroll 1
        for (int kk = 0; kk < 12; kk++) {
            uint32_t a[4];
            ldsm4t(a, aa + kk * 16 * WROW);
#pragma unroll
            for (int i = 0; i < 12; i++) {
                uint32_t bb[4];
                ldsm4(bb, ba + i * 16 * WROW + kk * 32);
                mma(d[2 * i], a[0], a[1], a[2], a[3], bb[0], bb[1]);
                mma(d[2 * i + 1], a[0], a[1], a[2], a[3], bb[2], bb[3]);
            }
        }
        float c0 = 0.f, c1 = 0.f, m0 = 0.f, m1 = 0.f;
#pragma unroll
        for (int i = 0; i < 24; i++) { c0 += d[i][0] + d[i][1]; c1 += d[i][2] + d[i][3]; }
        c0 += __shfl_xor_sync(~0u, c0, 1); c1 += __shfl_xor_sync(~0u, c1, 1);
        c0 += __shfl_xor_sync(~0u, c0, 2); c1 += __shfl_xor_sync(~0u, c1, 2);
        c0 *= 1.f / C; c1 *= 1.f / C;
#pragma unroll
        for (int i = 0; i < 24; i++) {
            d[i][0] -= c0; d[i][1] -= c0; d[i][2] -= c1; d[i][3] -= c1;
            m0 = fmaxf(m0, fmaxf(fabsf(d[i][0]), fabsf(d[i][1]))); m1 = fmaxf(m1, fmaxf(fabsf(d[i][2]), fabsf(d[i][3])));
        }
        m0 = fmaxf(m0, __shfl_xor_sync(~0u, m0, 1)); m1 = fmaxf(m1, __shfl_xor_sync(~0u, m1, 1));
        m0 = fmaxf(m0, __shfl_xor_sync(~0u, m0, 2)); m1 = fmaxf(m1, __shfl_xor_sync(~0u, m1, 2));
        const uint32_t e0 = min(max(u(m0) >> 23, 12u), 254u), e1 = min(max(u(m1) >> 23, 12u), 254u);
        const float s0 = f((265u - e0) << 23), s1 = f((265u - e1) << 23);
        const bool k0 = fabsf(c0) < INFINITY, k1 = fabsf(c1) < INFINITY;
#pragma unroll
        for (int j = 0; j < 6; j++) {
            const int n[4] = {j < 4 ? j : 8 + 2 * j, j < 4 ? 4 + j : 12 + 2 * j, j < 4 ? 8 + j : 9 + 2 * j, j < 4 ? 12 + j : 13 + 2 * j};
            uint32_t a[2][4];
#pragma unroll
            for (int e = 0; e < 4; e++) {
                a[0][e] = k0 ? packh(d[n[e]][0] * s0, d[n[e]][1] * s0) : 0u;
                a[1][e] = k1 ? packh(d[n[e]][2] * s1, d[n[e]][3] * s1) : 0u;
            }
#pragma unroll
            for (int e = 0; e < 2; e++) sts128(sb + RD_A + ((2 * warp + e) * 6 + j) * 512 + lane * 16, a[e][0], a[e][1], a[e][2], a[e][3]);
        }
        sts32(sb + RD_WS + 2 * warp * 128 + lane * 4, k0 ? (e0 - 11u) << 23 : u(c0));
        sts32(sb + RD_WS + (2 * warp + 1) * 128 + lane * 4, k1 ? (e1 - 11u) << 23 : u(c1));
        if (warp < 4) bar_sync(B_PARK, 192); else bar_arrive(B_PARK, 192);
        if (threadIdx.x == 0) TSE(6);
    }
    if (warp >= 4) {
        if (threadIdx.x == 128) {
            uint32_t m, place = lds32(sb + RD_PLACE);
            for (int it = 0;; it++) {
                const int left = NT - 2 * NST * GS - (int)ldg_relaxed32(g_ctr);
                m = ldg_relaxed32(g_mmax + b);
                if (left <= REFT && m) break;
                if (left <= 0) { m = 0x80000000u; break; }
                if (it > SPIN_LIMIT) __trap();
                __nanosleep(300);
            }
            if (b & 1) for (int it = 0;; it++) {
                uint32_t r;
                asm volatile("ld.acquire.gpu.global.u32 %0, [%1];" : "=r"(r) : "l"(g_mref + b - 1) : "memory");
                place = ~r & PLACE;
                if (r) break;
                if (it > SPIN_LIMIT) __trap();
            }
            asm volatile("st.release.gpu.global.u32 [%0], %1;" ::"l"(g_mref + b), "r"(~((u(f(m >> 31 ? m ^ 0x80000000u : ~m) + 8.f) & ~PLACE) | place)) : "memory");
            sts32(sb + RD_PLACE, place);
            TSE(7);
        }
        __syncwarp();
        if (warp == 4) {
            uint4* p0 = g_qk + min(b, NSRC - 1) * 32 + lane;
            unsigned* p1 = lane == 1 && b == NSRC ? g_ctr : g_mref + b;
            asm volatile("" : "+l"(p0), "+l"(p1));
            bar_arrive(B_PLACE, NTHREADS);
            bar_sync(B_RDY, 192);
            *p0 = make_uint4(0, 0, 0, 0);
            *p1 = 0;
            return;
        }
        bar_sync(B_PLACE, NTHREADS);
        if (warp >= 5 + NPW) return;
        const uint32_t place = lds32(sb + RD_PLACE);
        const uint4* const pa = reinterpret_cast<const uint4*>(ap + (acc_line(lane >> 3) ^ place)) + (lane & 7);
        const uint32_t bw = opaque(sb + brow(lane & 7) + (lane >> 3) * 16);
        const uint32_t n0 = packh(0.f, (float)GS), nstart = packh(0.f, (float)POLLN);
        for (int it = 0; ldg_relaxed32(ap + place + 12) < nstart; it++)
            if (it > SPIN_LIMIT) __trap();
        for (const unsigned c = clock32(); clock32() - c < (warp - 5) * PGAP;) {}
        for (int it = 0;; it++) {
            const uint4 a0 = ldg_relaxed(pa), b0 = ldg_relaxed(pa + 1024);
            if (it > SPIN_LIMIT) __trap();
            bar_sync(B_WARP, 32);
            asm volatile("{.reg .pred p, q; .reg .b32 a; setp.ge.u32 p, %5, %10; setp.ge.and.u32 p, %9, %10, p; vote.sync.all.pred q, p, 0xffffffff; selp.b32 a, %0, %1, p;"
                         " st.shared.v4.b32 [a], {%2,%3,%4,%5}; st.shared.v4.b32 [a + 704], {%6,%7,%8,%9}; @q bar.arrive 15, 192; @q exit;}"
                         ::"r"(bw), "r"(bw - (RD_B - RD_QN)), "r"(a0.x), "r"(a0.y), "r"(a0.z), "r"(a0.w), "r"(b0.x), "r"(b0.y), "r"(b0.z), "r"(b0.w), "r"(n0) : "memory");
        }
    }
    const uint32_t br = opaque(sb + brow(8 * (g & 1) + 2 * (g & 2) + t));
    const bool hi = t >= 2;
    const int oi = ((b & 14) + (t & 1)) * C + 96 * (b & 1) + 24 * warp + g;
    const float qv0 = __bfloat162float(q[oi + 4 * (t & 2)]), qv1 = __bfloat162float(q[oi + 16]);
    const float ws0 = f(lds32(sb + RD_WS + (3 * warp + (t >> 1)) * 128 + lane * 4)), ws1 = f(lds32(sb + RD_WS + (3 * warp + 2) * 128 + lane * 4));
    __nv_bfloat16* op0 = out + oi + 4 * (t & 2), * op1 = out + oi + 16;
    asm volatile("" : "+l"(op0), "+l"(op1));
    const uint32_t ar = sb + RD_A + warp * 18 * 512 + lane * 16;
    project<true>(ar, br, hi, ws0, ws1, qv0, qv1, op0, op1, scr);
    slow_rows(f0, f1, q, wq, wk, sb);
    project<false>(ar, br + RD_B2, hi, ws0, ws1, qv0, qv1, op0, op1, scr);
}

__global__ void __launch_bounds__(NTHREADS, 1)
attn_main(const char* __restrict__ f0, const char* __restrict__ f1,
          const __nv_bfloat16* __restrict__ q, const __nv_bfloat16* __restrict__ wq, const __nv_bfloat16* __restrict__ wk, Scratch* scr,
          const __nv_bfloat16* __restrict__ wv, const __nv_bfloat16* __restrict__ wo, __nv_bfloat16* __restrict__ out,
          const __grid_constant__ CUtensorMap m0, const __grid_constant__ CUtensorMap m1)
{
    extern __shared__ char smem_raw[];
    const uint32_t sb = (s2u(smem_raw) + 1023u) & ~1023u;
    const int G = gridDim.x - NRD;
    const int b = blockIdx.x - NRD;
    if (threadIdx.x == 0 && b >= 0) {
        const char* a = f0 + (uint32_t)(b * (4 * TP * C * 2) + (b >> 4) * (W0 * C * 2));
        prefetch_l2(a, 4 * TP * C * 2);
        prefetch_l2(a + W0 * C * 2, 4 * TP * C * 2);
        prefetch_l2(f1 + b * (2 * TP * C * 2), 2 * TP * C * 2);
        prefetch_l2((const char*)(b % (2 * WSL) < WSL ? wq : wk) + b % WSL * (C * C * 2 / WSL), C * C * 2 / WSL);
    }
    if (b < 0) { reducer(f0, f1, q, wq, wk, scr, wv, wo, out, sb, G); return; }
    const int warp = __shfl_sync(~0u, threadIdx.x >> 5, 0), lane = threadIdx.x & 31;
    const int g = lane >> 2, t = lane & 3;

    if (warp >= 8) {
        if (warp < 10) {
            const int p = warp - 8;
            const unsigned c0 = clock32();
            const uint32_t sbp = opaque(sb), bar = sbp + SM_BAR + p * 8;
            uint64_t pol; asm volatile("createpolicy.fractional.L2::evict_first.b64 %0, 1.0;" : "=l"(pol));
            if (elect()) {
                if (p == 0) TS(0);
                asm volatile("prefetch.tensormap [%0];" ::"l"(p ? &m1 : &m0) : "memory");
#pragma unroll
                for (int n = 0; n < NI; n++) mbar_init(bar + n * 16, 2);
                asm volatile("fence.mbarrier_init.release.cluster;" ::: "memory");
#pragma unroll
                for (int n = 0; n < NI; n++) {
                    issue_tile(&m0, &m1, sbp, p + 2 * n, 2 * b + p + 2 * n * G, pol);
                    TR(0, 2 * n + p);
                    sts32(sbp + SM_FLAG + (p + 2 * n) * 4, 0);
                    mbar_arrive(bar + n * 16);
                }
#pragma unroll
                for (int n = 0; n < NS / 2; n++) {
                    if (n >= NI) mbar_init(bar + n * 16, 2);
                    mbar_init(bar + NS * 8 + n * 16, 1);
                }
                if (p == 0) mbar_init(sbp + SM_REF, 1);
                asm volatile("fence.mbarrier_init.release.cluster;" ::: "memory");
            }
            __syncwarp();
            bar_arrive(B_QK, NTHREADS);
            if (elect()) {
                int tl = 2 * b + p + 2 * NI * G;
                int s = p + 2 * NI; uint32_t ph = 1;
                int sa = p, na = 0; uint32_t pa = 0;
                bool late = false;
                for (int n = NI;; n++) {
                    const int d = n < NRAMP ? D0 : (tl >= NT - (TA) ? 1 : D1);
                    while (n - na >= d) {
                        mbar_wait(sbp + SM_BAR + sa * 8, pa);
                        if (na < NS / 2) TR(1, 2 * na + p);
                        na++; sa += 2;
                        if (sa >= NS) { sa -= NS; pa ^= 1; }
                    }
                    mbar_wait(sbp + SM_BAR + (NS + s) * 8, ph);
                    if (n < NPACE) while (clock32() - c0 < (n ? T1 + (2 * (n - 1) + p) * TG : T0)) {}
                    issue_tile(&m0, &m1, sbp, s, tl, pol);
                    TR(0, 2 * n + p);
                    int nxt = tl + 2 * G;
                    if (n >= NST - 1) nxt = grab_tile(g_ctr) + 2 * NST * G;
                    const bool last = nxt >= NT;
                    uint32_t flag = last;
                    if (!late && nxt >= NT - MAXT - 16 * b) { late = true; flag |= 2; }
                    if (last) mbar_wait(sbp + SM_REF, 0);
                    sts32(sbp + SM_FLAG + s * 4, flag);
                    mbar_arrive(sbp + SM_BAR + s * 8);
                    if (last) break;
                    s += 2;
                    if (s >= NS) { s -= NS; ph ^= 1; }
                    tl = nxt;
                }
                if (p) TSE(5);
            }
            return;
        }
        const int h = threadIdx.x - 320;
        uint4 v[6];
        for (int it = 0;; it++) {
            bool miss = false;
#pragma unroll
            for (int k = 0; k < 6; k++) v[k] = ldg_relaxed(g_qk + k * 64 + h);
#pragma unroll
            for (int k = 0; k < 6; k++) miss |= has(v[k], 0);
            if (!miss) break;
            if (it > SPIN_LIMIT) __trap();
            if (it == 0) __nanosleep(QSLEEP);
        }
#pragma unroll
        for (int k = 0; k < 6; k++) sts128(sb + SM_QK + (k * 64 + h) * 16, ~v[k].x, ~v[k].y, ~v[k].z, ~v[k].w);
        __syncwarp();
        bar_sync(B_QK, NTHREADS);
        if (warp == 11) return;
        uint32_t r = 1;
        for (int it = 0;; it++) {
            __nanosleep(500);
            if (lane < NQ) asm volatile("ld.acquire.gpu.global.u32 %0, [%1];" : "=r"(r) : "l"(g_mref + lane) : "memory");
            if (__all_sync(~0u, r != 0)) break;
            if (it > SPIN_LIMIT) __trap();
        }
        if (lane < NQ) sts32(sb + SM_M + lane * 4, ~r);
        __syncwarp();
        if (lane == 0) { mbar_arrive(sb + SM_REF); TSE(7); }
        return;
    }

    const int grp = warp >> 2, cw = warp & 3;
    const int xp = lane & 7, mi = lane >> 3;
    const uint32_t offS1 = opaque(12288 + xp * 128 + ((mi ^ xp) << 4)), offS1x = opaque(offS1 ^ 64);
    const uint32_t offS0 = opaque(offS1 - 12288 + cw * 3072), offS0x = opaque(offS0 ^ 64);
    const uint32_t offT = opaque(mi * 3072 + xp * 128 + (((cw + 4 * grp) ^ xp) << 4)), offTx = opaque(offT ^ 64);
    const uint32_t offU = opaque(12288 + (mi % 3) * 1024 + xp * 128 + (((cw + 4 * (grp ^ (mi / 3))) ^ xp) << 4));
    const uint32_t offV = opaque(12288 + (1 + (mi & 1)) * 1024 + xp * 128 + (((cw + 4 * (grp ^ 1)) ^ xp) << 4));
    const int shl = opaque(9 * t), shl4 = opaque(9 * t + 4);
    const uint32_t pw = opaque((cw >> 1) * 512 + lane * 16 + (cw & 1) * 8), muw = opaque(1024 + t * 16 + cw * 4);
    const uint32_t prd = opaque(lane * 16), mur = opaque(1024 + t * 16), mof = g * 4;
    uint32_t pb0 = sb + SM_P + grp * 2 * PBUF;
    const uint32_t pbx = pb0 ^ (pb0 + PBUF);
    const bool odd = g & 1;
    const int barid = B_GRP + grp;
    const bool elected = cw == 3 && lane == 0;

    uint32_t qa[48];
    float r_lo, r_hi;
    bar_sync(B_QK, NTHREADS);
    {
        float rr[2][4] = {{0.f, 0.f, 0.f, 0.f}, {0.f, 0.f, 0.f, 0.f}};
#pragma unroll
        for (int kk = 0; kk < 12; kk++) {
            const uint4 v = lds128(sb + SM_QK + kk * 512 + lane * 16);
            qa[4 * kk] = v.x; qa[4 * kk + 1] = v.y; qa[4 * kk + 2] = v.z; qa[4 * kk + 3] = v.w;
            mma(rr[kk & 1], v.x, v.y, v.z, v.w, ONES, ONES);
        }
        r_lo = rr[0][0] + rr[1][0]; r_hi = rr[0][2] + rr[1][2];
    }
    if (threadIdx.x == 0) TS(1);

    float acc[6][4];
#pragma unroll
    for (int i = 0; i < 6; i++) acc[i][0] = acc[i][1] = acc[i][2] = acc[i][3] = 0.f;
    float m_lo = -INFINITY, m_hi = -INFINITY, l_lo = 0.f, l_hi = 0.f;
    float cm[4] = {0.f, 0.f, 0.f, 0.f};
    uint32_t xt[6][4], yt[6]; uint4 pa, pb, mv;
    const uint32_t dof = opaque(acc_line(warp) + (lane & 7) * 16);
    const uint32_t xof = 512 - lane * 8;
    uint32_t ref_lo = 0, ref_hi = 0;
    const uint32_t mad = sb + SM_M + mof;
    uint32_t st = sb + SM_STAGES + grp * STAGE;
    int s = grp; uint32_t ph = 0;
    while (true) {
        mbar_wait(sb + SM_BAR + s * 8, ph);
        PH(0, 0);
        const uint32_t stop = lds32(sb + SM_FLAG + s * 4);
        float sc[2][4], gr[4][4], sx[4];
#pragma unroll
        for (int e = 0; e < 4; e++) sc[0][e] = sc[1][e] = gr[0][e] = gr[1][e] = gr[2][e] = gr[3][e] = sx[e] = 0.f;
#pragma unroll
        for (int qq = 0; qq < 6; qq++) {
            uint32_t x[4], y[4];
            ldsm4(x, st + (qq & 1 ? offS0x : offS0) + (qq >> 1) * 1024);
            ldsm4(y, st + (qq & 1 ? offS1x : offS1) + (qq >> 1) * 1024);
#pragma unroll
            for (int e = 0; e < 4; e++) x[e] = hadd2(x[e], y[e]);
            mma8(gr[0], x[0], x[1], x[0]);
            mma8(gr[1], x[0], x[1], x[1]);
            mma(sx, x[0], x[1], x[2], x[3], ONES, ONES);
            mma8(gr[GR4 ? 2 : 0], x[2], x[3], x[2]);
            mma8(gr[GR4 ? 3 : 1], x[2], x[3], x[3]);
            mma(sc[0], qa[8 * qq], qa[8 * qq + 1], qa[8 * qq + 2], qa[8 * qq + 3], x[0], x[1]);
            mma(sc[1], qa[8 * qq + 4], qa[8 * qq + 5], qa[8 * qq + 6], qa[8 * qq + 7], x[2], x[3]);
        }
        ldsm4t(yt, st + offU);
        ldsm2t(yt + 4, st + offV);
#pragma unroll
        for (int i = 0; i < 6; i++) ldsm4t(xt[i], st + (i < 3 ? offT : offTx) + (i % 3) * 1024);

        const float mu = (sx[0] + sx[2]) * (1.f / C), ss = GR4 ? (odd ? (gr[0][1] + gr[1][3]) + (gr[2][1] + gr[3][3]) : (gr[0][0] + gr[1][2]) + (gr[2][0] + gr[3][2])) : (odd ? gr[0][1] + gr[1][3] : gr[0][0] + gr[1][2]);
        const float rs = rsq(fmaxf(fmaf(-mu, mu, fmaf(ss, 1.f / C, 1e-5f)), 1e-5f));
        const float mu0 = __shfl_sync(~0u, mu, shl), mu1 = __shfl_sync(~0u, mu, shl4);
        const float rs0 = __shfl_sync(~0u, rs, shl), rs1 = __shfl_sync(~0u, rs, shl4);
        const float u0 = fmaf(-mu0, r_lo, sc[0][0] + sc[1][0]), u1 = fmaf(-mu1, r_lo, sc[0][1] + sc[1][1]);
        const float u2 = fmaf(-mu0, r_hi, sc[0][2] + sc[1][2]), u3 = fmaf(-mu1, r_hi, sc[0][3] + sc[1][3]);
        const float d0 = fmaf(u0, rs0, -m_lo), d1 = fmaf(u1, rs1, -m_lo), d2 = fmaf(u2, rs0, -m_hi), d3 = fmaf(u3, rs1, -m_hi);
        PH(1, u(d0 + d2));
        float p0 = ex2(d0), p1 = ex2(d1), p2 = ex2(d2), p3 = ex2(d3);
        sts64(pb0 + pw, pack2(p0 * rs0, p1 * rs1), pack2(p2 * rs0, p3 * rs1));
        if (lane < 4) sts32(pb0 + muw, pack2(mu0, mu1));
        asm volatile("{.reg .pred p; setp.ne.u32 p, %2, 0; @p ld.shared.b32 %0, [%3]; @p ld.shared.b32 %1, [%3+32];}" : "+r"(ref_lo), "+r"(ref_hi) : "r"(stop & 1), "r"(mad) : "memory");
        const bool over = bar_any(barid, 128, fmaxf(fmaxf(d0, d1), fmaxf(d2, d3)) > LAZY);
        PH(3, 0);
        pa = lds128(pb0 + prd); pb = lds128(pb0 + prd + 512); mv = lds128(pb0 + mur);
        if (stop & 1) { l_lo += p0 + p1; l_hi += p2 + p3; break; }
        if (elected) mbar_arrive(sb + SM_BAR + (NS + s) * 8);
        if (__builtin_expect(over, 0)) {
            const float s0 = u0 * rs0, s1 = u1 * rs1, s2 = u2 * rs0, s3 = u3 * rs1;
            float xl = fmaxf(s0, s1), xh = fmaxf(s2, s3);
            xl = fmaxf(xl, __shfl_xor_sync(~0u, xl, 1)); xh = fmaxf(xh, __shfl_xor_sync(~0u, xh, 1));
            xl = fmaxf(xl, __shfl_xor_sync(~0u, xl, 2)); xh = fmaxf(xh, __shfl_xor_sync(~0u, xh, 2));
            if (t < 2) sts32(sb + SM_MX + grp * 256 + ((g + 8 * t) * 4 + cw) * 4, u(t ? xh : xl));
            bar_sync(B_MAX + grp, 128);
            const uint4 ml4 = lds128(sb + SM_MX + grp * 256 + g * 16), mh4 = lds128(sb + SM_MX + grp * 256 + g * 16 + 128);
            const float nl = fmaxf(fmaxf(fmaxf(f(ml4.x), f(ml4.y)), fmaxf(f(ml4.z), f(ml4.w))), m_lo);
            const float nh = fmaxf(fmaxf(fmaxf(f(mh4.x), f(mh4.y)), fmaxf(f(mh4.z), f(mh4.w))), m_hi);
            p0 = ex2(s0 - nl); p1 = ex2(s1 - nl); p2 = ex2(s2 - nh); p3 = ex2(s3 - nh);
            sts64(pb0 + pw, pack2(p0 * rs0, p1 * rs1), pack2(p2 * rs0, p3 * rs1));
            const float al = ex2(m_lo - nl), ah = ex2(m_hi - nh);
            m_lo = nl; m_hi = nh;
            l_lo *= al; l_hi *= ah; cm[0] *= al; cm[2] *= ah;
#pragma unroll
            for (int i = 0; i < 6; i++) { acc[i][0] *= al; acc[i][1] *= al; acc[i][2] *= ah; acc[i][3] *= ah; }
            bar_sync(B_MAX + grp, 128);
            pa = lds128(pb0 + prd); pb = lds128(pb0 + prd + 512);
        }
        l_lo += p0 + p1; l_hi += p2 + p3;
#pragma unroll
        for (int i = 0; i < 6; i++) mma(acc[i], pa.x, pa.y, pa.z, pa.w, hadd2v(xt[i][0], yt[i]), hadd2v(xt[i][1], yt[i]));
        mma(cm, pa.x, pa.y, pa.z, pa.w, mv.x, mv.y);
#pragma unroll
        for (int i = 0; i < 6; i++) mma(acc[i], pb.x, pb.y, pb.z, pb.w, hadd2v(xt[i][2], yt[i]), hadd2v(xt[i][3], yt[i]));
        mma(cm, pb.x, pb.y, pb.z, pb.w, mv.z, mv.w);
        PH(4, u(acc[5][0]));
        if (stop) {
            float a = l_lo + __shfl_xor_sync(~0u, l_lo, 1), c = l_hi + __shfl_xor_sync(~0u, l_hi, 1);
            a += __shfl_xor_sync(~0u, a, 2); c += __shfl_xor_sync(~0u, c, 2);
            const uint32_t m = u((t ? m_hi : m_lo) + lg2(fmaxf(t ? c : a, 1.f)));
            if (t < 2) asm volatile("red.relaxed.gpu.global.max.u32 [%0], %1;" ::"l"(g_mmax + g + 8 * t), "r"(m >> 31 ? ~m : m | 0x80000000u) : "memory");
        }
        pb0 ^= pbx;
        s += 2;
        st += 2 * STAGE;
        if (s >= NS) { s -= NS; ph ^= 1; st -= NS * STAGE; }
        asm volatile("" : "+r"(st));
    }
    const float al = ex2(m_lo - f(ref_lo)), ah = ex2(m_hi - f(ref_hi));
    mma(cm, pa.x, pa.y, pa.z, pa.w, mv.x, mv.y);
#pragma unroll
    for (int i = 3; i < 6; i++) mma(acc[i], pa.x, pa.y, pa.z, pa.w, hadd2v(xt[i][0], yt[i]), hadd2v(xt[i][1], yt[i]));
    mma(cm, pb.x, pb.y, pb.z, pb.w, mv.z, mv.w);
#pragma unroll
    for (int i = 3; i < 6; i++) mma(acc[i], pb.x, pb.y, pb.z, pb.w, hadd2v(xt[i][2], yt[i]), hadd2v(xt[i][3], yt[i]));
#pragma unroll
    for (int i = 0; i < 3; i++) mma(acc[i], pa.x, pa.y, pa.z, pa.w, hadd2v(xt[i][0], yt[i]), hadd2v(xt[i][1], yt[i]));
#pragma unroll
    for (int i = 0; i < 3; i++) mma(acc[i], pb.x, pb.y, pb.z, pb.w, hadd2v(xt[i][2], yt[i]), hadd2v(xt[i][3], yt[i]));
    if (threadIdx.x == grp * 128) TSE(2 + grp);
    if (threadIdx.x == grp * 128 + 96) TSX(2 + grp, u(acc[5][0]));

    uint4* const dst = reinterpret_cast<uint4*>(reinterpret_cast<char*>(g_acc) + (dof ^ (ref_lo & PLACE)));
    uint4* const dsu = reinterpret_cast<uint4*>(reinterpret_cast<char*>(g_acc) + (dof ^ (ref_hi & PLACE)));
    const uint32_t xw = sb + SM_STAGES + grp * STAGE + cw * 768 + prd, xr = sb + SM_STAGES + (grp ^ 1) * STAGE + cw * 768 + prd;
    const float cl = -cm[0] * al, ch = -cm[2] * ah;
    uint32_t hl[6], hh[6];
#pragma unroll
    for (int i = 3; i < 6; i++) { hl[i] = packh(fmaf(acc[i][0], al, cl), fmaf(acc[i][1], al, cl)); hh[i] = packh(fmaf(acc[i][2], ah, ch), fmaf(acc[i][3], ah, ch)); }
    sts128(xw, hl[3], hl[4], hl[5], hh[3]);
    sts64(xw + xof, hh[4], hh[5]);
#pragma unroll
    for (int i = 0; i < 3; i++) { hl[i] = packh(fmaf(acc[i][0], al, cl), fmaf(acc[i][1], al, cl)); hh[i] = packh(fmaf(acc[i][2], ah, ch), fmaf(acc[i][3], ah, ch)); }
    const uint32_t w_lo = packh(l_lo * al, 1.f), w_hi = packh(l_hi * ah, 1.f);
    bar_sync(B_MERGE, 256);
    if (threadIdx.x == 224) TSX(4, 0);
    const uint4 o = lds128(xr);
    const uint2 o2 = lds64(xr + xof);
    red8h(dst, haddh(hl[0], o.x), haddh(hl[1], o.y), haddh(hl[2], o.z), w_lo);
    red8h(dsu, haddh(hh[0], o.w), haddh(hh[1], o2.x), haddh(hh[2], o2.y), w_hi);
    if (threadIdx.x == 0) TSE(4);
    if (threadIdx.x == 224) TSX(9, 0);
}

typedef CUresult (*EncodeFn)(CUtensorMap*, CUtensorMapDataType, cuuint32_t, void*, const cuuint64_t*, const cuuint64_t*,
                             const cuuint32_t*, const cuuint32_t*, CUtensorMapInterleave, CUtensorMapSwizzle,
                             CUtensorMapL2promotion, CUtensorMapFloatOOBfill);

}

extern "C" void kernel_launch(void* const* d_in, const int* in_sizes, int n_in, void* d_out, int out_size) {
    const __nv_bfloat16* q = (const __nv_bfloat16*)d_in[0];
    char* f0 = (char*)d_in[1];
    char* f1 = (char*)d_in[2];
    const __nv_bfloat16* wq = (const __nv_bfloat16*)d_in[3];
    const __nv_bfloat16* wk = (const __nv_bfloat16*)d_in[4];
    const __nv_bfloat16* wv = (const __nv_bfloat16*)d_in[5];
    const __nv_bfloat16* wo = (const __nv_bfloat16*)d_in[6];

    static EncodeFn enc = nullptr;
    static int grid = 0;
    static Scratch* scr = nullptr;
    if (!enc) {
        void* fn = nullptr; cudaDriverEntryPointQueryResult qr;
        cudaGetDriverEntryPoint("cuTensorMapEncodeTiled", &fn, cudaEnableDefault, &qr);
        enc = (EncodeFn)fn;
        cudaGetSymbolAddress((void**)&scr, g_scratch);
        int dev = 0, sms = 0;
        cudaGetDevice(&dev);
        cudaDeviceGetAttribute(&sms, cudaDevAttrMultiProcessorCount, dev);
        grid = sms < MAXG ? sms : MAXG;
        cudaFuncSetAttribute(attn_main, cudaFuncAttributeMaxDynamicSharedMemorySize, SMEM_BYTES);
    }
    CUtensorMap m0, m1;
    {
        cuuint64_t dims[5] = {64, W1, 3, 2, W0};
        cuuint64_t str[4] = {2 * C * 2, 128, C * 2, (cuuint64_t)W0 * C * 2};
        cuuint32_t box[5] = {64, TP, 3, 2, 2}, es[5] = {1, 1, 1, 1, 1};
        enc(&m0, CU_TENSOR_MAP_DATA_TYPE_BFLOAT16, 5, f0, dims, str, box, es, CU_TENSOR_MAP_INTERLEAVE_NONE,
            CU_TENSOR_MAP_SWIZZLE_128B, CU_TENSOR_MAP_L2_PROMOTION_NONE, CU_TENSOR_MAP_FLOAT_OOB_FILL_NONE);
    }
    {
        cuuint64_t dims[4] = {64, W1, 3, W1};
        cuuint64_t str[3] = {C * 2, 128, (cuuint64_t)W1 * C * 2};
        cuuint32_t box[4] = {64, TP, 3, 1}, es[4] = {1, 1, 1, 1};
        enc(&m1, CU_TENSOR_MAP_DATA_TYPE_BFLOAT16, 4, f1, dims, str, box, es, CU_TENSOR_MAP_INTERLEAVE_NONE,
            CU_TENSOR_MAP_SWIZZLE_128B, CU_TENSOR_MAP_L2_PROMOTION_NONE, CU_TENSOR_MAP_FLOAT_OOB_FILL_NONE);
    }
    attn_main<<<grid, NTHREADS, SMEM_BYTES, cudaStreamPerThread>>>(f0, f1, q, wq, wk, scr, wv, wo, (__nv_bfloat16*)d_out, m0, m1);
}
```

```cpp
#include <cuda_runtime.h>
#include <cuda_bf16.h>
#include <cuda.h>
#include <stdint.h>
#include <stdio.h>

namespace {

constexpr int C = 192;
constexpr int NQ = 16;
constexpr int W0 = 512;
constexpr int W1 = 256;
constexpr int TP = 8;
constexpr int NT = W1 * W1 / TP;
constexpr int STAGE = TP * 5 * C * 2;
#define NS 14
#define D0 3
#define D1 2
#define NRAMP 5
#define TA (p ? 470 : 185)
#define QSLEEP 700
#define WSL 24
#define MAXT 3000
#define REFT 1800
#define POLLN 1
#define PGAP 64
#define NPW 5
#define NPROBE 8
#define LAZY 12.f
#define GR4 1
#define NST 4
#define NI 1
#define NPACE 5
#define T0 0
#define T1 1600
#define TG 960
static_assert(NST > D0, "the first dynamic tile index must not delay the start");
constexpr int NTHREADS = 384;
constexpr int MAXG = 132;
constexpr int NRD = NQ;
constexpr int NSRC = 12;
constexpr int SPIN_LIMIT = 1 << 22;

constexpr int SM_STAGES = 0;
constexpr int SM_P = NS * STAGE;
constexpr int PBUF = 1088;
constexpr int SM_QK = SM_P + 4 * PBUF;
constexpr int SM_MX = SM_QK + 6144;
constexpr int SM_M = SM_MX + 512;
constexpr int SM_BAR = SM_M + 64;
constexpr int SM_REF = SM_BAR + 16 * NS;
constexpr int SM_FLAG = SM_REF + 8;
constexpr int SM_TOTAL = SM_FLAG + 4 * NS;
constexpr int SMEM_BYTES = SM_TOTAL + 1024;
static_assert(SMEM_BYTES <= 232448, "smem");
constexpr int WROW = 400;
constexpr int RD_W = 0;
constexpr int RD_QN = 2 * C * WROW;
constexpr int RD_KQ = RD_QN + 6144;
constexpr int RD_B = RD_KQ + 7168;
constexpr int RD_B2 = 17 * 80;
constexpr int RD_PLACE = RD_B + 2 * RD_B2;
constexpr int RD_BAR = RD_PLACE + 16;
constexpr int RD_A = RD_BAR + 64;
constexpr int RD_WS = RD_A + 12 * 6 * 512;
static_assert(RD_WS + 12 * 128 <= SM_TOTAL, "smem");

struct Scratch {
    uint4 acc[2048];
    uint4 qk[NSRC * 32];
    unsigned ctr[32];
    unsigned mmax[32];
    unsigned mref[32];
};
__device__ __align__(8192) Scratch g_scratch;
#define g_acc (scr->acc)
#define g_qk (scr->qk)
#define g_ctr (scr->ctr)
#define g_mmax (scr->mmax)
#define g_mref (scr->mref)
#define g_ts (scr->ts)
#define g_tr (scr->tr)
#define TR(k, i) do {} while (0)
#define TS(i) do {} while (0)
#define TSD(i, dep) do {} while (0)
#define TSX(i, dep) do {} while (0)
#define TSP(i, dep) do {} while (0)
#define TSE(i) TS(i)
#define CK_(i, dep) do {} while (0)
#define PH(i, dep) do {} while (0)

__device__ __forceinline__ uint32_t s2u(const void* p) { return (uint32_t)__cvta_generic_to_shared(p); }
__device__ __forceinline__ void mbar_init(uint32_t a, int c) { asm volatile("mbarrier.init.shared::cta.b64 [%0], %1;" ::"r"(a), "r"(c) : "memory"); }
__device__ __forceinline__ void mbar_expect(uint32_t a, uint32_t b) { asm volatile("mbarrier.arrive.expect_tx.shared::cta.b64 _, [%0], %1;" ::"r"(a), "r"(b) : "memory"); }
__device__ __forceinline__ void mbar_arrive(uint32_t a) { asm volatile("mbarrier.arrive.shared::cta.b64 _, [%0];" ::"r"(a) : "memory"); }
__device__ __forceinline__ void mbar_wait(uint32_t a, uint32_t ph) {
    uint32_t ok; int it = 0;
    do {
        asm volatile("{.reg .pred p; mbarrier.try_wait.parity.shared::cta.b64 p, [%1], %2; selp.u32 %0,1,0,p;}" : "=r"(ok) : "r"(a), "r"(ph) : "memory");
        if (++it > SPIN_LIMIT) __trap();
    } while (!ok);
}
__device__ __forceinline__ bool elect() {
    uint32_t r; asm volatile("{.reg .pred p; elect.sync _|p, 0xffffffff; selp.u32 %0, 1, 0, p;}" : "=r"(r)); return r;
}
__device__ __forceinline__ void bar_sync(int id, int n) { asm volatile("bar.sync %0, %1;" ::"r"(id), "r"(n) : "memory"); }
__device__ __forceinline__ bool bar_any(int id, int n, bool c) {
    uint32_t r;
    asm volatile("{.reg .pred p, q; setp.ne.u32 q, %3, 0; bar.red.or.pred p, %1, %2, q; selp.u32 %0, 1, 0, p;}" : "=r"(r) : "r"(id), "r"(n), "r"((uint32_t)c) : "memory");
    return r;
}
__device__ __forceinline__ void bar_arrive(int id, int n) { asm volatile("bar.arrive %0, %1;" ::"r"(id), "r"(n) : "memory"); }
__device__ __forceinline__ void ldsm4(uint32_t* r, uint32_t a) {
    asm volatile("ldmatrix.sync.aligned.m8n8.x4.shared.b16 {%0,%1,%2,%3}, [%4];" : "=r"(r[0]), "=r"(r[1]), "=r"(r[2]), "=r"(r[3]) : "r"(a) : "memory");
}
__device__ __forceinline__ void ldsm4t(uint32_t* r, uint32_t a) {
    asm volatile("ldmatrix.sync.aligned.m8n8.x4.trans.shared.b16 {%0,%1,%2,%3}, [%4];" : "=r"(r[0]), "=r"(r[1]), "=r"(r[2]), "=r"(r[3]) : "r"(a) : "memory");
}
__device__ __forceinline__ void ldsm2t(uint32_t* r, uint32_t a) {
    asm volatile("ldmatrix.sync.aligned.m8n8.x2.trans.shared.b16 {%0,%1}, [%2];" : "=r"(r[0]), "=r"(r[1]) : "r"(a) : "memory");
}
__device__ __forceinline__ void mma(float* d, uint32_t a0, uint32_t a1, uint32_t a2, uint32_t a3, uint32_t b0, uint32_t b1) {
    asm("mma.sync.aligned.m16n8k16.row.col.f32.bf16.bf16.f32 {%0,%1,%2,%3}, {%4,%5,%6,%7}, {%8,%9}, {%0,%1,%2,%3};"
        : "+f"(d[0]), "+f"(d[1]), "+f"(d[2]), "+f"(d[3]) : "r"(a0), "r"(a1), "r"(a2), "r"(a3), "r"(b0), "r"(b1));
}
__device__ __forceinline__ void mmah(float* d, uint32_t a0, uint32_t a1, uint32_t a2, uint32_t a3, uint32_t b0, uint32_t b1) {
    asm("mma.sync.aligned.m16n8k16.row.col.f32.f16.f16.f32 {%0,%1,%2,%3}, {%4,%5,%6,%7}, {%8,%9}, {%0,%1,%2,%3};"
        : "+f"(d[0]), "+f"(d[1]), "+f"(d[2]), "+f"(d[3]) : "r"(a0), "r"(a1), "r"(a2), "r"(a3), "r"(b0), "r"(b1));
}
__device__ __forceinline__ void mma8(float* d, uint32_t a0, uint32_t a1, uint32_t b0) {
    asm("mma.sync.aligned.m16n8k8.row.col.f32.bf16.bf16.f32 {%0,%1,%2,%3}, {%4,%5}, {%6}, {%0,%1,%2,%3};"
        : "+f"(d[0]), "+f"(d[1]), "+f"(d[2]), "+f"(d[3]) : "r"(a0), "r"(a1), "r"(b0));
}
__device__ __forceinline__ uint32_t hadd2(uint32_t a, uint32_t b) {
    uint32_t r; asm("add.rn.bf16x2 %0, %1, %2;" : "=r"(r) : "r"(a), "r"(b)); return r;
}
__device__ __forceinline__ uint32_t pack2(float lo, float hi) {
    uint32_t r; asm("cvt.rn.bf16x2.f32 %0, %1, %2;" : "=r"(r) : "f"(hi), "f"(lo)); return r;
}
__device__ __forceinline__ uint32_t packh(float lo, float hi) {
    uint32_t r; asm("cvt.rn.f16x2.f32 %0, %1, %2;" : "=r"(r) : "f"(hi), "f"(lo)); return r;
}
__device__ __forceinline__ float2 unpackh(uint32_t v) {
    float2 r; asm("{.reg .b16 l, h; mov.b32 {l, h}, %2; cvt.f32.f16 %0, l; cvt.f32.f16 %1, h;}" : "=f"(r.x), "=f"(r.y) : "r"(v)); return r;
}
__device__ __forceinline__ float bflo(uint32_t v) { return __uint_as_float(v << 16); }
__device__ __forceinline__ float bfhi(uint32_t v) { return __uint_as_float(v & 0xffff0000u); }
__device__ __forceinline__ float ex2(float x) { float r; asm("ex2.approx.ftz.f32 %0, %1;" : "=f"(r) : "f"(x)); return r; }
__device__ __forceinline__ void sts128(uint32_t a, uint32_t x, uint32_t y, uint32_t z, uint32_t w) {
    asm volatile("st.shared.v4.b32 [%0], {%1,%2,%3,%4};" ::"r"(a), "r"(x), "r"(y), "r"(z), "r"(w) : "memory");
}
__device__ __forceinline__ void sts64(uint32_t a, uint32_t x, uint32_t y) {
    asm volatile("st.shared.v2.b32 [%0], {%1,%2};" ::"r"(a), "r"(x), "r"(y) : "memory");
}
__device__ __forceinline__ void sts32(uint32_t a, uint32_t x) { asm volatile("st.shared.b32 [%0], %1;" ::"r"(a), "r"(x) : "memory"); }
__device__ __forceinline__ uint4 lds128(uint32_t a) {
    uint4 v; asm volatile("ld.shared.v4.b32 {%0,%1,%2,%3}, [%4];" : "=r"(v.x), "=r"(v.y), "=r"(v.z), "=r"(v.w) : "r"(a) : "memory"); return v;
}
__device__ __forceinline__ uint2 lds64(uint32_t a) {
    uint2 v; asm volatile("ld.shared.v2.b32 {%0,%1}, [%2];" : "=r"(v.x), "=r"(v.y) : "r"(a) : "memory"); return v;
}
__device__ __forceinline__ uint32_t haddh(uint32_t a, uint32_t b) {
    uint32_t r; asm("add.rn.f16x2 %0, %1, %2;" : "=r"(r) : "r"(a), "r"(b)); return r;
}
__device__ __forceinline__ uint32_t lds32(uint32_t a) { uint32_t v; asm volatile("ld.shared.b32 %0, [%1];" : "=r"(v) : "r"(a) : "memory"); return v; }
__device__ __forceinline__ int grab_tile(unsigned* ctr) {
    int v; asm volatile("atom.relaxed.gpu.global.inc.u32 %0, [%1], 0x7fffffff;" : "=r"(v) : "l"(ctr) : "memory"); return v;
}
__device__ __forceinline__ uint32_t opaque(uint32_t v) { uint32_t r; asm volatile("mov.b32 %0, %1;" : "=r"(r) : "r"(v)); return r; }
__device__ __forceinline__ unsigned clock32() { unsigned c; asm volatile("mov.u32 %0, %%clock;" : "=r"(c)); return c; }
__device__ __forceinline__ float rsq(float x) { float r; asm("rsqrt.approx.ftz.f32 %0, %1;" : "=f"(r) : "f"(x)); return r; }
__device__ __forceinline__ float rcp(float x) { float r; asm("rcp.approx.ftz.f32 %0, %1;" : "=f"(r) : "f"(x)); return r; }
__device__ __forceinline__ float lg2(float x) { float r; asm("lg2.approx.ftz.f32 %0, %1;" : "=f"(r) : "f"(x)); return r; }
__device__ __forceinline__ float f(uint32_t v) { return __uint_as_float(v); }
__device__ __forceinline__ uint32_t u(float v) { return __float_as_uint(v); }

constexpr uint32_t ONES = 0x3F803F80u;
constexpr float QSCALE = 0.07216878364870322f * 1.4426950408889634f;

__device__ __forceinline__ void issue_tile(const CUtensorMap* m0, const CUtensorMap* m1, uint32_t sb, int s, int tl, uint64_t pol) {
    const uint32_t full = sb + SM_BAR + s * 8, dst = sb + SM_STAGES + s * STAGE;
    const int par = tl * TP, y = par >> 8, x = par & 255;
    mbar_expect(full, STAGE);
    asm volatile("cp.async.bulk.tensor.5d.shared::cluster.global.mbarrier::complete_tx::bytes.L2::cache_hint [%0], [%1, {%3,%4,%3,%3,%5}], [%2], %6;"
                 ::"r"(dst), "l"(m0), "r"(full), "r"(0), "r"(x), "r"(2 * y), "l"(pol) : "memory");
    asm volatile("cp.async.bulk.tensor.4d.shared::cluster.global.mbarrier::complete_tx::bytes.L2::cache_hint [%0], [%1, {%3,%4,%3,%5}], [%2], %6;"
                 ::"r"(dst + TP * 4 * C * 2), "l"(m1), "r"(full), "r"(0), "r"(x), "r"(y), "l"(pol) : "memory");
}

__device__ __forceinline__ void prefetch_l2(const void* a, int n) { asm volatile("cp.async.bulk.prefetch.L2.global [%0], %1;" ::"l"(a), "r"(n) : "memory"); }
__device__ __forceinline__ uint4 ldg_relaxed(const uint4* p) {
    uint4 v; asm volatile("ld.relaxed.gpu.global.v4.u32 {%0,%1,%2,%3}, [%4];" : "=r"(v.x), "=r"(v.y), "=r"(v.z), "=r"(v.w) : "l"(p) : "memory"); return v;
}
__device__ __forceinline__ uint32_t ldg_relaxed32(const void* p) {
    uint32_t v; asm volatile("ld.relaxed.gpu.global.u32 %0, [%1];" : "=r"(v) : "l"(p) : "memory"); return v;
}
__device__ __forceinline__ void stg_relaxed(uint4* p, uint32_t x, uint32_t y, uint32_t z, uint32_t w) {
    asm volatile("st.relaxed.gpu.global.v4.u32 [%0], {%1,%2,%3,%4};" ::"l"(p), "r"(x), "r"(y), "r"(z), "r"(w) : "memory");
}
__device__ __forceinline__ void stg_relaxed32(void* p, uint32_t x) { asm volatile("st.relaxed.gpu.global.u32 [%0], %1;" ::"l"(p), "r"(x) : "memory"); }
__device__ __forceinline__ bool has(const uint4& v, uint32_t m) { return v.x == m || v.y == m || v.z == m || v.w == m; }
__device__ __forceinline__ uint32_t hadd2v(uint32_t a, uint32_t b) {
    uint32_t r; asm volatile("add.rn.bf16x2 %0, %1, %2;" : "=r"(r) : "r"(a), "r"(b)); return r;
}

__device__ __forceinline__ void red8h(uint4* p, uint32_t x, uint32_t y, uint32_t z, uint32_t w) {
    asm volatile("red.relaxed.gpu.global.add.noftz.v4.f16x2 [%0], {%1,%2,%3,%4};" ::"l"(p), "r"(x), "r"(y), "r"(z), "r"(w) : "memory");
}
__device__ __forceinline__ uint4 lds128v(uint32_t a) {
    uint4 v; asm volatile("ld.volatile.shared.v4.b32 {%0,%1,%2,%3}, [%4];" : "=r"(v.x), "=r"(v.y), "=r"(v.z), "=r"(v.w) : "r"(a) : "memory"); return v;
}
__device__ __forceinline__ uint32_t brow(int r) { return RD_B + r * 80 + (r >> 3) * 64; }

constexpr uint32_t PLACE = 0x1980;
__device__ __forceinline__ uint32_t acc_line(int k) { return (k >> 2) * 16384 + (k & 2) * 6144 + (k & 1) * 1024; }
__device__ __forceinline__ uint32_t acc_place(int side, int s) { return side * 4096 + (s & 1) * 256 + (s & 2) * 1024 + (s & 4) * 32; }

enum { B_QK = 1, B_QN = 2, B_GRP = 3  , B_Q = 5, B_MERGE = 6, B_ALL = 7, B_MAX = 8  , B_WARP = 10, B_SLOW = 12, B_PARK = 13, B_PLACE = 14, B_RDY = 15 };

__device__ __noinline__ void slow_rows(const char* __restrict__ f0, const char* __restrict__ f1, const __nv_bfloat16* __restrict__ q,
                                       const __nv_bfloat16* __restrict__ wq, const __nv_bfloat16* __restrict__ wk, const uint32_t sb)
{
    const int warp = threadIdx.x >> 5, lane = threadIdx.x & 31;
    float* const sm = reinterpret_cast<float*>(__cvta_shared_to_generic(sb + RD_W));
    for (int i = threadIdx.x; i < 2 * C; i += 128) sm[i] = __bfloat162float(q[(blockIdx.x & 14) * C + i]);
    bar_sync(B_SLOW, 128);
#pragma unroll 1
    for (int j = threadIdx.x; j < 2 * C; j += 128) {
        const float* const x = sm + j / C * C;
        float mu = 0.f, var = 0.f, s = 0.f;
#pragma unroll 1
        for (int i = 0; i < C; i++) mu += x[i];
        mu *= 1.f / C;
#pragma unroll 4
        for (int i = 0; i < C; i++) { var = fmaf(x[i] - mu, x[i] - mu, var); s = fmaf(x[i] - mu, __bfloat162float(wq[i * C + j % C]), s); }
        sm[4 * C + j] = s * rsq(var * (1.f / C) + 1e-5f);
    }
    bar_sync(B_SLOW, 128);
#pragma unroll 1
    for (int j = threadIdx.x; j < 2 * C; j += 128) {
        float s = 0.f;
#pragma unroll 4
        for (int i = 0; i < C; i++) s = fmaf(sm[4 * C + j / C * C + i], __bfloat162float(wk[j % C * C + i]), s);
        sm[j] = s * QSCALE;
    }
    bar_sync(B_SLOW, 128);
    float k[2][6], a[2][6], m[2], l[2];
#pragma unroll
    for (int r = 0; r < 2; r++) {
        m[r] = -INFINITY; l[r] = 0.f;
#pragma unroll
        for (int i = 0; i < 6; i++) { k[r][i] = sm[r * C + 64 * (i >> 1) + 2 * lane + (i & 1)]; a[r][i] = 0.f; }
    }
#pragma unroll 1
    for (int par = warp; par < W1 * W1; par += 4) {
        const uint32_t* p0 = reinterpret_cast<const uint32_t*>(f0 + (size_t)((par >> 8) * 2 * W0 + (par & 255) * 2) * (C * 2)) + lane;
        const uint32_t* p1 = reinterpret_cast<const uint32_t*>(f1 + (size_t)par * (C * 2)) + lane;
        uint32_t v[4][3];
#pragma unroll
        for (int i = 0; i < 3; i++)
#pragma unroll
            for (int j = 0; j < 4; j++) v[j][i] = hadd2(__ldg(p0 + ((j >> 1) * W0 + (j & 1)) * (C / 2) + 32 * i), __ldg(p1 + 32 * i));
#pragma unroll
        for (int j = 0; j < 4; j++) {
            float x[6], s1 = 0.f, s2 = 0.f, d[2] = {0.f, 0.f};
#pragma unroll
            for (int i = 0; i < 3; i++) { x[2 * i] = bflo(v[j][i]); x[2 * i + 1] = bfhi(v[j][i]); s1 += x[2 * i] + x[2 * i + 1]; }
#pragma unroll
            for (int o = 1; o < 32; o <<= 1) s1 += __shfl_xor_sync(~0u, s1, o);
#pragma unroll
            for (int i = 0; i < 6; i++) {
                x[i] -= s1 * (1.f / C); s2 = fmaf(x[i], x[i], s2);
#pragma unroll
                for (int r = 0; r < 2; r++) d[r] = fmaf(x[i], k[r][i], d[r]);
            }
#pragma unroll
            for (int o = 1; o < 32; o <<= 1) {
                s2 += __shfl_xor_sync(~0u, s2, o);
#pragma unroll
                for (int r = 0; r < 2; r++) d[r] += __shfl_xor_sync(~0u, d[r], o);
            }
            const float rs = rsq(s2 * (1.f / C) + 1e-5f);
#pragma unroll
            for (int r = 0; r < 2; r++) {
                const float nm = fmaxf(m[r], d[r] * rs), al = ex2(m[r] - nm), p = ex2(d[r] * rs - nm);
                m[r] = nm; l[r] = fmaf(l[r], al, p);
#pragma unroll
                for (int i = 0; i < 6; i++) a[r][i] = fmaf(a[r][i], al, x[i] * (p * rs));
            }
        }
    }
    bar_sync(B_SLOW, 128);
#pragma unroll
    for (int r = 0; r < 2; r++) {
        float* const o = sm + ((r * 4 + warp) * 32 + lane) * 8;
#pragma unroll
        for (int i = 0; i < 6; i++) o[i] = a[r][i];
        o[6] = l[r]; o[7] = m[r];
    }
    bar_sync(B_SLOW, 128);
    if (warp < 2) {
        const int r = warp;
        const float* const o = sm + (r * 128 + lane) * 8;
        float M = o[7], x[7] = {0.f, 0.f, 0.f, 0.f, 0.f, 0.f, 0.f};
#pragma unroll
        for (int w = 1; w < 4; w++) M = fmaxf(M, o[256 * w + 7]);
#pragma unroll
        for (int w = 0; w < 4; w++) {
            const float e = ex2(o[256 * w + 7] - M);
#pragma unroll
            for (int i = 0; i < 7; i++) x[i] = fmaf(o[256 * w + i], e, x[i]);
        }
        const float rl = 1.f / x[6];
        sts128(sb + RD_B2 + brow(8 * (lane >> 4) + 4 * r + (lane & 3)) + ((lane >> 2) & 3) * 16, packh(x[0] * rl, x[1] * rl), packh(x[2] * rl, x[3] * rl), packh(x[4] * rl, x[5] * rl), lane ? 0u : 0x3C00u);
    }
}

template <bool FIRST>
__device__ __forceinline__ void project(const uint32_t ar, const uint32_t br, const bool hi, const float ws0, const float ws1, const float qv0, const float qv1,
                                        __nv_bfloat16* op0, __nv_bfloat16* op1, Scratch* scr)
{
    uint4 wa[3][6], x[4];
#pragma unroll
    for (int i = 0; i < 18; i++) wa[i / 6][i % 6] = lds128v(ar + i * 512);
    if (FIRST) { bar_arrive(B_PLACE, NTHREADS); bar_sync(B_RDY, 192); }
    else bar_sync(B_SLOW, 128);
    if (FIRST && threadIdx.x == 0) TSX(8, 0);
#pragma unroll
    for (int j = 0; j < 4; j++) x[j] = lds128v(br + 16 * j);
    float o[7][4];
#pragma unroll
    for (int j = 0; j < 7; j++) o[j][0] = o[j][1] = o[j][2] = o[j][3] = 0.f;
#pragma unroll
    for (int i = 0; i < 2; i++) {
        mmah(o[6], 0x3C00u, 0x3C00u, 0x3C00u, 0x3C00u, x[2 * i].w, x[2 * i + 1].w);
#pragma unroll
        for (int n = 0; n < 3; n++) mmah(o[2 * n + i], wa[n][2 * i].x, wa[n][2 * i].y, wa[n][2 * i].z, wa[n][2 * i].w, x[2 * i].x, x[2 * i].y);
#pragma unroll
        for (int n = 0; n < 3; n++) mmah(o[2 * n + 1 - i], wa[n][2 * i + 1].x, wa[n][2 * i + 1].y, wa[n][2 * i + 1].z, wa[n][2 * i + 1].w, x[2 * i + 1].x, x[2 * i + 1].y);
#pragma unroll
        for (int n = 0; n < 3; n++) mmah(o[2 * n + i], wa[n][4 + i].x, wa[n][4 + i].y, wa[n][4 + i].z, wa[n][4 + i].w, x[2 * i].z, x[2 * i + 1].z);
    }
    const float L = o[6][0] + o[6][1], r = rcp(L);
    const float y0 = hi ? (o[2][0] + o[2][3]) + (o[3][0] + o[3][3]) : (o[0][0] + o[0][3]) + (o[1][0] + o[1][3]), y1 = (o[4][0] + o[4][3]) + (o[5][0] + o[5][3]);
    const uint32_t y = pack2(fmaf(y0, r * ws0, qv0), fmaf(y1, r * ws1, qv1));
    asm volatile("{.reg .b16 l, h; mov.b32 {l, h}, %2; st.global.b16 [%0], l; st.global.b16 [%1], h;}" ::"l"(op0), "l"(op1), "r"(y) : "memory");
    if (FIRST && threadIdx.x == 0) TSD(11, y);
    if (FIRST)
        asm volatile("{.reg .pred p; .reg .f32 a; abs.f32 a, %1; setp.ge.f32 p, %0, 0f3B000000; setp.le.and.f32 p, %0, 0f45000000, p; setp.lt.and.f32 p, a, 0f7F800000, p;"
                     " vote.sync.all.pred p, p, 0xffffffff; @p exit;}" ::"f"(L), "f"(y0) : "memory");
}

__device__ __forceinline__ void reducer(const char* __restrict__ f0, const char* __restrict__ f1, const __nv_bfloat16* __restrict__ q, const __nv_bfloat16* __restrict__ wq, const __nv_bfloat16* __restrict__ wk,
                                        Scratch* scr, const __nv_bfloat16* __restrict__ wv, const __nv_bfloat16* __restrict__ wo,
                                        __nv_bfloat16* __restrict__ out, const uint32_t sb, const int GS)
{
    const int warp = threadIdx.x >> 5, lane = threadIdx.x & 31, b = blockIdx.x;
    const int g = lane >> 2, t = lane & 3;
    char* const ap = reinterpret_cast<char*>(g_acc);
    if (threadIdx.x == 256) TS(0);
    if (b < NSRC && warp < 8) {
        const uint32_t wqs = sb + RD_W, wbar = sb + RD_BAR;
        const int hr = lane >> 4, qt = (lane >> 2) & 3, sub = lane & 3;
        const uint32_t* qp = reinterpret_cast<const uint32_t*>(q + (warp + 8 * hr) * C + 48 * qt + 6 * sub);
        uint32_t qw[6];
#pragma unroll
        for (int j = 0; j < 3; j++) { qw[j] = __ldg(qp + j); qw[3 + j] = __ldg(qp + 12 + j); }
        if (lane == 0) { mbar_init(wbar + warp * 8, 1); asm volatile("fence.mbarrier_init.release.cluster;" ::: "memory"); mbar_expect(wbar + warp * 8, 9216);
            asm volatile("cp.async.bulk.shared::cluster.global.mbarrier::complete_tx::bytes [%0], [%1], 9216, [%2];"
                         ::"r"(wqs + warp * 9232), "l"(wq + 24 * warp * C), "r"(wbar + warp * 8) : "memory");
        }
        __syncwarp();
        if (threadIdx.x == 0) TSP(2, 0);
        float e[12];
#pragma unroll
        for (int j = 0; j < 6; j++) { e[2 * j] = bflo(qw[j]); e[2 * j + 1] = bfhi(qw[j]); }
        float sm = ((e[0] + e[1]) + (e[2] + e[3])) + ((e[4] + e[5]) + (e[6] + e[7])) + ((e[8] + e[9]) + (e[10] + e[11]));
#pragma unroll
        for (int o = 1; o < 16; o <<= 1) sm += __shfl_xor_sync(~0u, sm, o);
        if (threadIdx.x == 0) TSP(5, u(sm));
        float v0 = 0.f, v1 = 0.f;
#pragma unroll
        for (int j = 0; j < 12; j++) e[j] -= sm * (1.f / C);
#pragma unroll
        for (int j = 0; j < 6; j++) { v0 = fmaf(e[j], e[j], v0); v1 = fmaf(e[6 + j], e[6 + j], v1); }
        v0 += v1;
#pragma unroll
        for (int o = 1; o < 16; o <<= 1) v0 += __shfl_xor_sync(~0u, v0, o);
        const float rq = rsq(v0 * (1.f / C) + 1e-5f);
#pragma unroll
        for (int j = 0; j < 6; j++)
            sts32(sb + RD_QN + (3 * sub + (j >> 1)) * 512 + (4 * warp + qt) * 16 + (2 * (j & 1) + hr) * 4, pack2(e[j] * rq, e[6 + j] * rq));
        if (threadIdx.x == 0) TSP(8, 0);
        uint32_t wkf[2][3];
#pragma unroll
        for (int i = 0; i < 2; i++)
#pragma unroll
            for (int j = 0; j < 3; j++) wkf[i][j] = __ldg(reinterpret_cast<const uint32_t*>(wk + (16 * b + 8 * i + g) * C + 24 * warp + 8 * j + 2 * t));
        bar_sync(B_QN, 256);
        float acc[2][3][4];
#pragma unroll
        for (int i = 0; i < 3; i++)
#pragma unroll
            for (int e = 0; e < 4; e++) acc[0][i][e] = acc[1][i][e] = 0.f;
        const uint32_t ba = wqs + (lane & 7) * 9232 + (lane >> 3) * 384 + 48 * warp;
        uint4 a[12];
#pragma unroll
        for (int kk = 0; kk < 12; kk++) a[kk] = lds128(sb + RD_QN + kk * 512 + lane * 16);
        mbar_wait(wbar + (lane & 7) * 8, 0);
        __syncwarp();
        if (threadIdx.x == 0) TSP(4, 0);
#pragma unroll
        for (int kp = 0; kp < 6; kp++)
#pragma unroll
            for (int i = 0; i < 3; i++) {
                uint32_t bb[4];
                ldsm4t(bb, ba + kp * 1536 + i * 16);
                mma(acc[0][i], a[2 * kp].x, a[2 * kp].y, a[2 * kp].z, a[2 * kp].w, bb[0], bb[1]);
                mma(acc[1][i], a[2 * kp + 1].x, a[2 * kp + 1].y, a[2 * kp + 1].z, a[2 * kp + 1].w, bb[2], bb[3]);
            }
        if (threadIdx.x == 0) TSP(7, u(acc[1][2][3]));
        float kq[2][4] = {{0.f, 0.f, 0.f, 0.f}, {0.f, 0.f, 0.f, 0.f}};
#pragma unroll
        for (int j = 0; j < 3; j++) {
            const uint32_t a0 = pack2(acc[0][j][0] + acc[1][j][0], acc[0][j][1] + acc[1][j][1]), a1 = pack2(acc[0][j][2] + acc[1][j][2], acc[0][j][3] + acc[1][j][3]);
            mma8(kq[0], a0, a1, wkf[0][j]);
            mma8(kq[1], a0, a1, wkf[1][j]);
        }
        if (warp < 7) {
            sts128(sb + RD_KQ + warp * 1024 + lane * 16, u(kq[0][0]), u(kq[0][1]), u(kq[0][2]), u(kq[0][3]));
            sts128(sb + RD_KQ + warp * 1024 + 512 + lane * 16, u(kq[1][0]), u(kq[1][1]), u(kq[1][2]), u(kq[1][3]));
            bar_arrive(B_Q, 256);
        } else {
            bar_sync(B_Q, 256);
#pragma unroll
            for (int w = 0; w < 7; w++)
#pragma unroll
                for (int i = 0; i < 2; i++) {
                    const uint4 o = lds128(sb + RD_KQ + w * 1024 + i * 512 + lane * 16);
                    kq[i][0] += f(o.x); kq[i][1] += f(o.y); kq[i][2] += f(o.z); kq[i][3] += f(o.w);
                }
            stg_relaxed(g_qk + b * 32 + lane, ~pack2(kq[0][0] * QSCALE, kq[0][1] * QSCALE), ~pack2(kq[0][2] * QSCALE, kq[0][3] * QSCALE),
                        ~pack2(kq[1][0] * QSCALE, kq[1][1] * QSCALE), ~pack2(kq[1][2] * QSCALE, kq[1][3] * QSCALE));
            if (lane == 0) TS(10);
        }
    } else if (warp == 8 && !(b & 1)) {
        char* const pp = ap + (b >> 2) * 8192 + (b & 2) * 512;
        if (lane < 16) stg_relaxed(reinterpret_cast<uint4*>(pp + (lane >> 3) * 4096) + (lane & 7), 0, 0, 0, 0);
        __syncwarp();
        uint32_t place = 0;
        if (lane == 0) {
            uint32_t best[2] = {~0u, ~0u};
#pragma unroll 1
            for (int it = 0; it < NPROBE; it++) {
#pragma unroll
                for (int i = 0; i < 2; i++) {
                    uint32_t c;
                    asm volatile("{.reg .b32 v, c0; .reg .pred p; mov.u32 c0, %%clock; atom.relaxed.gpu.global.exch.b32 v, [%1], 0; setp.ne.u32 p, v, 0; @p trap;"
                                 " mov.u32 %0, %%clock; sub.u32 %0, %0, c0;}" : "=r"(c) : "l"(pp + i * 4096) : "memory");
                    best[i] = min(best[i], c);
                }
            }
            place = acc_place((best[1] < best[0]) ^ ((b >> 2) & 1), b >> 1);
            sts32(sb + RD_PLACE, place);
        }
        place = __shfl_sync(~0u, place, 0);
#pragma unroll
        for (int i = 0; i < 2; i++) stg_relaxed(reinterpret_cast<uint4*>(ap + (acc_line(4 * i + (lane >> 3)) ^ place)) + (lane & 7), 0, 0, 0, 0);
        __threadfence();
    } else if (b >= NSRC) {
        if (b == NSRC && warp == 0) stg_relaxed32(g_mmax + lane, 0);
        __nanosleep(2500);
    }
    bar_sync(B_ALL, NTHREADS);

#pragma unroll 1
    for (int r = 0; r < 3; r++) {
        uint4 v[8];
#pragma unroll
        for (int k = 0; k < 8; k++) {
            const int idx = (8 * r + k) * 384 + threadIdx.x;
            v[k] = __ldg(reinterpret_cast<const uint4*>(idx < 4608 ? wv : wo - C * C) + idx);
        }
#pragma unroll
        for (int k = 0; k < 8; k++) {
            const int idx = (8 * r + k) * 384 + threadIdx.x, row = idx / 24;
            sts128(sb + RD_W + row * WROW + (idx - 24 * row) * 16, v[k].x, v[k].y, v[k].z, v[k].w);
        }
    }
    bar_sync(B_ALL, NTHREADS);
    if (warp < 6) {
        const int col = 96 * (b & 1) + 16 * warp;
        float d[24][4];
#pragma unroll
        for (int i = 0; i < 24; i++) d[i][0] = d[i][1] = d[i][2] = d[i][3] = 0.f;
        const int mi = lane >> 3, r = lane & 7;
        const uint32_t aa = sb + RD_W + (C + (mi >> 1) * 8 + r) * WROW + (col + (mi & 1) * 8) * 2;
        const uint32_t ba = sb + RD_W + ((mi >> 1) * 8 + r) * WROW + (mi & 1) * 16;
#pragma unroll 1
        for (int kk = 0; kk < 12; kk++) {
            uint32_t a[4];
            ldsm4t(a, aa + kk * 16 * WROW);
#pragma unroll
            for (int i = 0; i < 12; i++) {
                uint32_t bb[4];
                ldsm4(bb, ba + i * 16 * WROW + kk * 32);
                mma(d[2 * i], a[0], a[1], a[2], a[3], bb[0], bb[1]);
                mma(d[2 * i + 1], a[0], a[1], a[2], a[3], bb[2], bb[3]);
            }
        }
        float c0 = 0.f, c1 = 0.f, m0 = 0.f, m1 = 0.f;
#pragma unroll
        for (int i = 0; i < 24; i++) { c0 += d[i][0] + d[i][1]; c1 += d[i][2] + d[i][3]; }
        c0 += __shfl_xor_sync(~0u, c0, 1); c1 += __shfl_xor_sync(~0u, c1, 1);
        c0 += __shfl_xor_sync(~0u, c0, 2); c1 += __shfl_xor_sync(~0u, c1, 2);
        c0 *= 1.f / C; c1 *= 1.f / C;
#pragma unroll
        for (int i = 0; i < 24; i++) {
            d[i][0] -= c0; d[i][1] -= c0; d[i][2] -= c1; d[i][3] -= c1;
            m0 = fmaxf(m0, fmaxf(fabsf(d[i][0]), fabsf(d[i][1]))); m1 = fmaxf(m1, fmaxf(fabsf(d[i][2]), fabsf(d[i][3])));
        }
        m0 = fmaxf(m0, __shfl_xor_sync(~0u, m0, 1)); m1 = fmaxf(m1, __shfl_xor_sync(~0u, m1, 1));
        m0 = fmaxf(m0, __shfl_xor_sync(~0u, m0, 2)); m1 = fmaxf(m1, __shfl_xor_sync(~0u, m1, 2));
        const uint32_t e0 = min(max(u(m0) >> 23, 12u), 254u), e1 = min(max(u(m1) >> 23, 12u), 254u);
        const float s0 = f((265u - e0) << 23), s1 = f((265u - e1) << 23);
        const bool k0 = fabsf(c0) < INFINITY, k1 = fabsf(c1) < INFINITY;
#pragma unroll
        for (int j = 0; j < 6; j++) {
            const int n[4] = {j < 4 ? j : 8 + 2 * j, j < 4 ? 4 + j : 12 + 2 * j, j < 4 ? 8 + j : 9 + 2 * j, j < 4 ? 12 + j : 13 + 2 * j};
            uint32_t a[2][4];
#pragma unroll
            for (int e = 0; e < 4; e++) {
                a[0][e] = k0 ? packh(d[n[e]][0] * s0, d[n[e]][1] * s0) : 0u;
                a[1][e] = k1 ? packh(d[n[e]][2] * s1, d[n[e]][3] * s1) : 0u;
            }
#pragma unroll
            for (int e = 0; e < 2; e++) sts128(sb + RD_A + ((2 * warp + e) * 6 + j) * 512 + lane * 16, a[e][0], a[e][1], a[e][2], a[e][3]);
        }
        sts32(sb + RD_WS + 2 * warp * 128 + lane * 4, k0 ? (e0 - 11u) << 23 : u(c0));
        sts32(sb + RD_WS + (2 * warp + 1) * 128 + lane * 4, k1 ? (e1 - 11u) << 23 : u(c1));
        if (warp < 4) bar_sync(B_PARK, 192); else bar_arrive(B_PARK, 192);
        if (threadIdx.x == 0) TSE(6);
    }
    if (warp >= 4) {
        if (threadIdx.x == 128) {
            uint32_t m, place = lds32(sb + RD_PLACE);
            for (int it = 0;; it++) {
                const int left = NT - 2 * NST * GS - (int)ldg_relaxed32(g_ctr);
                m = ldg_relaxed32(g_mmax + b);
                if (left <= REFT && m) break;
                if (left <= 0) { m = 0x80000000u; break; }
                if (it > SPIN_LIMIT) __trap();
                __nanosleep(300);
            }
            if (b & 1) for (int it = 0;; it++) {
                uint32_t r;
                asm volatile("ld.acquire.gpu.global.u32 %0, [%1];" : "=r"(r) : "l"(g_mref + b - 1) : "memory");
                place = ~r & PLACE;
                if (r) break;
                if (it > SPIN_LIMIT) __trap();
            }
            asm volatile("st.release.gpu.global.u32 [%0], %1;" ::"l"(g_mref + b), "r"(~((u(f(m >> 31 ? m ^ 0x80000000u : ~m) + 8.f) & ~PLACE) | place)) : "memory");
            sts32(sb + RD_PLACE, place);
            TSE(7);
        }
        __syncwarp();
        if (warp == 4) {
            uint4* p0 = g_qk + min(b, NSRC - 1) * 32 + lane;
            unsigned* p1 = lane == 1 && b == NSRC ? g_ctr : g_mref + b;
            asm volatile("" : "+l"(p0), "+l"(p1));
            bar_arrive(B_PLACE, NTHREADS);
            bar_sync(B_RDY, 192);
            *p0 = make_uint4(0, 0, 0, 0);
            *p1 = 0;
            return;
        }
        bar_sync(B_PLACE, NTHREADS);
        if (warp >= 5 + NPW) return;
        const uint32_t place = lds32(sb + RD_PLACE);
        const uint4* const pa = reinterpret_cast<const uint4*>(ap + (acc_line(lane >> 3) ^ place)) + (lane & 7);
        const uint32_t bw = opaque(sb + brow(lane & 7) + (lane >> 3) * 16);
        const uint32_t n0 = packh(0.f, (float)GS), nstart = packh(0.f, (float)POLLN);
        for (int it = 0; ldg_relaxed32(ap + place + 12) < nstart; it++)
            if (it > SPIN_LIMIT) __trap();
        for (const unsigned c = clock32(); clock32() - c < (warp - 5) * PGAP;) {}
        for (int it = 0;; it++) {
            const uint4 a0 = ldg_relaxed(pa), b0 = ldg_relaxed(pa + 1024);
            if (it > SPIN_LIMIT) __trap();
            bar_sync(B_WARP, 32);
            asm volatile("{.reg .pred p, q; .reg .b32 a; setp.ge.u32 p, %5, %10; setp.ge.and.u32 p, %9, %10, p; vote.sync.all.pred q, p, 0xffffffff; selp.b32 a, %0, %1, p;"
                         " st.shared.v4.b32 [a], {%2,%3,%4,%5}; st.shared.v4.b32 [a + 704], {%6,%7,%8,%9}; @q bar.arrive 15, 192; @q exit;}"
                         ::"r"(bw), "r"(bw - (RD_B - RD_QN)), "r"(a0.x), "r"(a0.y), "r"(a0.z), "r"(a0.w), "r"(b0.x), "r"(b0.y), "r"(b0.z), "r"(b0.w), "r"(n0) : "memory");
        }
    }
    const uint32_t br = opaque(sb + brow(8 * (g & 1) + 2 * (g & 2) + t));
    const bool hi = t >= 2;
    const int oi = ((b & 14) + (t & 1)) * C + 96 * (b & 1) + 24 * warp + g;
    const float qv0 = __bfloat162float(q[oi + 4 * (t & 2)]), qv1 = __bfloat162float(q[oi + 16]);
    const float ws0 = f(lds32(sb + RD_WS + (3 * warp + (t >> 1)) * 128 + lane * 4)), ws1 = f(lds32(sb + RD_WS + (3 * warp + 2) * 128 + lane * 4));
    __nv_bfloat16* op0 = out + oi + 4 * (t & 2), * op1 = out + oi + 16;
    asm volatile("" : "+l"(op0), "+l"(op1));
    const uint32_t ar = sb + RD_A + warp * 18 * 512 + lane * 16;
    project<true>(ar, br, hi, ws0, ws1, qv0, qv1, op0, op1, scr);
    slow_rows(f0, f1, q, wq, wk, sb);
    project<false>(ar, br + RD_B2, hi, ws0, ws1, qv0, qv1, op0, op1, scr);
}

__global__ void __launch_bounds__(NTHREADS, 1)
attn_main(const char* __restrict__ f0, const char* __restrict__ f1,
          const __nv_bfloat16* __restrict__ q, const __nv_bfloat16* __restrict__ wq, const __nv_bfloat16* __restrict__ wk, Scratch* scr,
          const __nv_bfloat16* __restrict__ wv, const __nv_bfloat16* __restrict__ wo, __nv_bfloat16* __restrict__ out,
          const __grid_constant__ CUtensorMap m0, const __grid_constant__ CUtensorMap m1)
{
    extern __shared__ char smem_raw[];
    const uint32_t sb = (s2u(smem_raw) + 1023u) & ~1023u;
    const int G = gridDim.x - NRD;
    const int b = blockIdx.x - NRD;
    if (threadIdx.x == 0 && b >= 0) {
        const char* a = f0 + (uint32_t)(b * (4 * TP * C * 2) + (b >> 4) * (W0 * C * 2));
        prefetch_l2(a, 4 * TP * C * 2);
        prefetch_l2(a + W0 * C * 2, 4 * TP * C * 2);
        prefetch_l2(f1 + b * (2 * TP * C * 2), 2 * TP * C * 2);
        prefetch_l2((const char*)(b % (2 * WSL) < WSL ? wq : wk) + b % WSL * (C * C * 2 / WSL), C * C * 2 / WSL);
    }
    if (b < 0) { reducer(f0, f1, q, wq, wk, scr, wv, wo, out, sb, G); return; }
    const int warp = __shfl_sync(~0u, threadIdx.x >> 5, 0), lane = threadIdx.x & 31;
    const int g = lane >> 2, t = lane & 3;

    if (warp >= 8) {
        if (warp < 10) {
            const int p = warp - 8;
            const unsigned c0 = clock32();
            const uint32_t sbp = opaque(sb), bar = sbp + SM_BAR + p * 8;
            uint64_t pol; asm volatile("createpolicy.fractional.L2::evict_first.b64 %0, 1.0;" : "=l"(pol));
            if (elect()) {
                if (p == 0) TS(0);
                asm volatile("prefetch.tensormap [%0];" ::"l"(p ? &m1 : &m0) : "memory");
#pragma unroll
                for (int n = 0; n < NI; n++) mbar_init(bar + n * 16, 2);
                asm volatile("fence.mbarrier_init.release.cluster;" ::: "memory");
#pragma unroll
                for (int n = 0; n < NI; n++) {
                    issue_tile(&m0, &m1, sbp, p + 2 * n, 2 * b + p + 2 * n * G, pol);
                    TR(0, 2 * n + p);
                    sts32(sbp + SM_FLAG + (p + 2 * n) * 4, 0);
                    mbar_arrive(bar + n * 16);
                }
#pragma unroll
                for (int n = 0; n < NS / 2; n++) {
                    if (n >= NI) mbar_init(bar + n * 16, 2);
                    mbar_init(bar + NS * 8 + n * 16, 1);
                }
                if (p == 0) mbar_init(sbp + SM_REF, 1);
                asm volatile("fence.mbarrier_init.release.cluster;" ::: "memory");
            }
            __syncwarp();
            bar_arrive(B_QK, NTHREADS);
            if (elect()) {
                int tl = 2 * b + p + 2 * NI * G;
                int s = p + 2 * NI; uint32_t ph = 1;
                int sa = p, na = 0; uint32_t pa = 0;
                bool late = false;
                for (int n = NI;; n++) {
                    const int d = n < NRAMP ? D0 : (tl >= NT - (TA) ? 1 : D1);
                    while (n - na >= d) {
                        mbar_wait(sbp + SM_BAR + sa * 8, pa);
                        if (na < NS / 2) TR(1, 2 * na + p);
                        na++; sa += 2;
                        if (sa >= NS) { sa -= NS; pa ^= 1; }
                    }
                    mbar_wait(sbp + SM_BAR + (NS + s) * 8, ph);
                    if (n < NPACE) while (clock32() - c0 < (n ? T1 + (2 * (n - 1) + p) * TG : T0)) {}
                    issue_tile(&m0, &m1, sbp, s, tl, pol);
                    TR(0, 2 * n + p);
                    int nxt = tl + 2 * G;
                    if (n >= NST - 1) nxt = grab_tile(g_ctr) + 2 * NST * G;
                    const bool last = nxt >= NT;
                    uint32_t flag = last;
                    if (!late && nxt >= NT - MAXT - 16 * b) { late = true; flag |= 2; }
                    if (last) mbar_wait(sbp + SM_REF, 0);
                    sts32(sbp + SM_FLAG + s * 4, flag);
                    mbar_arrive(sbp + SM_BAR + s * 8);
                    if (last) break;
                    s += 2;
                    if (s >= NS) { s -= NS; ph ^= 1; }
                    tl = nxt;
                }
                if (p) TSE(5);
            }
            return;
        }
        const int h = threadIdx.x - 320;
        uint4 v[6];
        for (int it = 0;; it++) {
            bool miss = false;
#pragma unroll
            for (int k = 0; k < 6; k++) v[k] = ldg_relaxed(g_qk + k * 64 + h);
#pragma unroll
            for (int k = 0; k < 6; k++) miss |= has(v[k], 0);
            if (!miss) break;
            if (it > SPIN_LIMIT) __trap();
            if (it == 0) __nanosleep(QSLEEP);
        }
#pragma unroll
        for (int k = 0; k < 6; k++) sts128(sb + SM_QK + (k * 64 + h) * 16, ~v[k].x, ~v[k].y, ~v[k].z, ~v[k].w);
        __syncwarp();
        bar_sync(B_QK, NTHREADS);
        if (warp == 11) return;
        uint32_t r = 1;
        for (int it = 0;; it++) {
            __nanosleep(500);
            if (lane < NQ) asm volatile("ld.acquire.gpu.global.u32 %0, [%1];" : "=r"(r) : "l"(g_mref + lane) : "memory");
            if (__all_sync(~0u, r != 0)) break;
            if (it > SPIN_LIMIT) __trap();
        }
        if (lane < NQ) sts32(sb + SM_M + lane * 4, ~r);
        __syncwarp();
        if (lane == 0) { mbar_arrive(sb + SM_REF); TSE(7); }
        return;
    }

    const int grp = warp >> 2, cw = warp & 3;
    const int xp = lane & 7, mi = lane >> 3;
    const uint32_t offS1 = opaque(12288 + xp * 128 + ((mi ^ xp) << 4)), offS1x = opaque(offS1 ^ 64);
    const uint32_t offS0 = opaque(offS1 - 12288 + cw * 3072), offS0x = opaque(offS0 ^ 64);
    const uint32_t offT = opaque(mi * 3072 + xp * 128 + (((cw + 4 * grp) ^ xp) << 4)), offTx = opaque(offT ^ 64);
    const uint32_t offU = opaque(12288 + (mi % 3) * 1024 + xp * 128 + (((cw + 4 * (grp ^ (mi / 3))) ^ xp) << 4));
    const uint32_t offV = opaque(12288 + (1 + (mi & 1)) * 1024 + xp * 128 + (((cw + 4 * (grp ^ 1)) ^ xp) << 4));
    const int shl = opaque(9 * t), shl4 = opaque(9 * t + 4);
    const uint32_t pw = opaque((cw >> 1) * 512 + lane * 16 + (cw & 1) * 8), muw = opaque(1024 + t * 16 + cw * 4);
    const uint32_t prd = opaque(lane * 16), mur = opaque(1024 + t * 16), mof = g * 4;
    uint32_t pb0 = sb + SM_P + grp * 2 * PBUF;
    const uint32_t pbx = pb0 ^ (pb0 + PBUF);
    const bool odd = g & 1;
    const int barid = B_GRP + grp;
    const bool elected = cw == 3 && lane == 0;

    uint32_t qa[48];
    float r_lo, r_hi;
    bar_sync(B_QK, NTHREADS);
    {
        float rr[2][4] = {{0.f, 0.f, 0.f, 0.f}, {0.f, 0.f, 0.f, 0.f}};
#pragma unroll
        for (int kk = 0; kk < 12; kk++) {
            const uint4 v = lds128(sb + SM_QK + kk * 512 + lane * 16);
            qa[4 * kk] = v.x; qa[4 * kk + 1] = v.y; qa[4 * kk + 2] = v.z; qa[4 * kk + 3] = v.w;
            mma(rr[kk & 1], v.x, v.y, v.z, v.w, ONES, ONES);
        }
        r_lo = rr[0][0] + rr[1][0]; r_hi = rr[0][2] + rr[1][2];
    }
    if (threadIdx.x == 0) TS(1);

    float acc[6][4];
#pragma unroll
    for (int i = 0; i < 6; i++) acc[i][0] = acc[i][1] = acc[i][2] = acc[i][3] = 0.f;
    float m_lo = -INFINITY, m_hi = -INFINITY, l_lo = 0.f, l_hi = 0.f;
    float cm[4] = {0.f, 0.f, 0.f, 0.f};
    uint32_t xt[6][4], yt[6]; uint4 pa, pb, mv;
    const uint32_t dof = opaque(acc_line(warp) + (lane & 7) * 16);
    const uint32_t xof = 512 - lane * 8;
    uint32_t ref_lo = 0, ref_hi = 0;
    const uint32_t mad = sb + SM_M + mof;
    uint32_t st = sb + SM_STAGES + grp * STAGE;
    int s = grp; uint32_t ph = 0;
    while (true) {
        mbar_wait(sb + SM_BAR + s * 8, ph);
        PH(0, 0);
        const uint32_t stop = lds32(sb + SM_FLAG + s * 4);
        float sc[2][4], gr[4][4], sx[4];
#pragma unroll
        for (int e = 0; e < 4; e++) sc[0][e] = sc[1][e] = gr[0][e] = gr[1][e] = gr[2][e] = gr[3][e] = sx[e] = 0.f;
#pragma unroll
        for (int qq = 0; qq < 6; qq++) {
            uint32_t x[4], y[4];
            ldsm4(x, st + (qq & 1 ? offS0x : offS0) + (qq >> 1) * 1024);
            ldsm4(y, st + (qq & 1 ? offS1x : offS1) + (qq >> 1) * 1024);
#pragma unroll
            for (int e = 0; e < 4; e++) x[e] = hadd2(x[e], y[e]);
            mma8(gr[0], x[0], x[1], x[0]);
            mma8(gr[1], x[0], x[1], x[1]);
            mma(sx, x[0], x[1], x[2], x[3], ONES, ONES);
            mma8(gr[GR4 ? 2 : 0], x[2], x[3], x[2]);
            mma8(gr[GR4 ? 3 : 1], x[2], x[3], x[3]);
            mma(sc[0], qa[8 * qq], qa[8 * qq + 1], qa[8 * qq + 2], qa[8 * qq + 3], x[0], x[1]);
            mma(sc[1], qa[8 * qq + 4], qa[8 * qq + 5], qa[8 * qq + 6], qa[8 * qq + 7], x[2], x[3]);
        }
        ldsm4t(yt, st + offU);
        ldsm2t(yt + 4, st + offV);
#pragma unroll
        for (int i = 0; i < 6; i++) ldsm4t(xt[i], st + (i < 3 ? offT : offTx) + (i % 3) * 1024);

        const float mu = (sx[0] + sx[2]) * (1.f / C), ss = GR4 ? (odd ? (gr[0][1] + gr[1][3]) + (gr[2][1] + gr[3][3]) : (gr[0][0] + gr[1][2]) + (gr[2][0] + gr[3][2])) : (odd ? gr[0][1] + gr[1][3] : gr[0][0] + gr[1][2]);
        const float rs = rsq(fmaxf(fmaf(-mu, mu, fmaf(ss, 1.f / C, 1e-5f)), 1e-5f));
        const float mu0 = __shfl_sync(~0u, mu, shl), mu1 = __shfl_sync(~0u, mu, shl4);
        const float rs0 = __shfl_sync(~0u, rs, shl), rs1 = __shfl_sync(~0u, rs, shl4);
        const float u0 = fmaf(-mu0, r_lo, sc[0][0] + sc[1][0]), u1 = fmaf(-mu1, r_lo, sc[0][1] + sc[1][1]);
        const float u2 = fmaf(-mu0, r_hi, sc[0][2] + sc[1][2]), u3 = fmaf(-mu1, r_hi, sc[0][3] + sc[1][3]);
        const float d0 = fmaf(u0, rs0, -m_lo), d1 = fmaf(u1, rs1, -m_lo), d2 = fmaf(u2, rs0, -m_hi), d3 = fmaf(u3, rs1, -m_hi);
        PH(1, u(d0 + d2));
        float p0 = ex2(d0), p1 = ex2(d1), p2 = ex2(d2), p3 = ex2(d3);
        sts64(pb0 + pw, pack2(p0 * rs0, p1 * rs1), pack2(p2 * rs0, p3 * rs1));
        if (lane < 4) sts32(pb0 + muw, pack2(mu0, mu1));
        asm volatile("{.reg .pred p; setp.ne.u32 p, %2, 0; @p ld.shared.b32 %0, [%3]; @p ld.shared.b32 %1, [%3+32];}" : "+r"(ref_lo), "+r"(ref_hi) : "r"(stop & 1), "r"(mad) : "memory");
        const bool over = bar_any(barid, 128, fmaxf(fmaxf(d0, d1), fmaxf(d2, d3)) > LAZY);
        PH(3, 0);
        pa = lds128(pb0 + prd); pb = lds128(pb0 + prd + 512); mv = lds128(pb0 + mur);
        if (stop & 1) { l_lo += p0 + p1; l_hi += p2 + p3; break; }
        if (elected) mbar_arrive(sb + SM_BAR + (NS + s) * 8);
        if (__builtin_expect(over, 0)) {
            const float s0 = u0 * rs0, s1 = u1 * rs1, s2 = u2 * rs0, s3 = u3 * rs1;
            float xl = fmaxf(s0, s1), xh = fmaxf(s2, s3);
            xl = fmaxf(xl, __shfl_xor_sync(~0u, xl, 1)); xh = fmaxf(xh, __shfl_xor_sync(~0u, xh, 1));
            xl = fmaxf(xl, __shfl_xor_sync(~0u, xl, 2)); xh = fmaxf(xh, __shfl_xor_sync(~0u, xh, 2));
            if (t < 2) sts32(sb + SM_MX + grp * 256 + ((g + 8 * t) * 4 + cw) * 4, u(t ? xh : xl));
            bar_sync(B_MAX + grp, 128);
            const uint4 ml4 = lds128(sb + SM_MX + grp * 256 + g * 16), mh4 = lds128(sb + SM_MX + grp * 256 + g * 16 + 128);
            const float nl = fmaxf(fmaxf(fmaxf(f(ml4.x), f(ml4.y)), fmaxf(f(ml4.z), f(ml4.w))), m_lo);
            const float nh = fmaxf(fmaxf(fmaxf(f(mh4.x), f(mh4.y)), fmaxf(f(mh4.z), f(mh4.w))), m_hi);
            p0 = ex2(s0 - nl); p1 = ex2(s1 - nl); p2 = ex2(s2 - nh); p3 = ex2(s3 - nh);
            sts64(pb0 + pw, pack2(p0 * rs0, p1 * rs1), pack2(p2 * rs0, p3 * rs1));
            const float al = ex2(m_lo - nl), ah = ex2(m_hi - nh);
            m_lo = nl; m_hi = nh;
            l_lo *= al; l_hi *= ah; cm[0] *= al; cm[2] *= ah;
#pragma unroll
            for (int i = 0; i < 6; i++) { acc[i][0] *= al; acc[i][1] *= al; acc[i][2] *= ah; acc[i][3] *= ah; }
            bar_sync(B_MAX + grp, 128);
            pa = lds128(pb0 + prd); pb = lds128(pb0 + prd + 512);
        }
        l_lo += p0 + p1; l_hi += p2 + p3;
#pragma unroll
        for (int i = 0; i < 6; i++) mma(acc[i], pa.x, pa.y, pa.z, pa.w, hadd2v(xt[i][0], yt[i]), hadd2v(xt[i][1], yt[i]));
        mma(cm, pa.x, pa.y, pa.z, pa.w, mv.x, mv.y);
#pragma unroll
        for (int i = 0; i < 6; i++) mma(acc[i], pb.x, pb.y, pb.z, pb.w, hadd2v(xt[i][2], yt[i]), hadd2v(xt[i][3], yt[i]));
        mma(cm, pb.x, pb.y, pb.z, pb.w, mv.z, mv.w);
        PH(4, u(acc[5][0]));
        if (stop) {
            float a = l_lo + __shfl_xor_sync(~0u, l_lo, 1), c = l_hi + __shfl_xor_sync(~0u, l_hi, 1);
            a += __shfl_xor_sync(~0u, a, 2); c += __shfl_xor_sync(~0u, c, 2);
            const uint32_t m = u((t ? m_hi : m_lo) + lg2(fmaxf(t ? c : a, 1.f)));
            if (t < 2) asm volatile("red.relaxed.gpu.global.max.u32 [%0], %1;" ::"l"(g_mmax + g + 8 * t), "r"(m >> 31 ? ~m : m | 0x80000000u) : "memory");
        }
        pb0 ^= pbx;
        s += 2;
        st += 2 * STAGE;
        if (s >= NS) { s -= NS; ph ^= 1; st -= NS * STAGE; }
        asm volatile("" : "+r"(st));
    }
    const float al = ex2(m_lo - f(ref_lo)), ah = ex2(m_hi - f(ref_hi));
    mma(cm, pa.x, pa.y, pa.z, pa.w, mv.x, mv.y);
#pragma unroll
    for (int i = 3; i < 6; i++) mma(acc[i], pa.x, pa.y, pa.z, pa.w, hadd2v(xt[i][0], yt[i]), hadd2v(xt[i][1], yt[i]));
    mma(cm, pb.x, pb.y, pb.z, pb.w, mv.z, mv.w);
#pragma unroll
    for (int i = 3; i < 6; i++) mma(acc[i], pb.x, pb.y, pb.z, pb.w, hadd2v(xt[i][2], yt[i]), hadd2v(xt[i][3], yt[i]));
#pragma unroll
    for (int i = 0; i < 3; i++) mma(acc[i], pa.x, pa.y, pa.z, pa.w, hadd2v(xt[i][0], yt[i]), hadd2v(xt[i][1], yt[i]));
#pragma unroll
    for (int i = 0; i < 3; i++) mma(acc[i], pb.x, pb.y, pb.z, pb.w, hadd2v(xt[i][2], yt[i]), hadd2v(xt[i][3], yt[i]));
    if (threadIdx.x == grp * 128) TSE(2 + grp);
    if (threadIdx.x == grp * 128 + 96) TSX(2 + grp, u(acc[5][0]));

    uint4* const dst = reinterpret_cast<uint4*>(reinterpret_cast<char*>(g_acc) + (dof ^ (ref_lo & PLACE)));
    uint4* const dsu = reinterpret_cast<uint4*>(reinterpret_cast<char*>(g_acc) + (dof ^ (ref_hi & PLACE)));
    const uint32_t xw = sb + SM_STAGES + grp * STAGE + cw * 768 + prd, xr = sb + SM_STAGES + (grp ^ 1) * STAGE + cw * 768 + prd;
    const float cl = -cm[0] * al, ch = -cm[2] * ah;
    uint32_t hl[6], hh[6];
#pragma unroll
    for (int i = 3; i < 6; i++) { hl[i] = packh(fmaf(acc[i][0], al, cl), fmaf(acc[i][1], al, cl)); hh[i] = packh(fmaf(acc[i][2], ah, ch), fmaf(acc[i][3], ah, ch)); }
    sts128(xw, hl[3], hl[4], hl[5], hh[3]);
    sts64(xw + xof, hh[4], hh[5]);
#pragma unroll
    for (int i = 0; i < 3; i++) { hl[i] = packh(fmaf(acc[i][0], al, cl), fmaf(acc[i][1], al, cl)); hh[i] = packh(fmaf(acc[i][2], ah, ch), fmaf(acc[i][3], ah, ch)); }
    const uint32_t w_lo = packh(l_lo * al, 1.f), w_hi = packh(l_hi * ah, 1.f);
    bar_sync(B_MERGE, 256);
    if (threadIdx.x == 224) TSX(4, 0);
    const uint4 o = lds128(xr);
    const uint2 o2 = lds64(xr + xof);
    red8h(dst, haddh(hl[0], o.x), haddh(hl[1], o.y), haddh(hl[2], o.z), w_lo);
    red8h(dsu, haddh(hh[0], o.w), haddh(hh[1], o2.x), haddh(hh[2], o2.y), w_hi);
    if (threadIdx.x == 0) TSE(4);
    if (threadIdx.x == 224) TSX(9, 0);
}

__global__ void dbgk(Scratch* scr) {
    unsigned s; asm volatile("mov.u32 %0, %%smid;" : "=r"(s));
    if (s != 130) return;
    for (int i = 0; i < 8; i++) {
        unsigned best = ~0u; char* p = (char*)scr->acc + i * 4096;
        for (int r = 0; r < 8; r++) { unsigned c; asm volatile("{.reg .b32 v, c0; .reg .pred p; mov.u32 c0, %%clock; atom.relaxed.gpu.global.exch.b32 v, [%1], 0; setp.eq.u32 p, v, 0x12345; @p trap;"
                                 " mov.u32 %0, %%clock; sub.u32 %0, %0, c0;}" : "=r"(c) : "l"(p) : "memory"); best = min(best, c); }
        scr->mmax[16 + i] = best;
    }
}
typedef CUresult (*EncodeFn)(CUtensorMap*, CUtensorMapDataType, cuuint32_t, void*, const cuuint64_t*, const cuuint64_t*,
                             const cuuint32_t*, const cuuint32_t*, CUtensorMapInterleave, CUtensorMapSwizzle,
                             CUtensorMapL2promotion, CUtensorMapFloatOOBfill);

}

extern "C" void kernel_launch(void* const* d_in, const int* in_sizes, int n_in, void* d_out, int out_size) {
    const __nv_bfloat16* q = (const __nv_bfloat16*)d_in[0];
    char* f0 = (char*)d_in[1];
    char* f1 = (char*)d_in[2];
    const __nv_bfloat16* wq = (const __nv_bfloat16*)d_in[3];
    const __nv_bfloat16* wk = (const __nv_bfloat16*)d_in[4];
    const __nv_bfloat16* wv = (const __nv_bfloat16*)d_in[5];
    const __nv_bfloat16* wo = (const __nv_bfloat16*)d_in[6];

    static EncodeFn enc = nullptr;
    static int grid = 0;
    static Scratch* scr = nullptr;
    if (!enc) {
        void* fn = nullptr; cudaDriverEntryPointQueryResult qr;
        cudaGetDriverEntryPoint("cuTensorMapEncodeTiled", &fn, cudaEnableDefault, &qr);
        enc = (EncodeFn)fn;
        cudaGetSymbolAddress((void**)&scr, g_scratch);
        int dev = 0, sms = 0;
        cudaGetDevice(&dev);
        cudaDeviceGetAttribute(&sms, cudaDevAttrMultiProcessorCount, dev);
        grid = sms < MAXG ? sms : MAXG;
        cudaFuncSetAttribute(attn_main, cudaFuncAttributeMaxDynamicSharedMemorySize, SMEM_BYTES);
        cudaFuncSetAttribute(dbgk, cudaFuncAttributeMaxDynamicSharedMemorySize, 200000);
        dbgk<<<132, 1, 200000, cudaStreamPerThread>>>(scr);
        cudaDeviceSynchronize();
        unsigned h[32]; cudaMemcpy(h, scr->mmax, 128, cudaMemcpyDeviceToHost);
        fprintf(stderr, "DBG scr %p f0 %p f1 %p out %p lat", (void*)scr, (void*)f0, (void*)f1, d_out);
        for (int i = 0; i < 8; i++) fprintf(stderr, " %u", h[16 + i]);
        fprintf(stderr, "\n");
    }
    CUtensorMap m0, m1;
    {
        cuuint64_t dims[5] = {64, W1, 3, 2, W0};
        cuuint64_t str[4] = {2 * C * 2, 128, C * 2, (cuuint64_t)W0 * C * 2};
        cuuint32_t box[5] = {64, TP, 3, 2, 2}, es[5] = {1, 1, 1, 1, 1};
        enc(&m0, CU_TENSOR_MAP_DATA_TYPE_BFLOAT16, 5, f0, dims, str, box, es, CU_TENSOR_MAP_INTERLEAVE_NONE,
            CU_TENSOR_MAP_SWIZZLE_128B, CU_TENSOR_MAP_L2_PROMOTION_NONE, CU_TENSOR_MAP_FLOAT_OOB_FILL_NONE);
    }
    {
        cuuint64_t dims[4] = {64, W1, 3, W1};
        cuuint64_t str[3] = {C * 2, 128, (cuuint64_t)W1 * C * 2};
        cuuint32_t box[4] = {64, TP, 3, 1}, es[4] = {1, 1, 1, 1};
        enc(&m1, CU_TENSOR_MAP_DATA_TYPE_BFLOAT16, 4, f1, dims, str, box, es, CU_TENSOR_MAP_INTERLEAVE_NONE,
            CU_TENSOR_MAP_SWIZZLE_128B, CU_TENSOR_MAP_L2_PROMOTION_NONE, CU_TENSOR_MAP_FLOAT_OOB_FILL_NONE);
    }
    attn_main<<<grid, NTHREADS, SMEM_BYTES, cudaStreamPerThread>>>(f0, f1, q, wq, wk, scr, wv, wo, (__nv_bfloat16*)d_out, m0, m1);
}
```

```cpp
#include <cuda_runtime.h>
#include <cuda_bf16.h>
#include <cuda.h>
#include <stdint.h>
#include <stddef.h>

namespace {

constexpr int C = 192;
constexpr int NQ = 16;
constexpr int W0 = 512;
constexpr int W1 = 256;
constexpr int TP = 8;
constexpr int NT = W1 * W1 / TP;
constexpr int STAGE = TP * 5 * C * 2;
#define NS 14
#define D0 3
#define D1 2
#define NRAMP 5
#define TA (p ? 470 : 185)
#define QSLEEP 700
#define WSL 24
#define MAXT 3000
#define REFT 1800
#define POLLN 1
#define PGAP 64
#define NPW 5
#define LAZY 12.f
#define GR4 1
#define NST 4
#define NI 1
#define NPACE 5
#define T0 0
#define T1 1600
#define TG 960
static_assert(NST > D0, "the first dynamic tile index must not delay the start");
constexpr int NTHREADS = 384;
constexpr int MAXG = 132;
constexpr int NRD = NQ;
constexpr int NSRC = 12;
constexpr int SPIN_LIMIT = 1 << 22;

constexpr int SM_STAGES = 0;
constexpr int SM_P = NS * STAGE;
constexpr int PBUF = 1088;
constexpr int SM_QK = SM_P + 4 * PBUF;
constexpr int SM_MX = SM_QK + 6144;
constexpr int SM_M = SM_MX + 512;
constexpr int SM_BAR = SM_M + 64;
constexpr int SM_REF = SM_BAR + 16 * NS;
constexpr int SM_FLAG = SM_REF + 8;
constexpr int SM_TOTAL = SM_FLAG + 4 * NS;
constexpr int SMEM_BYTES = SM_TOTAL + 1024;
static_assert(SMEM_BYTES <= 232448, "smem");
constexpr int WROW = 400;
constexpr int RD_W = 0;
constexpr int RD_QN = 2 * C * WROW;
constexpr int RD_KQ = RD_QN + 6144;
constexpr int RD_B = RD_KQ + 7168;
constexpr int RD_B2 = 17 * 80;
constexpr int RD_BAR = RD_B + 2 * RD_B2;
constexpr int RD_A = RD_BAR + 64;
constexpr int RD_WS = RD_A + 12 * 6 * 512;
static_assert(RD_WS + 12 * 128 <= SM_TOTAL, "smem");

struct Scratch {
    uint4 acc[2816];
    uint4 qk[NSRC * 32];
    unsigned ctr[32];
    unsigned mmax[32];
    unsigned mref[32];
    uint4 acc_hi[4096];
};
__device__ __align__(131072) Scratch g_scratch;
#define g_acc (scr->acc)
#define g_qk (scr->qk)
#define g_ctr (scr->ctr)
#define g_mmax (scr->mmax)
#define g_mref (scr->mref)
#define g_ts (scr->ts)
#define g_tr (scr->tr)
#define TR(k, i) do {} while (0)
#define TS(i) do {} while (0)
#define TSD(i, dep) do {} while (0)
#define TSX(i, dep) do {} while (0)
#define TSP(i, dep) do {} while (0)
#define TSE(i) TS(i)
#define CK_(i, dep) do {} while (0)
#define PH(i, dep) do {} while (0)

__device__ __forceinline__ uint32_t s2u(const void* p) { return (uint32_t)__cvta_generic_to_shared(p); }
__device__ __forceinline__ void mbar_init(uint32_t a, int c) { asm volatile("mbarrier.init.shared::cta.b64 [%0], %1;" ::"r"(a), "r"(c) : "memory"); }
__device__ __forceinline__ void mbar_expect(uint32_t a, uint32_t b) { asm volatile("mbarrier.arrive.expect_tx.shared::cta.b64 _, [%0], %1;" ::"r"(a), "r"(b) : "memory"); }
__device__ __forceinline__ void mbar_arrive(uint32_t a) { asm volatile("mbarrier.arrive.shared::cta.b64 _, [%0];" ::"r"(a) : "memory"); }
__device__ __forceinline__ void mbar_wait(uint32_t a, uint32_t ph) {
    uint32_t ok; int it = 0;
    do {
        asm volatile("{.reg .pred p; mbarrier.try_wait.parity.shared::cta.b64 p, [%1], %2; selp.u32 %0,1,0,p;}" : "=r"(ok) : "r"(a), "r"(ph) : "memory");
        if (++it > SPIN_LIMIT) __trap();
    } while (!ok);
}
__device__ __forceinline__ bool elect() {
    uint32_t r; asm volatile("{.reg .pred p; elect.sync _|p, 0xffffffff; selp.u32 %0, 1, 0, p;}" : "=r"(r)); return r;
}
__device__ __forceinline__ void bar_sync(int id, int n) { asm volatile("bar.sync %0, %1;" ::"r"(id), "r"(n) : "memory"); }
__device__ __forceinline__ bool bar_any(int id, int n, bool c) {
    uint32_t r;
    asm volatile("{.reg .pred p, q; setp.ne.u32 q, %3, 0; bar.red.or.pred p, %1, %2, q; selp.u32 %0, 1, 0, p;}" : "=r"(r) : "r"(id), "r"(n), "r"((uint32_t)c) : "memory");
    return r;
}
__device__ __forceinline__ void bar_arrive(int id, int n) { asm volatile("bar.arrive %0, %1;" ::"r"(id), "r"(n) : "memory"); }
__device__ __forceinline__ void ldsm4(uint32_t* r, uint32_t a) {
    asm volatile("ldmatrix.sync.aligned.m8n8.x4.shared.b16 {%0,%1,%2,%3}, [%4];" : "=r"(r[0]), "=r"(r[1]), "=r"(r[2]), "=r"(r[3]) : "r"(a) : "memory");
}
__device__ __forceinline__ void ldsm4t(uint32_t* r, uint32_t a) {
    asm volatile("ldmatrix.sync.aligned.m8n8.x4.trans.shared.b16 {%0,%1,%2,%3}, [%4];" : "=r"(r[0]), "=r"(r[1]), "=r"(r[2]), "=r"(r[3]) : "r"(a) : "memory");
}
__device__ __forceinline__ void ldsm2t(uint32_t* r, uint32_t a) {
    asm volatile("ldmatrix.sync.aligned.m8n8.x2.trans.shared.b16 {%0,%1}, [%2];" : "=r"(r[0]), "=r"(r[1]) : "r"(a) : "memory");
}
__device__ __forceinline__ void mma(float* d, uint32_t a0, uint32_t a1, uint32_t a2, uint32_t a3, uint32_t b0, uint32_t b1) {
    asm("mma.sync.aligned.m16n8k16.row.col.f32.bf16.bf16.f32 {%0,%1,%2,%3}, {%4,%5,%6,%7}, {%8,%9}, {%0,%1,%2,%3};"
        : "+f"(d[0]), "+f"(d[1]), "+f"(d[2]), "+f"(d[3]) : "r"(a0), "r"(a1), "r"(a2), "r"(a3), "r"(b0), "r"(b1));
}
__device__ __forceinline__ void mmah(float* d, uint32_t a0, uint32_t a1, uint32_t a2, uint32_t a3, uint32_t b0, uint32_t b1) {
    asm("mma.sync.aligned.m16n8k16.row.col.f32.f16.f16.f32 {%0,%1,%2,%3}, {%4,%5,%6,%7}, {%8,%9}, {%0,%1,%2,%3};"
        : "+f"(d[0]), "+f"(d[1]), "+f"(d[2]), "+f"(d[3]) : "r"(a0), "r"(a1), "r"(a2), "r"(a3), "r"(b0), "r"(b1));
}
__device__ __forceinline__ void mma8(float* d, uint32_t a0, uint32_t a1, uint32_t b0) {
    asm("mma.sync.aligned.m16n8k8.row.col.f32.bf16.bf16.f32 {%0,%1,%2,%3}, {%4,%5}, {%6}, {%0,%1,%2,%3};"
        : "+f"(d[0]), "+f"(d[1]), "+f"(d[2]), "+f"(d[3]) : "r"(a0), "r"(a1), "r"(b0));
}
__device__ __forceinline__ uint32_t hadd2(uint32_t a, uint32_t b) {
    uint32_t r; asm("add.rn.bf16x2 %0, %1, %2;" : "=r"(r) : "r"(a), "r"(b)); return r;
}
__device__ __forceinline__ uint32_t pack2(float lo, float hi) {
    uint32_t r; asm("cvt.rn.bf16x2.f32 %0, %1, %2;" : "=r"(r) : "f"(hi), "f"(lo)); return r;
}
__device__ __forceinline__ uint32_t packh(float lo, float hi) {
    uint32_t r; asm("cvt.rn.f16x2.f32 %0, %1, %2;" : "=r"(r) : "f"(hi), "f"(lo)); return r;
}
__device__ __forceinline__ float bflo(uint32_t v) { return __uint_as_float(v << 16); }
__device__ __forceinline__ float bfhi(uint32_t v) { return __uint_as_float(v & 0xffff0000u); }
__device__ __forceinline__ float ex2(float x) { float r; asm("ex2.approx.ftz.f32 %0, %1;" : "=f"(r) : "f"(x)); return r; }
__device__ __forceinline__ void sts128(uint32_t a, uint32_t x, uint32_t y, uint32_t z, uint32_t w) {
    asm volatile("st.shared.v4.b32 [%0], {%1,%2,%3,%4};" ::"r"(a), "r"(x), "r"(y), "r"(z), "r"(w) : "memory");
}
__device__ __forceinline__ void sts64(uint32_t a, uint32_t x, uint32_t y) {
    asm volatile("st.shared.v2.b32 [%0], {%1,%2};" ::"r"(a), "r"(x), "r"(y) : "memory");
}
__device__ __forceinline__ void sts32(uint32_t a, uint32_t x) { asm volatile("st.shared.b32 [%0], %1;" ::"r"(a), "r"(x) : "memory"); }
__device__ __forceinline__ uint4 lds128(uint32_t a) {
    uint4 v; asm volatile("ld.shared.v4.b32 {%0,%1,%2,%3}, [%4];" : "=r"(v.x), "=r"(v.y), "=r"(v.z), "=r"(v.w) : "r"(a) : "memory"); return v;
}
__device__ __forceinline__ uint2 lds64(uint32_t a) {
    uint2 v; asm volatile("ld.shared.v2.b32 {%0,%1}, [%2];" : "=r"(v.x), "=r"(v.y) : "r"(a) : "memory"); return v;
}
__device__ __forceinline__ uint32_t haddh(uint32_t a, uint32_t b) {
    uint32_t r; asm("add.rn.f16x2 %0, %1, %2;" : "=r"(r) : "r"(a), "r"(b)); return r;
}
__device__ __forceinline__ uint32_t lds32(uint32_t a) { uint32_t v; asm volatile("ld.shared.b32 %0, [%1];" : "=r"(v) : "r"(a) : "memory"); return v; }
__device__ __forceinline__ int grab_tile(unsigned* ctr) {
    int v; asm volatile("atom.relaxed.gpu.global.inc.u32 %0, [%1], 0x7fffffff;" : "=r"(v) : "l"(ctr) : "memory"); return v;
}
__device__ __forceinline__ uint32_t opaque(uint32_t v) { uint32_t r; asm volatile("mov.b32 %0, %1;" : "=r"(r) : "r"(v)); return r; }
__device__ __forceinline__ int laneid() { int r; asm volatile("mov.u32 %0, %%laneid;" : "=r"(r)); return r; }
__device__ __forceinline__ unsigned clock32() { unsigned c; asm volatile("mov.u32 %0, %%clock;" : "=r"(c)); return c; }
__device__ __forceinline__ float rsq(float x) { float r; asm("rsqrt.approx.ftz.f32 %0, %1;" : "=f"(r) : "f"(x)); return r; }
__device__ __forceinline__ float rcp(float x) { float r; asm("rcp.approx.ftz.f32 %0, %1;" : "=f"(r) : "f"(x)); return r; }
__device__ __forceinline__ float lg2(float x) { float r; asm("lg2.approx.ftz.f32 %0, %1;" : "=f"(r) : "f"(x)); return r; }
__device__ __forceinline__ float f(uint32_t v) { return __uint_as_float(v); }
__device__ __forceinline__ uint32_t u(float v) { return __float_as_uint(v); }

constexpr uint32_t ONES = 0x3F803F80u;
constexpr float QSCALE = 0.07216878364870322f * 1.4426950408889634f;

__device__ __forceinline__ void issue_tile(const CUtensorMap* m0, const CUtensorMap* m1, uint32_t sb, int s, int tl, uint64_t pol) {
    const uint32_t full = sb + SM_BAR + s * 8, dst = sb + SM_STAGES + s * STAGE;
    const int par = tl * TP, y = par >> 8, x = par & 255;
    mbar_expect(full, STAGE);
    asm volatile("cp.async.bulk.tensor.5d.shared::cluster.global.mbarrier::complete_tx::bytes.L2::cache_hint [%0], [%1, {%3,%4,%3,%3,%5}], [%2], %6;"
                 ::"r"(dst), "l"(m0), "r"(full), "r"(0), "r"(x), "r"(2 * y), "l"(pol) : "memory");
    asm volatile("cp.async.bulk.tensor.4d.shared::cluster.global.mbarrier::complete_tx::bytes.L2::cache_hint [%0], [%1, {%3,%4,%3,%5}], [%2], %6;"
                 ::"r"(dst + TP * 4 * C * 2), "l"(m1), "r"(full), "r"(0), "r"(x), "r"(y), "l"(pol) : "memory");
}

__device__ __forceinline__ void prefetch_l2(const void* a, int n) { asm volatile("cp.async.bulk.prefetch.L2.global [%0], %1;" ::"l"(a), "r"(n) : "memory"); }
__device__ __forceinline__ uint4 ldg_relaxed(const uint4* p) {
    uint4 v; asm volatile("ld.relaxed.gpu.global.v4.u32 {%0,%1,%2,%3}, [%4];" : "=r"(v.x), "=r"(v.y), "=r"(v.z), "=r"(v.w) : "l"(p) : "memory"); return v;
}
__device__ __forceinline__ uint32_t ldg_relaxed32(const void* p) {
    uint32_t v; asm volatile("ld.relaxed.gpu.global.u32 %0, [%1];" : "=r"(v) : "l"(p) : "memory"); return v;
}
__device__ __forceinline__ void stg_relaxed(uint4* p, uint32_t x, uint32_t y, uint32_t z, uint32_t w) {
    asm volatile("st.relaxed.gpu.global.v4.u32 [%0], {%1,%2,%3,%4};" ::"l"(p), "r"(x), "r"(y), "r"(z), "r"(w) : "memory");
}
__device__ __forceinline__ void stg_relaxed32(void* p, uint32_t x) { asm volatile("st.relaxed.gpu.global.u32 [%0], %1;" ::"l"(p), "r"(x) : "memory"); }
__device__ __forceinline__ bool has(const uint4& v, uint32_t m) { return v.x == m || v.y == m || v.z == m || v.w == m; }
__device__ __forceinline__ uint32_t hadd2v(uint32_t a, uint32_t b) {
    uint32_t r; asm volatile("add.rn.bf16x2 %0, %1, %2;" : "=r"(r) : "r"(a), "r"(b)); return r;
}

__device__ __forceinline__ void red8h(uint4* p, uint32_t x, uint32_t y, uint32_t z, uint32_t w) {
    asm volatile("red.relaxed.gpu.global.add.noftz.v4.f16x2 [%0], {%1,%2,%3,%4};" ::"l"(p), "r"(x), "r"(y), "r"(z), "r"(w) : "memory");
}
__device__ __forceinline__ uint4 lds128v(uint32_t a) {
    uint4 v; asm volatile("ld.volatile.shared.v4.b32 {%0,%1,%2,%3}, [%4];" : "=r"(v.x), "=r"(v.y), "=r"(v.z), "=r"(v.w) : "r"(a) : "memory"); return v;
}
__device__ __forceinline__ uint32_t brow(int r) { return RD_B + r * 80 + (r >> 3) * 64; }

constexpr int ACC_HI = 65536;
static_assert(offsetof(Scratch, acc_hi) <= ACC_HI && offsetof(Scratch, acc_hi) + sizeof(Scratch::acc_hi) >= ACC_HI + 32768, "scratch");
__device__ __forceinline__ uint32_t acc_line(int s, int k) {
    return (k >> 2) * 16384 + (k & 2) * 6144 + (k & 1) * 1024 + (s & 1) * 256 + (s & 2) * 1024 + (s >> 2) * ACC_HI;
}

enum { B_QK = 1, B_QN = 2, B_GRP = 3  , B_Q = 5, B_MERGE = 6, B_ALL = 7, B_MAX = 8  , B_WARP = 10, B_SLOW = 12, B_PARK = 13, B_CLEAN = 14, B_RDY = 15 };

__device__ __noinline__ void slow_rows(const char* __restrict__ f0, const char* __restrict__ f1, const __nv_bfloat16* __restrict__ q,
                                       const __nv_bfloat16* __restrict__ wq, const __nv_bfloat16* __restrict__ wk, const uint32_t sb)
{
    const int warp = threadIdx.x >> 5, lane = threadIdx.x & 31;
    float* const sm = reinterpret_cast<float*>(__cvta_shared_to_generic(sb + RD_W));
    for (int i = threadIdx.x; i < 2 * C; i += 128) sm[i] = __bfloat162float(q[(blockIdx.x & 14) * C + i]);
    bar_sync(B_SLOW, 128);
#pragma unroll 1
    for (int j = threadIdx.x; j < 2 * C; j += 128) {
        const float* const x = sm + j / C * C;
        float mu = 0.f, var = 0.f, s = 0.f;
#pragma unroll 1
        for (int i = 0; i < C; i++) mu += x[i];
        mu *= 1.f / C;
#pragma unroll 4
        for (int i = 0; i < C; i++) { var = fmaf(x[i] - mu, x[i] - mu, var); s = fmaf(x[i] - mu, __bfloat162float(wq[i * C + j % C]), s); }
        sm[4 * C + j] = s * rsq(var * (1.f / C) + 1e-5f);
    }
    bar_sync(B_SLOW, 128);
#pragma unroll 1
    for (int j = threadIdx.x; j < 2 * C; j += 128) {
        float s = 0.f;
#pragma unroll 4
        for (int i = 0; i < C; i++) s = fmaf(sm[4 * C + j / C * C + i], __bfloat162float(wk[j % C * C + i]), s);
        sm[j] = s * QSCALE;
    }
    bar_sync(B_SLOW, 128);
    float k[2][6], a[2][6], m[2], l[2];
#pragma unroll
    for (int r = 0; r < 2; r++) {
        m[r] = -INFINITY; l[r] = 0.f;
#pragma unroll
        for (int i = 0; i < 6; i++) { k[r][i] = sm[r * C + 64 * (i >> 1) + 2 * lane + (i & 1)]; a[r][i] = 0.f; }
    }
#pragma unroll 1
    for (int par = warp; par < W1 * W1; par += 4) {
        const uint32_t* p0 = reinterpret_cast<const uint32_t*>(f0 + (size_t)((par >> 8) * 2 * W0 + (par & 255) * 2) * (C * 2)) + lane;
        const uint32_t* p1 = reinterpret_cast<const uint32_t*>(f1 + (size_t)par * (C * 2)) + lane;
        uint32_t v[4][3];
#pragma unroll
        for (int i = 0; i < 3; i++)
#pragma unroll
            for (int j = 0; j < 4; j++) v[j][i] = hadd2(__ldg(p0 + ((j >> 1) * W0 + (j & 1)) * (C / 2) + 32 * i), __ldg(p1 + 32 * i));
#pragma unroll
        for (int j = 0; j < 4; j++) {
            float x[6], s1 = 0.f, s2 = 0.f, d[2] = {0.f, 0.f};
#pragma unroll
            for (int i = 0; i < 3; i++) { x[2 * i] = bflo(v[j][i]); x[2 * i + 1] = bfhi(v[j][i]); s1 += x[2 * i] + x[2 * i + 1]; }
#pragma unroll
            for (int o = 1; o < 32; o <<= 1) s1 += __shfl_xor_sync(~0u, s1, o);
#pragma unroll
            for (int i = 0; i < 6; i++) {
                x[i] -= s1 * (1.f / C); s2 = fmaf(x[i], x[i], s2);
#pragma unroll
                for (int r = 0; r < 2; r++) d[r] = fmaf(x[i], k[r][i], d[r]);
            }
#pragma unroll
            for (int o = 1; o < 32; o <<= 1) {
                s2 += __shfl_xor_sync(~0u, s2, o);
#pragma unroll
                for (int r = 0; r < 2; r++) d[r] += __shfl_xor_sync(~0u, d[r], o);
            }
            const float rs = rsq(s2 * (1.f / C) + 1e-5f);
#pragma unroll
            for (int r = 0; r < 2; r++) {
                const float nm = fmaxf(m[r], d[r] * rs), al = ex2(m[r] - nm), p = ex2(d[r] * rs - nm);
                m[r] = nm; l[r] = fmaf(l[r], al, p);
#pragma unroll
                for (int i = 0; i < 6; i++) a[r][i] = fmaf(a[r][i], al, x[i] * (p * rs));
            }
        }
    }
    bar_sync(B_SLOW, 128);
#pragma unroll
    for (int r = 0; r < 2; r++) {
        float* const o = sm + ((r * 4 + warp) * 32 + lane) * 8;
#pragma unroll
        for (int i = 0; i < 6; i++) o[i] = a[r][i];
        o[6] = l[r]; o[7] = m[r];
    }
    bar_sync(B_SLOW, 128);
    if (warp < 2) {
        const int r = warp;
        const float* const o = sm + (r * 128 + lane) * 8;
        float M = o[7], x[7] = {0.f, 0.f, 0.f, 0.f, 0.f, 0.f, 0.f};
#pragma unroll
        for (int w = 1; w < 4; w++) M = fmaxf(M, o[256 * w + 7]);
#pragma unroll
        for (int w = 0; w < 4; w++) {
            const float e = ex2(o[256 * w + 7] - M);
#pragma unroll
            for (int i = 0; i < 7; i++) x[i] = fmaf(o[256 * w + i], e, x[i]);
        }
        const float rl = 1.f / x[6];
        sts128(sb + RD_B2 + brow(8 * (lane >> 4) + 4 * r + (lane & 3)) + ((lane >> 2) & 3) * 16, packh(x[0] * rl, x[1] * rl), packh(x[2] * rl, x[3] * rl), packh(x[4] * rl, x[5] * rl), lane ? 0u : 0x3C00u);
    }
}

template <bool FIRST>
__device__ __forceinline__ void project(const uint32_t ar, const uint32_t br, const bool hi, const float ws0, const float ws1, const float qv0, const float qv1,
                                        __nv_bfloat16* op0, __nv_bfloat16* op1, Scratch* scr)
{
    uint4 wa[3][6], x[4];
#pragma unroll
    for (int i = 0; i < 18; i++) wa[i / 6][i % 6] = lds128v(ar + i * 512);
    if (FIRST) { bar_arrive(B_CLEAN, NTHREADS); bar_sync(B_RDY, 192); }
    else bar_sync(B_SLOW, 128);
    if (FIRST && threadIdx.x == 0) TSX(8, 0);
#pragma unroll
    for (int j = 0; j < 4; j++) x[j] = lds128v(br + 16 * j);
    float o[7][4];
#pragma unroll
    for (int j = 0; j < 7; j++) o[j][0] = o[j][1] = o[j][2] = o[j][3] = 0.f;
#pragma unroll
    for (int i = 0; i < 2; i++) {
        mmah(o[6], 0x3C00u, 0x3C00u, 0x3C00u, 0x3C00u, x[2 * i].w, x[2 * i + 1].w);
#pragma unroll
        for (int n = 0; n < 3; n++) mmah(o[2 * n + i], wa[n][2 * i].x, wa[n][2 * i].y, wa[n][2 * i].z, wa[n][2 * i].w, x[2 * i].x, x[2 * i].y);
#pragma unroll
        for (int n = 0; n < 3; n++) mmah(o[2 * n + 1 - i], wa[n][2 * i + 1].x, wa[n][2 * i + 1].y, wa[n][2 * i + 1].z, wa[n][2 * i + 1].w, x[2 * i + 1].x, x[2 * i + 1].y);
#pragma unroll
        for (int n = 0; n < 3; n++) mmah(o[2 * n + i], wa[n][4 + i].x, wa[n][4 + i].y, wa[n][4 + i].z, wa[n][4 + i].w, x[2 * i].z, x[2 * i + 1].z);
    }
    const float L = o[6][0] + o[6][1], r = rcp(L);
    const float y0 = hi ? (o[2][0] + o[2][3]) + (o[3][0] + o[3][3]) : (o[0][0] + o[0][3]) + (o[1][0] + o[1][3]), y1 = (o[4][0] + o[4][3]) + (o[5][0] + o[5][3]);
    const uint32_t y = pack2(fmaf(y0, r * ws0, qv0), fmaf(y1, r * ws1, qv1));
    asm volatile("{.reg .b16 l, h; mov.b32 {l, h}, %2; st.global.b16 [%0], l; st.global.b16 [%1], h;}" ::"l"(op0), "l"(op1), "r"(y) : "memory");
    if (FIRST && threadIdx.x == 0) TSD(11, y);
    if (FIRST)
        asm volatile("{.reg .pred p; .reg .f32 a; abs.f32 a, %1; setp.ge.f32 p, %0, 0f3B000000; setp.le.and.f32 p, %0, 0f45000000, p; setp.lt.and.f32 p, a, 0f7F800000, p;"
                     " vote.sync.all.pred p, p, 0xffffffff; @p exit;}" ::"f"(L), "f"(y0) : "memory");
}

__device__ __forceinline__ void reducer(const char* __restrict__ f0, const char* __restrict__ f1, const __nv_bfloat16* __restrict__ q, const __nv_bfloat16* __restrict__ wq, const __nv_bfloat16* __restrict__ wk,
                                        Scratch* scr, const __nv_bfloat16* __restrict__ wv, const __nv_bfloat16* __restrict__ wo,
                                        __nv_bfloat16* __restrict__ out, const uint32_t sb, const int GS)
{
    const int warp = threadIdx.x >> 5, lane = threadIdx.x & 31, b = blockIdx.x;
    const int g = lane >> 2, t = lane & 3;
    char* const ap = reinterpret_cast<char*>(g_acc);
    if (threadIdx.x == 256) TS(0);
    if (b < NSRC && warp < 8) {
        const uint32_t wqs = sb + RD_W, wbar = sb + RD_BAR;
        const int hr = lane >> 4, qt = (lane >> 2) & 3, sub = lane & 3;
        const uint32_t* qp = reinterpret_cast<const uint32_t*>(q + (warp + 8 * hr) * C + 48 * qt + 6 * sub);
        uint32_t qw[6];
#pragma unroll
        for (int j = 0; j < 3; j++) { qw[j] = __ldg(qp + j); qw[3 + j] = __ldg(qp + 12 + j); }
        if (lane == 0) { mbar_init(wbar + warp * 8, 1); asm volatile("fence.mbarrier_init.release.cluster;" ::: "memory"); mbar_expect(wbar + warp * 8, 9216);
            asm volatile("cp.async.bulk.shared::cluster.global.mbarrier::complete_tx::bytes [%0], [%1], 9216, [%2];"
                         ::"r"(wqs + warp * 9232), "l"(wq + 24 * warp * C), "r"(wbar + warp * 8) : "memory");
        }
        __syncwarp();
        if (threadIdx.x == 0) TSP(2, 0);
        float e[12];
#pragma unroll
        for (int j = 0; j < 6; j++) { e[2 * j] = bflo(qw[j]); e[2 * j + 1] = bfhi(qw[j]); }
        float sm = ((e[0] + e[1]) + (e[2] + e[3])) + ((e[4] + e[5]) + (e[6] + e[7])) + ((e[8] + e[9]) + (e[10] + e[11]));
#pragma unroll
        for (int o = 1; o < 16; o <<= 1) sm += __shfl_xor_sync(~0u, sm, o);
        if (threadIdx.x == 0) TSP(5, u(sm));
        float v0 = 0.f, v1 = 0.f;
#pragma unroll
        for (int j = 0; j < 12; j++) e[j] -= sm * (1.f / C);
#pragma unroll
        for (int j = 0; j < 6; j++) { v0 = fmaf(e[j], e[j], v0); v1 = fmaf(e[6 + j], e[6 + j], v1); }
        v0 += v1;
#pragma unroll
        for (int o = 1; o < 16; o <<= 1) v0 += __shfl_xor_sync(~0u, v0, o);
        const float rq = rsq(v0 * (1.f / C) + 1e-5f);
#pragma unroll
        for (int j = 0; j < 6; j++)
            sts32(sb + RD_QN + (3 * sub + (j >> 1)) * 512 + (4 * warp + qt) * 16 + (2 * (j & 1) + hr) * 4, pack2(e[j] * rq, e[6 + j] * rq));
        if (threadIdx.x == 0) TSP(8, 0);
        uint32_t wkf[2][3];
#pragma unroll
        for (int i = 0; i < 2; i++)
#pragma unroll
            for (int j = 0; j < 3; j++) wkf[i][j] = __ldg(reinterpret_cast<const uint32_t*>(wk + (16 * b + 8 * i + g) * C + 24 * warp + 8 * j + 2 * t));
        bar_sync(B_QN, 256);
        float acc[2][3][4];
#pragma unroll
        for (int i = 0; i < 3; i++)
#pragma unroll
            for (int e = 0; e < 4; e++) acc[0][i][e] = acc[1][i][e] = 0.f;
        const uint32_t ba = wqs + (lane & 7) * 9232 + (lane >> 3) * 384 + 48 * warp;
        uint4 a[12];
#pragma unroll
        for (int kk = 0; kk < 12; kk++) a[kk] = lds128(sb + RD_QN + kk * 512 + lane * 16);
        mbar_wait(wbar + (lane & 7) * 8, 0);
        __syncwarp();
        if (threadIdx.x == 0) TSP(4, 0);
#pragma unroll
        for (int kp = 0; kp < 6; kp++)
#pragma unroll
            for (int i = 0; i < 3; i++) {
                uint32_t bb[4];
                ldsm4t(bb, ba + kp * 1536 + i * 16);
                mma(acc[0][i], a[2 * kp].x, a[2 * kp].y, a[2 * kp].z, a[2 * kp].w, bb[0], bb[1]);
                mma(acc[1][i], a[2 * kp + 1].x, a[2 * kp + 1].y, a[2 * kp + 1].z, a[2 * kp + 1].w, bb[2], bb[3]);
            }
        if (threadIdx.x == 0) TSP(7, u(acc[1][2][3]));
        float kq[2][4] = {{0.f, 0.f, 0.f, 0.f}, {0.f, 0.f, 0.f, 0.f}};
#pragma unroll
        for (int j = 0; j < 3; j++) {
            const uint32_t a0 = pack2(acc[0][j][0] + acc[1][j][0], acc[0][j][1] + acc[1][j][1]), a1 = pack2(acc[0][j][2] + acc[1][j][2], acc[0][j][3] + acc[1][j][3]);
            mma8(kq[0], a0, a1, wkf[0][j]);
            mma8(kq[1], a0, a1, wkf[1][j]);
        }
        if (warp < 7) {
            sts128(sb + RD_KQ + warp * 1024 + lane * 16, u(kq[0][0]), u(kq[0][1]), u(kq[0][2]), u(kq[0][3]));
            sts128(sb + RD_KQ + warp * 1024 + 512 + lane * 16, u(kq[1][0]), u(kq[1][1]), u(kq[1][2]), u(kq[1][3]));
            bar_arrive(B_Q, 256);
        } else {
            bar_sync(B_Q, 256);
#pragma unroll
            for (int w = 0; w < 7; w++)
#pragma unroll
                for (int i = 0; i < 2; i++) {
                    const uint4 o = lds128(sb + RD_KQ + w * 1024 + i * 512 + lane * 16);
                    kq[i][0] += f(o.x); kq[i][1] += f(o.y); kq[i][2] += f(o.z); kq[i][3] += f(o.w);
                }
            stg_relaxed(g_qk + b * 32 + lane, ~pack2(kq[0][0] * QSCALE, kq[0][1] * QSCALE), ~pack2(kq[0][2] * QSCALE, kq[0][3] * QSCALE),
                        ~pack2(kq[1][0] * QSCALE, kq[1][1] * QSCALE), ~pack2(kq[1][2] * QSCALE, kq[1][3] * QSCALE));
            if (lane == 0) TS(10);
        }
    } else if (warp == 8 && !(b & 1)) {
#pragma unroll
        for (int i = 0; i < 2; i++) stg_relaxed(reinterpret_cast<uint4*>(ap + acc_line(b >> 1, 4 * i + (lane >> 3))) + (lane & 7), 0, 0, 0, 0);
        __threadfence();
    } else if (b >= NSRC) {
        if (b == NSRC && warp == 0) stg_relaxed32(g_mmax + lane, 0);
        const unsigned c0 = clock32();
        for (int it = 0; it < 8; it++) {
            __nanosleep(500);
            if (clock32() - c0 > 4400) break;
        }
    }
    bar_sync(B_ALL, NTHREADS);

#pragma unroll 1
    for (int r = 0; r < 3; r++) {
        uint4 v[8];
#pragma unroll
        for (int k = 0; k < 8; k++) {
            const int idx = (8 * r + k) * 384 + threadIdx.x;
            v[k] = __ldg(reinterpret_cast<const uint4*>(idx < 4608 ? wv : wo - C * C) + idx);
        }
#pragma unroll
        for (int k = 0; k < 8; k++) {
            const int idx = (8 * r + k) * 384 + threadIdx.x, row = idx / 24;
            sts128(sb + RD_W + row * WROW + (idx - 24 * row) * 16, v[k].x, v[k].y, v[k].z, v[k].w);
        }
    }
    bar_sync(B_ALL, NTHREADS);
    if (warp < 6) {
        const int col = 96 * (b & 1) + 16 * warp;
        float d[24][4];
#pragma unroll
        for (int i = 0; i < 24; i++) d[i][0] = d[i][1] = d[i][2] = d[i][3] = 0.f;
        const int mi = lane >> 3, r = lane & 7;
        const uint32_t aa = sb + RD_W + (C + (mi >> 1) * 8 + r) * WROW + (col + (mi & 1) * 8) * 2;
        const uint32_t ba = sb + RD_W + ((mi >> 1) * 8 + r) * WROW + (mi & 1) * 16;
#pragma unroll 1
        for (int kk = 0; kk < 12; kk++) {
            uint32_t a[4];
            ldsm4t(a, aa + kk * 16 * WROW);
#pragma unroll
            for (int i = 0; i < 12; i++) {
                uint32_t bb[4];
                ldsm4(bb, ba + i * 16 * WROW + kk * 32);
                mma(d[2 * i], a[0], a[1], a[2], a[3], bb[0], bb[1]);
                mma(d[2 * i + 1], a[0], a[1], a[2], a[3], bb[2], bb[3]);
            }
        }
        float c0 = 0.f, c1 = 0.f, m0 = 0.f, m1 = 0.f;
#pragma unroll
        for (int i = 0; i < 24; i++) { c0 += d[i][0] + d[i][1]; c1 += d[i][2] + d[i][3]; }
        c0 += __shfl_xor_sync(~0u, c0, 1); c1 += __shfl_xor_sync(~0u, c1, 1);
        c0 += __shfl_xor_sync(~0u, c0, 2); c1 += __shfl_xor_sync(~0u, c1, 2);
        c0 *= 1.f / C; c1 *= 1.f / C;
#pragma unroll
        for (int i = 0; i < 24; i++) {
            d[i][0] -= c0; d[i][1] -= c0; d[i][2] -= c1; d[i][3] -= c1;
            m0 = fmaxf(m0, fmaxf(fabsf(d[i][0]), fabsf(d[i][1]))); m1 = fmaxf(m1, fmaxf(fabsf(d[i][2]), fabsf(d[i][3])));
        }
        m0 = fmaxf(m0, __shfl_xor_sync(~0u, m0, 1)); m1 = fmaxf(m1, __shfl_xor_sync(~0u, m1, 1));
        m0 = fmaxf(m0, __shfl_xor_sync(~0u, m0, 2)); m1 = fmaxf(m1, __shfl_xor_sync(~0u, m1, 2));
        const uint32_t e0 = min(max(u(m0) >> 23, 12u), 254u), e1 = min(max(u(m1) >> 23, 12u), 254u);
        const float s0 = f((265u - e0) << 23), s1 = f((265u - e1) << 23);
        const bool k0 = fabsf(c0) < INFINITY, k1 = fabsf(c1) < INFINITY;
#pragma unroll
        for (int j = 0; j < 6; j++) {
            const int n[4] = {j < 4 ? j : 8 + 2 * j, j < 4 ? 4 + j : 12 + 2 * j, j < 4 ? 8 + j : 9 + 2 * j, j < 4 ? 12 + j : 13 + 2 * j};
            uint32_t a[2][4];
#pragma unroll
            for (int e = 0; e < 4; e++) {
                a[0][e] = k0 ? packh(d[n[e]][0] * s0, d[n[e]][1] * s0) : 0u;
                a[1][e] = k1 ? packh(d[n[e]][2] * s1, d[n[e]][3] * s1) : 0u;
            }
#pragma unroll
            for (int e = 0; e < 2; e++) sts128(sb + RD_A + ((2 * warp + e) * 6 + j) * 512 + lane * 16, a[e][0], a[e][1], a[e][2], a[e][3]);
        }
        sts32(sb + RD_WS + 2 * warp * 128 + lane * 4, k0 ? (e0 - 11u) << 23 : u(c0));
        sts32(sb + RD_WS + (2 * warp + 1) * 128 + lane * 4, k1 ? (e1 - 11u) << 23 : u(c1));
        if (warp < 4) bar_sync(B_PARK, 192); else bar_arrive(B_PARK, 192);
        if (threadIdx.x == 0) TSE(6);
    }
    if (warp >= 4) {
        if (threadIdx.x == 128) {
            uint32_t m;
            for (int it = 0;; it++) {
                const int left = NT - 2 * NST * GS - (int)ldg_relaxed32(g_ctr);
                m = ldg_relaxed32(g_mmax + b);
                if (left <= REFT && m) break;
                if (left <= 0) { m = 0x80000000u; break; }
                if (it > SPIN_LIMIT) __trap();
                __nanosleep(300);
            }
            if (b & 1) for (int it = 0;; it++) {
                uint32_t r;
                asm volatile("ld.acquire.gpu.global.u32 %0, [%1];" : "=r"(r) : "l"(g_mref + b - 1) : "memory");
                if (r) break;
                if (it > SPIN_LIMIT) __trap();
            }
            asm volatile("st.release.gpu.global.u32 [%0], %1;" ::"l"(g_mref + b), "r"(~u(f(m >> 31 ? m ^ 0x80000000u : ~m) + 8.f)) : "memory");
            TSE(7);
        }
        __syncwarp();
        if (warp == 4) {
            uint4* p0 = g_qk + min(b, NSRC - 1) * 32 + lane;
            unsigned* p1 = lane == 1 && b == NSRC ? g_ctr : g_mref + b;
            asm volatile("" : "+l"(p0), "+l"(p1));
            bar_arrive(B_CLEAN, NTHREADS);
            bar_sync(B_RDY, 192);
            *p0 = make_uint4(0, 0, 0, 0);
            *p1 = 0;
            return;
        }
        bar_sync(B_CLEAN, NTHREADS);
        if (warp >= 5 + NPW) return;
        const uint4* const pa = reinterpret_cast<const uint4*>(ap + acc_line(b >> 1, lane >> 3)) + (lane & 7);
        const uint32_t bw = opaque(sb + brow(lane & 7) + (lane >> 3) * 16);
        const uint32_t n0 = packh(0.f, (float)GS), nstart = packh(0.f, (float)POLLN);
        for (int it = 0; ldg_relaxed32(ap + acc_line(b >> 1, 0) + 12) < nstart; it++)
            if (it > SPIN_LIMIT) __trap();
        for (const unsigned c = clock32(); clock32() - c < (warp - 5) * PGAP;) {}
        for (int it = 0;; it++) {
            const uint4 a0 = ldg_relaxed(pa), b0 = ldg_relaxed(pa + 1024);
            if (it > SPIN_LIMIT) __trap();
            bar_sync(B_WARP, 32);
            asm volatile("{.reg .pred p, q; .reg .b32 a; setp.ge.u32 p, %5, %10; setp.ge.and.u32 p, %9, %10, p; vote.sync.all.pred q, p, 0xffffffff; selp.b32 a, %0, %1, p;"
                         " st.shared.v4.b32 [a], {%2,%3,%4,%5}; st.shared.v4.b32 [a + 704], {%6,%7,%8,%9}; @q bar.arrive 15, 192; @q exit;}"
                         ::"r"(bw), "r"(bw - (RD_B - RD_QN)), "r"(a0.x), "r"(a0.y), "r"(a0.z), "r"(a0.w), "r"(b0.x), "r"(b0.y), "r"(b0.z), "r"(b0.w), "r"(n0) : "memory");
        }
    }
    const uint32_t br = opaque(sb + brow(8 * (g & 1) + 2 * (g & 2) + t));
    const bool hi = t >= 2;
    const int oi = ((b & 14) + (t & 1)) * C + 96 * (b & 1) + 24 * warp + g;
    const float qv0 = __bfloat162float(q[oi + 4 * (t & 2)]), qv1 = __bfloat162float(q[oi + 16]);
    const float ws0 = f(lds32(sb + RD_WS + (3 * warp + (t >> 1)) * 128 + lane * 4)), ws1 = f(lds32(sb + RD_WS + (3 * warp + 2) * 128 + lane * 4));
    __nv_bfloat16* op0 = out + oi + 4 * (t & 2), * op1 = out + oi + 16;
    asm volatile("" : "+l"(op0), "+l"(op1));
    const uint32_t ar = sb + RD_A + warp * 18 * 512 + lane * 16;
    project<true>(ar, br, hi, ws0, ws1, qv0, qv1, op0, op1, scr);
    slow_rows(f0, f1, q, wq, wk, sb);
    project<false>(ar, br + RD_B2, hi, ws0, ws1, qv0, qv1, op0, op1, scr);
}

__global__ void __launch_bounds__(NTHREADS, 1)
attn_main(const char* __restrict__ f0, const char* __restrict__ f1,
          const __nv_bfloat16* __restrict__ q, const __nv_bfloat16* __restrict__ wq, const __nv_bfloat16* __restrict__ wk, Scratch* scr,
          const __nv_bfloat16* __restrict__ wv, const __nv_bfloat16* __restrict__ wo, __nv_bfloat16* __restrict__ out,
          const __grid_constant__ CUtensorMap m0, const __grid_constant__ CUtensorMap m1)
{
    extern __shared__ char smem_raw[];
    const uint32_t sb = (s2u(smem_raw) + 1023u) & ~1023u;
    const int G = gridDim.x - NRD;
    const int b = blockIdx.x - NRD;
    if (threadIdx.x == 0 && b >= 0) {
        const char* a = f0 + (uint32_t)(b * (4 * TP * C * 2) + (b >> 4) * (W0 * C * 2));
        prefetch_l2(a, 4 * TP * C * 2);
        prefetch_l2(a + W0 * C * 2, 4 * TP * C * 2);
        prefetch_l2(f1 + b * (2 * TP * C * 2), 2 * TP * C * 2);
        prefetch_l2((const char*)(b % (2 * WSL) < WSL ? wq : wk) + b % WSL * (C * C * 2 / WSL), C * C * 2 / WSL);
    }
    if (b < 0) { reducer(f0, f1, q, wq, wk, scr, wv, wo, out, sb, G); return; }
    const int warp = __shfl_sync(~0u, threadIdx.x >> 5, 0), lane = laneid();
    const int g = lane >> 2, t = lane & 3;

    if (warp >= 8) {
        if (warp < 10) {
            const int p = warp - 8;
            const unsigned c0 = clock32();
            const uint32_t sbp = opaque(sb), bar = sbp + SM_BAR + p * 8;
            uint64_t pol; asm volatile("createpolicy.fractional.L2::evict_first.b64 %0, 1.0;" : "=l"(pol));
            if (elect()) {
                if (p == 0) TS(0);
                asm volatile("prefetch.tensormap [%0];" ::"l"(p ? &m1 : &m0) : "memory");
#pragma unroll
                for (int n = 0; n < NI; n++) mbar_init(bar + n * 16, 2);
                asm volatile("fence.mbarrier_init.release.cluster;" ::: "memory");
#pragma unroll
                for (int n = 0; n < NI; n++) {
                    issue_tile(&m0, &m1, sbp, p + 2 * n, 2 * b + p + 2 * n * G, pol);
                    TR(0, 2 * n + p);
                    sts32(sbp + SM_FLAG + (p + 2 * n) * 4, 0);
                    mbar_arrive(bar + n * 16);
                }
#pragma unroll
                for (int n = 0; n < NS / 2; n++) {
                    if (n >= NI) mbar_init(bar + n * 16, 2);
                    mbar_init(bar + NS * 8 + n * 16, 1);
                }
                if (p == 0) mbar_init(sbp + SM_REF, 1);
                asm volatile("fence.mbarrier_init.release.cluster;" ::: "memory");
            }
            __syncwarp();
            bar_arrive(B_QK, NTHREADS);
            if (elect()) {
                int tl = 2 * b + p + 2 * NI * G;
                int s = p + 2 * NI; uint32_t ph = 1;
                int sa = p, na = 0; uint32_t pa = 0;
                bool late = false;
                for (int n = NI;; n++) {
                    const int d = n < NRAMP ? D0 : (tl >= NT - (TA) ? 1 : D1);
                    while (n - na >= d) {
                        mbar_wait(sbp + SM_BAR + sa * 8, pa);
                        if (na < NS / 2) TR(1, 2 * na + p);
                        na++; sa += 2;
                        if (sa >= NS) { sa -= NS; pa ^= 1; }
                    }
                    mbar_wait(sbp + SM_BAR + (NS + s) * 8, ph);
                    if (n < NPACE) while (clock32() - c0 < (n ? T1 + (2 * (n - 1) + p) * TG : T0)) {}
                    issue_tile(&m0, &m1, sbp, s, tl, pol);
                    TR(0, 2 * n + p);
                    int nxt = tl + 2 * G;
                    if (n >= NST - 1) nxt = grab_tile(g_ctr) + 2 * NST * G;
                    const bool last = nxt >= NT;
                    uint32_t flag = last;
                    if (!late && nxt >= NT - MAXT - 16 * b) { late = true; flag |= 2; }
                    if (last) mbar_wait(sbp + SM_REF, 0);
                    sts32(sbp + SM_FLAG + s * 4, flag);
                    mbar_arrive(sbp + SM_BAR + s * 8);
                    if (last) break;
                    s += 2;
                    if (s >= NS) { s -= NS; ph ^= 1; }
                    tl = nxt;
                }
                if (p) TSE(5);
            }
            return;
        }
        const int h = threadIdx.x - 320;
        uint4 v[6];
        for (int it = 0;; it++) {
            bool miss = false;
#pragma unroll
            for (int k = 0; k < 6; k++) v[k] = ldg_relaxed(g_qk + k * 64 + h);
#pragma unroll
            for (int k = 0; k < 6; k++) miss |= has(v[k], 0);
            if (!miss) break;
            if (it > SPIN_LIMIT) __trap();
            if (it == 0) __nanosleep(QSLEEP);
        }
#pragma unroll
        for (int k = 0; k < 6; k++) sts128(sb + SM_QK + (k * 64 + h) * 16, ~v[k].x, ~v[k].y, ~v[k].z, ~v[k].w);
        __syncwarp();
        bar_sync(B_QK, NTHREADS);
        if (warp == 11) return;
        uint32_t r = 1;
        for (int it = 0;; it++) {
            __nanosleep(500);
            if (lane < NQ) asm volatile("ld.acquire.gpu.global.u32 %0, [%1];" : "=r"(r) : "l"(g_mref + lane) : "memory");
            if (__all_sync(~0u, r != 0)) break;
            if (it > SPIN_LIMIT) __trap();
        }
        if (lane < NQ) sts32(sb + SM_M + lane * 4, ~r);
        __syncwarp();
        if (lane == 0) { mbar_arrive(sb + SM_REF); TSE(7); }
        return;
    }

    const int grp = warp >> 2, cw = warp & 3;
    const int xp = lane & 7, mi = lane >> 3;
    const uint32_t offS1 = opaque(12288 + xp * 128 + ((mi ^ xp) << 4)), offS1x = opaque(offS1 ^ 64);
    const uint32_t offS0 = opaque(offS1 - 12288 + cw * 3072), offS0x = opaque(offS0 ^ 64);
    const uint32_t offT = opaque(mi * 3072 + xp * 128 + (((cw + 4 * grp) ^ xp) << 4)), offTx = opaque(offT ^ 64);
    const uint32_t offU = opaque(12288 + (mi % 3) * 1024 + xp * 128 + (((cw + 4 * (grp ^ (mi / 3))) ^ xp) << 4));
    const uint32_t offV = opaque(12288 + (1 + (mi & 1)) * 1024 + xp * 128 + (((cw + 4 * (grp ^ 1)) ^ xp) << 4));
    const int shl = opaque(9 * t), shl4 = opaque(9 * t + 4);
    const uint32_t pw = opaque((cw >> 1) * 512 + lane * 16 + (cw & 1) * 8), muw = opaque(1024 + t * 16 + cw * 4);
    const uint32_t prd = opaque(lane * 16), mur = opaque(1024 + t * 16), mof = g * 4;
    uint32_t pb0 = sb + SM_P + grp * 2 * PBUF;
    const uint32_t pbx = pb0 ^ (pb0 + PBUF);
    const bool odd = g & 1;
    const int barid = B_GRP + grp;
    const bool elected = cw == 3 && lane == 0;

    uint32_t qa[48];
    float r_lo, r_hi;
    bar_sync(B_QK, NTHREADS);
    {
        float rr[2][4] = {{0.f, 0.f, 0.f, 0.f}, {0.f, 0.f, 0.f, 0.f}};
#pragma unroll
        for (int kk = 0; kk < 12; kk++) {
            const uint4 v = lds128(sb + SM_QK + kk * 512 + lane * 16);
            qa[4 * kk] = v.x; qa[4 * kk + 1] = v.y; qa[4 * kk + 2] = v.z; qa[4 * kk + 3] = v.w;
            mma(rr[kk & 1], v.x, v.y, v.z, v.w, ONES, ONES);
        }
        r_lo = rr[0][0] + rr[1][0]; r_hi = rr[0][2] + rr[1][2];
    }
    if (threadIdx.x == 0) TS(1);

    float acc[6][4];
#pragma unroll
    for (int i = 0; i < 6; i++) acc[i][0] = acc[i][1] = acc[i][2] = acc[i][3] = 0.f;
    float m_lo = -INFINITY, m_hi = -INFINITY, l_lo = 0.f, l_hi = 0.f;
    float cm[4] = {0.f, 0.f, 0.f, 0.f};
    uint32_t xt[6][4], yt[6]; uint4 pa, pb, mv;
    uint4* dst = reinterpret_cast<uint4*>(reinterpret_cast<char*>(g_acc) + acc_line(g >> 1, warp) + (lane & 7) * 16);
    asm volatile("" : "+l"(dst));
    const uint32_t xof = __shfl_sync(~0u, 512 - lane * 8, lane);
    uint32_t ref_lo = 0, ref_hi = 0;
    const uint32_t mad = __shfl_sync(~0u, sb + SM_M + mof, lane);
    uint32_t st = sb + SM_STAGES + grp * STAGE;
    int s = grp; uint32_t ph = 0;
    while (true) {
        mbar_wait(sb + SM_BAR + s * 8, ph);
        PH(0, 0);
        const uint32_t stop = lds32(sb + SM_FLAG + s * 4);
        float sc[2][4], gr[4][4], sx[4];
#pragma unroll
        for (int e = 0; e < 4; e++) sc[0][e] = sc[1][e] = gr[0][e] = gr[1][e] = gr[2][e] = gr[3][e] = sx[e] = 0.f;
#pragma unroll
        for (int qq = 0; qq < 6; qq++) {
            uint32_t x[4], y[4];
            ldsm4(x, st + (qq & 1 ? offS0x : offS0) + (qq >> 1) * 1024);
            ldsm4(y, st + (qq & 1 ? offS1x : offS1) + (qq >> 1) * 1024);
#pragma unroll
            for (int e = 0; e < 4; e++) x[e] = hadd2(x[e], y[e]);
            mma8(gr[0], x[0], x[1], x[0]);
            mma8(gr[1], x[0], x[1], x[1]);
            mma(sx, x[0], x[1], x[2], x[3], ONES, ONES);
            mma8(gr[GR4 ? 2 : 0], x[2], x[3], x[2]);
            mma8(gr[GR4 ? 3 : 1], x[2], x[3], x[3]);
            mma(sc[0], qa[8 * qq], qa[8 * qq + 1], qa[8 * qq + 2], qa[8 * qq + 3], x[0], x[1]);
            mma(sc[1], qa[8 * qq + 4], qa[8 * qq + 5], qa[8 * qq + 6], qa[8 * qq + 7], x[2], x[3]);
        }
        ldsm4t(yt, st + offU);
        ldsm2t(yt + 4, st + offV);
#pragma unroll
        for (int i = 0; i < 6; i++) ldsm4t(xt[i], st + (i < 3 ? offT : offTx) + (i % 3) * 1024);

        const float mu = (sx[0] + sx[2]) * (1.f / C), ss = GR4 ? (odd ? (gr[0][1] + gr[1][3]) + (gr[2][1] + gr[3][3]) : (gr[0][0] + gr[1][2]) + (gr[2][0] + gr[3][2])) : (odd ? gr[0][1] + gr[1][3] : gr[0][0] + gr[1][2]);
        const float rs = rsq(fmaxf(fmaf(-mu, mu, fmaf(ss, 1.f / C, 1e-5f)), 1e-5f));
        const float mu0 = __shfl_sync(~0u, mu, shl), mu1 = __shfl_sync(~0u, mu, shl4);
        const float rs0 = __shfl_sync(~0u, rs, shl), rs1 = __shfl_sync(~0u, rs, shl4);
        const float u0 = fmaf(-mu0, r_lo, sc[0][0] + sc[1][0]), u1 = fmaf(-mu1, r_lo, sc[0][1] + sc[1][1]);
        const float u2 = fmaf(-mu0, r_hi, sc[0][2] + sc[1][2]), u3 = fmaf(-mu1, r_hi, sc[0][3] + sc[1][3]);
        const float d0 = fmaf(u0, rs0, -m_lo), d1 = fmaf(u1, rs1, -m_lo), d2 = fmaf(u2, rs0, -m_hi), d3 = fmaf(u3, rs1, -m_hi);
        PH(1, u(d0 + d2));
        float p0 = ex2(d0), p1 = ex2(d1), p2 = ex2(d2), p3 = ex2(d3);
        sts64(pb0 + pw, pack2(p0 * rs0, p1 * rs1), pack2(p2 * rs0, p3 * rs1));
        if (lane < 4) sts32(pb0 + muw, pack2(mu0, mu1));
        asm volatile("{.reg .pred p; setp.ne.u32 p, %2, 0; @p ld.shared.b32 %0, [%3]; @p ld.shared.b32 %1, [%3+32];}" : "+r"(ref_lo), "+r"(ref_hi) : "r"(stop & 1), "r"(mad) : "memory");
        const bool over = bar_any(barid, 128, fmaxf(fmaxf(d0, d1), fmaxf(d2, d3)) > LAZY);
        PH(3, 0);
        pa = lds128(pb0 + prd); pb = lds128(pb0 + prd + 512); mv = lds128(pb0 + mur);
        if (stop & 1) { l_lo += p0 + p1; l_hi += p2 + p3; break; }
        if (elected) mbar_arrive(sb + SM_BAR + (NS + s) * 8);
        if (__builtin_expect(over, 0)) {
            const float s0 = u0 * rs0, s1 = u1 * rs1, s2 = u2 * rs0, s3 = u3 * rs1;
            float xl = fmaxf(s0, s1), xh = fmaxf(s2, s3);
            xl = fmaxf(xl, __shfl_xor_sync(~0u, xl, 1)); xh = fmaxf(xh, __shfl_xor_sync(~0u, xh, 1));
            xl = fmaxf(xl, __shfl_xor_sync(~0u, xl, 2)); xh = fmaxf(xh, __shfl_xor_sync(~0u, xh, 2));
            if (t < 2) sts32(sb + SM_MX + grp * 256 + ((g + 8 * t) * 4 + cw) * 4, u(t ? xh : xl));
            bar_sync(B_MAX + grp, 128);
            const uint4 ml4 = lds128(sb + SM_MX + grp * 256 + g * 16), mh4 = lds128(sb + SM_MX + grp * 256 + g * 16 + 128);
            const float nl = fmaxf(fmaxf(fmaxf(f(ml4.x), f(ml4.y)), fmaxf(f(ml4.z), f(ml4.w))), m_lo);
            const float nh = fmaxf(fmaxf(fmaxf(f(mh4.x), f(mh4.y)), fmaxf(f(mh4.z), f(mh4.w))), m_hi);
            p0 = ex2(s0 - nl); p1 = ex2(s1 - nl); p2 = ex2(s2 - nh); p3 = ex2(s3 - nh);
            sts64(pb0 + pw, pack2(p0 * rs0, p1 * rs1), pack2(p2 * rs0, p3 * rs1));
            const float al = ex2(m_lo - nl), ah = ex2(m_hi - nh);
            m_lo = nl; m_hi = nh;
            l_lo *= al; l_hi *= ah; cm[0] *= al; cm[2] *= ah;
#pragma unroll
            for (int i = 0; i < 6; i++) { acc[i][0] *= al; acc[i][1] *= al; acc[i][2] *= ah; acc[i][3] *= ah; }
            bar_sync(B_MAX + grp, 128);
            pa = lds128(pb0 + prd); pb = lds128(pb0 + prd + 512);
        }
        l_lo += p0 + p1; l_hi += p2 + p3;
#pragma unroll
        for (int i = 0; i < 6; i++) mma(acc[i], pa.x, pa.y, pa.z, pa.w, hadd2v(xt[i][0], yt[i]), hadd2v(xt[i][1], yt[i]));
        mma(cm, pa.x, pa.y, pa.z, pa.w, mv.x, mv.y);
#pragma unroll
        for (int i = 0; i < 6; i++) mma(acc[i], pb.x, pb.y, pb.z, pb.w, hadd2v(xt[i][2], yt[i]), hadd2v(xt[i][3], yt[i]));
        mma(cm, pb.x, pb.y, pb.z, pb.w, mv.z, mv.w);
        PH(4, u(acc[5][0]));
        if (stop) {
            float a = l_lo + __shfl_xor_sync(~0u, l_lo, 1), c = l_hi + __shfl_xor_sync(~0u, l_hi, 1);
            a += __shfl_xor_sync(~0u, a, 2); c += __shfl_xor_sync(~0u, c, 2);
            const uint32_t m = u((t ? m_hi : m_lo) + lg2(fmaxf(t ? c : a, 1.f)));
            if (t < 2) asm volatile("red.relaxed.gpu.global.max.u32 [%0], %1;" ::"l"(g_mmax + g + 8 * t), "r"(m >> 31 ? ~m : m | 0x80000000u) : "memory");
        }
        pb0 ^= pbx;
        s += 2;
        st += 2 * STAGE;
        if (s >= NS) { s -= NS; ph ^= 1; st -= NS * STAGE; }
        asm volatile("" : "+r"(st));
    }
    const float al = ex2(m_lo - f(ref_lo)), ah = ex2(m_hi - f(ref_hi));
    mma(cm, pa.x, pa.y, pa.z, pa.w, mv.x, mv.y);
#pragma unroll
    for (int i = 3; i < 6; i++) mma(acc[i], pa.x, pa.y, pa.z, pa.w, hadd2v(xt[i][0], yt[i]), hadd2v(xt[i][1], yt[i]));
    mma(cm, pb.x, pb.y, pb.z, pb.w, mv.z, mv.w);
#pragma unroll
    for (int i = 3; i < 6; i++) mma(acc[i], pb.x, pb.y, pb.z, pb.w, hadd2v(xt[i][2], yt[i]), hadd2v(xt[i][3], yt[i]));
#pragma unroll
    for (int i = 0; i < 3; i++) mma(acc[i], pa.x, pa.y, pa.z, pa.w, hadd2v(xt[i][0], yt[i]), hadd2v(xt[i][1], yt[i]));
#pragma unroll
    for (int i = 0; i < 3; i++) mma(acc[i], pb.x, pb.y, pb.z, pb.w, hadd2v(xt[i][2], yt[i]), hadd2v(xt[i][3], yt[i]));
    if (threadIdx.x == grp * 128) TSE(2 + grp);
    if (threadIdx.x == grp * 128 + 96) TSX(2 + grp, u(acc[5][0]));

    const uint32_t xw = sb + SM_STAGES + grp * STAGE + cw * 768 + prd, xr = sb + SM_STAGES + (grp ^ 1) * STAGE + cw * 768 + prd;
    const float cl = -cm[0] * al, ch = -cm[2] * ah;
    uint32_t hl[6], hh[6];
#pragma unroll
    for (int i = 3; i < 6; i++) { hl[i] = packh(fmaf(acc[i][0], al, cl), fmaf(acc[i][1], al, cl)); hh[i] = packh(fmaf(acc[i][2], ah, ch), fmaf(acc[i][3], ah, ch)); }
    sts128(xw, hl[3], hl[4], hl[5], hh[3]);
    sts64(xw + xof, hh[4], hh[5]);
#pragma unroll
    for (int i = 0; i < 3; i++) { hl[i] = packh(fmaf(acc[i][0], al, cl), fmaf(acc[i][1], al, cl)); hh[i] = packh(fmaf(acc[i][2], ah, ch), fmaf(acc[i][3], ah, ch)); }
    const uint32_t w_lo = packh(l_lo * al, 1.f), w_hi = packh(l_hi * ah, 1.f);
    bar_sync(B_MERGE, 256);
    if (threadIdx.x == 224) TSX(4, 0);
    const uint4 o = lds128(xr);
    const uint2 o2 = lds64(xr + xof);
    red8h(dst, haddh(hl[0], o.x), haddh(hl[1], o.y), haddh(hl[2], o.z), w_lo);
    red8h(dst + ACC_HI / 16, haddh(hh[0], o.w), haddh(hh[1], o2.x), haddh(hh[2], o2.y), w_hi);
    if (threadIdx.x == 0) TSE(4);
    if (threadIdx.x == 224) TSX(9, 0);
}

typedef CUresult (*EncodeFn)(CUtensorMap*, CUtensorMapDataType, cuuint32_t, void*, const cuuint64_t*, const cuuint64_t*,
                             const cuuint32_t*, const cuuint32_t*, CUtensorMapInterleave, CUtensorMapSwizzle,
                             CUtensorMapL2promotion, CUtensorMapFloatOOBfill);

}

extern "C" void kernel_launch(void* const* d_in, const int* in_sizes, int n_in, void* d_out, int out_size) {
    const __nv_bfloat16* q = (const __nv_bfloat16*)d_in[0];
    char* f0 = (char*)d_in[1];
    char* f1 = (char*)d_in[2];
    const __nv_bfloat16* wq = (const __nv_bfloat16*)d_in[3];
    const __nv_bfloat16* wk = (const __nv_bfloat16*)d_in[4];
    const __nv_bfloat16* wv = (const __nv_bfloat16*)d_in[5];
    const __nv_bfloat16* wo = (const __nv_bfloat16*)d_in[6];

    static EncodeFn enc = nullptr;
    static int grid = 0;
    static Scratch* scr = nullptr;
    if (!enc) {
        void* fn = nullptr; cudaDriverEntryPointQueryResult qr;
        cudaGetDriverEntryPoint("cuTensorMapEncodeTiled", &fn, cudaEnableDefault, &qr);
        enc = (EncodeFn)fn;
        cudaGetSymbolAddress((void**)&scr, g_scratch);
        int dev = 0, sms = 0;
        cudaGetDevice(&dev);
        cudaDeviceGetAttribute(&sms, cudaDevAttrMultiProcessorCount, dev);
        grid = sms < MAXG ? sms : MAXG;
        cudaFuncSetAttribute(attn_main, cudaFuncAttributeMaxDynamicSharedMemorySize, SMEM_BYTES);
    }
    CUtensorMap m0, m1;
    {
        cuuint64_t dims[5] = {64, W1, 3, 2, W0};
        cuuint64_t str[4] = {2 * C * 2, 128, C * 2, (cuuint64_t)W0 * C * 2};
        cuuint32_t box[5] = {64, TP, 3, 2, 2}, es[5] = {1, 1, 1, 1, 1};
        enc(&m0, CU_TENSOR_MAP_DATA_TYPE_BFLOAT16, 5, f0, dims, str, box, es, CU_TENSOR_MAP_INTERLEAVE_NONE,
            CU_TENSOR_MAP_SWIZZLE_128B, CU_TENSOR_MAP_L2_PROMOTION_NONE, CU_TENSOR_MAP_FLOAT_OOB_FILL_NONE);
    }
    {
        cuuint64_t dims[4] = {64, W1, 3, W1};
        cuuint64_t str[3] = {C * 2, 128, (cuuint64_t)W1 * C * 2};
        cuuint32_t box[4] = {64, TP, 3, 1}, es[4] = {1, 1, 1, 1};
        enc(&m1, CU_TENSOR_MAP_DATA_TYPE_BFLOAT16, 4, f1, dims, str, box, es, CU_TENSOR_MAP_INTERLEAVE_NONE,
            CU_TENSOR_MAP_SWIZZLE_128B, CU_TENSOR_MAP_L2_PROMOTION_NONE, CU_TENSOR_MAP_FLOAT_OOB_FILL_NONE);
    }
    attn_main<<<grid, NTHREADS, SMEM_BYTES, cudaStreamPerThread>>>(f0, f1, q, wq, wk, scr, wv, wo, (__nv_bfloat16*)d_out, m0, m1);
}
```

```cpp
#include <cuda_runtime.h>
#include <cuda_bf16.h>
#include <cuda.h>
#include <stdint.h>
#include <stddef.h>

namespace {

constexpr int C = 192;
constexpr int NQ = 16;
constexpr int W0 = 512;
constexpr int W1 = 256;
constexpr int TP = 8;
constexpr int NT = W1 * W1 / TP;
constexpr int STAGE = TP * 5 * C * 2;
#define NS 14
#define D0 3
#define D1 2
#define NRAMP 5
#define TA (p ? NT : 100 + 6 * b)
#define QSLEEP 700
#define WSL 32
#define MAXT 3000
#define REFT 1800
#define POLLN 1
#define PGAP 120
#define NPW 4
#define LAZY 12.f
#define RDEL 20
#define NST 4
#define NI 1
#define NPACE 5
#define T0 0
#define T1 1600
#define TG 960
static_assert(NST > D0, "the first dynamic tile index must not delay the start");
constexpr int NTHREADS = 384;
constexpr int MAXG = 132;
constexpr int NRD = NQ;
constexpr int NSRC = 12;
constexpr int SPIN_LIMIT = 1 << 22;

constexpr int SM_STAGES = 0;
constexpr int SM_P = NS * STAGE;
constexpr int PBUF = 1088;
constexpr int SM_QK = SM_P + 4 * PBUF;
constexpr int SM_MX = SM_QK + 6144;
constexpr int SM_M = SM_MX + 512;
constexpr int SM_BAR = SM_M + 64;
constexpr int SM_REF = SM_BAR + 16 * NS;
constexpr int SM_FLAG = SM_REF + 8;
constexpr int SM_TOTAL = SM_FLAG + 4 * NS;
constexpr int SMEM_BYTES = SM_TOTAL + 1024;
static_assert(SMEM_BYTES <= 232448, "smem");
constexpr int WROW = 400;
constexpr int RD_W = 0;
constexpr int RD_QN = 2 * C * WROW;
constexpr int RD_KQ = RD_QN + 6144;
constexpr int RD_B = RD_KQ + 7168;
constexpr int RD_B2 = 17 * 80;
constexpr int RD_BAR = RD_B + 2 * RD_B2;
constexpr int RD_A = RD_BAR + 64;
constexpr int RD_WS = RD_A + 12 * 6 * 512;
static_assert(RD_WS + 12 * 128 <= SM_TOTAL, "smem");

struct Scratch {
    uint4 acc[2816];
    uint4 qk[NSRC * 32];
    unsigned ctr[32];
    unsigned mmax[32];
    unsigned mref[32];
    uint4 acc_hi[4096];
};
__device__ __align__(131072) Scratch g_scratch;
#define g_acc (scr->acc)
#define g_qk (scr->qk)
#define g_ctr (scr->ctr)
#define g_mmax (scr->mmax)
#define g_mref (scr->mref)
#define g_ts (scr->ts)
#define g_tr (scr->tr)
#define TR(k, i) do {} while (0)
#define TS(i) do {} while (0)
#define TSD(i, dep) do {} while (0)
#define TSX(i, dep) do {} while (0)
#define TSP(i, dep) do {} while (0)
#define TSE(i) TS(i)
#define CK_(i, dep) do {} while (0)
#define PH(i, dep) do {} while (0)

__device__ __forceinline__ uint32_t s2u(const void* p) { return (uint32_t)__cvta_generic_to_shared(p); }
__device__ __forceinline__ void mbar_init(uint32_t a, int c) { asm volatile("mbarrier.init.shared::cta.b64 [%0], %1;" ::"r"(a), "r"(c) : "memory"); }
__device__ __forceinline__ void mbar_expect(uint32_t a, uint32_t b) { asm volatile("mbarrier.arrive.expect_tx.shared::cta.b64 _, [%0], %1;" ::"r"(a), "r"(b) : "memory"); }
__device__ __forceinline__ void mbar_arrive(uint32_t a) { asm volatile("mbarrier.arrive.shared::cta.b64 _, [%0];" ::"r"(a) : "memory"); }
__device__ __forceinline__ void mbar_wait(uint32_t a, uint32_t ph) {
    uint32_t ok; int it = 0;
    do {
        asm volatile("{.reg .pred p; mbarrier.try_wait.parity.shared::cta.b64 p, [%1], %2; selp.u32 %0,1,0,p;}" : "=r"(ok) : "r"(a), "r"(ph) : "memory");
        if (++it > SPIN_LIMIT) __trap();
    } while (!ok);
}
__device__ __forceinline__ bool elect() {
    uint32_t r; asm volatile("{.reg .pred p; elect.sync _|p, 0xffffffff; selp.u32 %0, 1, 0, p;}" : "=r"(r)); return r;
}
__device__ __forceinline__ void bar_sync(int id, int n) { asm volatile("bar.sync %0, %1;" ::"r"(id), "r"(n) : "memory"); }
__device__ __forceinline__ bool bar_any(int id, int n, bool c) {
    uint32_t r;
    asm volatile("{.reg .pred p, q; setp.ne.u32 q, %3, 0; bar.red.or.pred p, %1, %2, q; selp.u32 %0, 1, 0, p;}" : "=r"(r) : "r"(id), "r"(n), "r"((uint32_t)c) : "memory");
    return r;
}
__device__ __forceinline__ void bar_arrive(int id, int n) { asm volatile("bar.arrive %0, %1;" ::"r"(id), "r"(n) : "memory"); }
__device__ __forceinline__ void ldsm4(uint32_t* r, uint32_t a) {
    asm volatile("ldmatrix.sync.aligned.m8n8.x4.shared.b16 {%0,%1,%2,%3}, [%4];" : "=r"(r[0]), "=r"(r[1]), "=r"(r[2]), "=r"(r[3]) : "r"(a) : "memory");
}
__device__ __forceinline__ void ldsm4t(uint32_t* r, uint32_t a) {
    asm volatile("ldmatrix.sync.aligned.m8n8.x4.trans.shared.b16 {%0,%1,%2,%3}, [%4];" : "=r"(r[0]), "=r"(r[1]), "=r"(r[2]), "=r"(r[3]) : "r"(a) : "memory");
}
__device__ __forceinline__ void ldsm2t(uint32_t* r, uint32_t a) {
    asm volatile("ldmatrix.sync.aligned.m8n8.x2.trans.shared.b16 {%0,%1}, [%2];" : "=r"(r[0]), "=r"(r[1]) : "r"(a) : "memory");
}
__device__ __forceinline__ void mma(float* d, uint32_t a0, uint32_t a1, uint32_t a2, uint32_t a3, uint32_t b0, uint32_t b1) {
    asm("mma.sync.aligned.m16n8k16.row.col.f32.bf16.bf16.f32 {%0,%1,%2,%3}, {%4,%5,%6,%7}, {%8,%9}, {%0,%1,%2,%3};"
        : "+f"(d[0]), "+f"(d[1]), "+f"(d[2]), "+f"(d[3]) : "r"(a0), "r"(a1), "r"(a2), "r"(a3), "r"(b0), "r"(b1));
}
__device__ __forceinline__ void mmah(float* d, uint32_t a0, uint32_t a1, uint32_t a2, uint32_t a3, uint32_t b0, uint32_t b1) {
    asm("mma.sync.aligned.m16n8k16.row.col.f32.f16.f16.f32 {%0,%1,%2,%3}, {%4,%5,%6,%7}, {%8,%9}, {%0,%1,%2,%3};"
        : "+f"(d[0]), "+f"(d[1]), "+f"(d[2]), "+f"(d[3]) : "r"(a0), "r"(a1), "r"(a2), "r"(a3), "r"(b0), "r"(b1));
}
__device__ __forceinline__ void mma8(float* d, uint32_t a0, uint32_t a1, uint32_t b0) {
    asm("mma.sync.aligned.m16n8k8.row.col.f32.bf16.bf16.f32 {%0,%1,%2,%3}, {%4,%5}, {%6}, {%0,%1,%2,%3};"
        : "+f"(d[0]), "+f"(d[1]), "+f"(d[2]), "+f"(d[3]) : "r"(a0), "r"(a1), "r"(b0));
}
__device__ __forceinline__ uint32_t hadd2(uint32_t a, uint32_t b) {
    uint32_t r; asm("add.rn.bf16x2 %0, %1, %2;" : "=r"(r) : "r"(a), "r"(b)); return r;
}
__device__ __forceinline__ uint32_t pack2(float lo, float hi) {
    uint32_t r; asm("cvt.rn.bf16x2.f32 %0, %1, %2;" : "=r"(r) : "f"(hi), "f"(lo)); return r;
}
__device__ __forceinline__ uint32_t packh(float lo, float hi) {
    uint32_t r; asm("cvt.rn.f16x2.f32 %0, %1, %2;" : "=r"(r) : "f"(hi), "f"(lo)); return r;
}
__device__ __forceinline__ float bflo(uint32_t v) { return __uint_as_float(v << 16); }
__device__ __forceinline__ float bfhi(uint32_t v) { return __uint_as_float(v & 0xffff0000u); }
__device__ __forceinline__ float ex2(float x) { float r; asm("ex2.approx.ftz.f32 %0, %1;" : "=f"(r) : "f"(x)); return r; }
__device__ __forceinline__ void sts128(uint32_t a, uint32_t x, uint32_t y, uint32_t z, uint32_t w) {
    asm volatile("st.shared.v4.b32 [%0], {%1,%2,%3,%4};" ::"r"(a), "r"(x), "r"(y), "r"(z), "r"(w) : "memory");
}
__device__ __forceinline__ void sts64(uint32_t a, uint32_t x, uint32_t y) {
    asm volatile("st.shared.v2.b32 [%0], {%1,%2};" ::"r"(a), "r"(x), "r"(y) : "memory");
}
__device__ __forceinline__ void sts32(uint32_t a, uint32_t x) { asm volatile("st.shared.b32 [%0], %1;" ::"r"(a), "r"(x) : "memory"); }
__device__ __forceinline__ uint4 lds128(uint32_t a) {
    uint4 v; asm volatile("ld.shared.v4.b32 {%0,%1,%2,%3}, [%4];" : "=r"(v.x), "=r"(v.y), "=r"(v.z), "=r"(v.w) : "r"(a) : "memory"); return v;
}
__device__ __forceinline__ uint2 lds64(uint32_t a) {
    uint2 v; asm volatile("ld.shared.v2.b32 {%0,%1}, [%2];" : "=r"(v.x), "=r"(v.y) : "r"(a) : "memory"); return v;
}
__device__ __forceinline__ uint32_t haddh(uint32_t a, uint32_t b) {
    uint32_t r; asm("add.rn.f16x2 %0, %1, %2;" : "=r"(r) : "r"(a), "r"(b)); return r;
}
__device__ __forceinline__ uint32_t lds32(uint32_t a) { uint32_t v; asm volatile("ld.shared.b32 %0, [%1];" : "=r"(v) : "r"(a) : "memory"); return v; }
__device__ __forceinline__ int grab_tile(unsigned* ctr) {
    int v; asm volatile("atom.relaxed.gpu.global.inc.u32 %0, [%1], 0x7fffffff;" : "=r"(v) : "l"(ctr) : "memory"); return v;
}
__device__ __forceinline__ uint32_t opaque(uint32_t v) { uint32_t r; asm volatile("mov.b32 %0, %1;" : "=r"(r) : "r"(v)); return r; }
__device__ __forceinline__ int laneid() { int r; asm volatile("mov.u32 %0, %%laneid;" : "=r"(r)); return r; }
__device__ __forceinline__ unsigned clock32() { unsigned c; asm volatile("mov.u32 %0, %%clock;" : "=r"(c)); return c; }
__device__ __forceinline__ float rsq(float x) { float r; asm("rsqrt.approx.ftz.f32 %0, %1;" : "=f"(r) : "f"(x)); return r; }
__device__ __forceinline__ float rcp(float x) { float r; asm("rcp.approx.ftz.f32 %0, %1;" : "=f"(r) : "f"(x)); return r; }
__device__ __forceinline__ float lg2(float x) { float r; asm("lg2.approx.ftz.f32 %0, %1;" : "=f"(r) : "f"(x)); return r; }
__device__ __forceinline__ float f(uint32_t v) { return __uint_as_float(v); }
__device__ __forceinline__ uint32_t u(float v) { return __float_as_uint(v); }

constexpr uint32_t ONES = 0x3F803F80u;
constexpr float QSCALE = 0.07216878364870322f * 1.4426950408889634f;

__device__ __forceinline__ void issue_tile(const CUtensorMap* m0, const CUtensorMap* m1, uint32_t sb, int s, int tl, uint64_t pol) {
    const uint32_t full = sb + SM_BAR + s * 8, dst = sb + SM_STAGES + s * STAGE;
    const int par = tl * TP, y = par >> 8, x = par & 255;
    asm volatile("cp.async.bulk.tensor.5d.shared::cluster.global.mbarrier::complete_tx::bytes.L2::cache_hint [%0], [%1, {%3,%4,%3,%3,%5}], [%2], %6;"
                 ::"r"(dst), "l"(m0), "r"(full), "r"(0), "r"(x), "r"(2 * y), "l"(pol) : "memory");
    asm volatile("cp.async.bulk.tensor.4d.shared::cluster.global.mbarrier::complete_tx::bytes.L2::cache_hint [%0], [%1, {%3,%4,%3,%5}], [%2], %6;"
                 ::"r"(dst + TP * 4 * C * 2), "l"(m1), "r"(full), "r"(0), "r"(x), "r"(y), "l"(pol) : "memory");
}

__device__ __forceinline__ void prefetch_l2(const void* a, int n) { asm volatile("cp.async.bulk.prefetch.L2.global [%0], %1;" ::"l"(a), "r"(n) : "memory"); }
__device__ __forceinline__ uint4 ldg_relaxed(const uint4* p) {
    uint4 v; asm volatile("ld.relaxed.gpu.global.v4.u32 {%0,%1,%2,%3}, [%4];" : "=r"(v.x), "=r"(v.y), "=r"(v.z), "=r"(v.w) : "l"(p) : "memory"); return v;
}
__device__ __forceinline__ uint32_t ldg_relaxed32(const void* p) {
    uint32_t v; asm volatile("ld.relaxed.gpu.global.u32 %0, [%1];" : "=r"(v) : "l"(p) : "memory"); return v;
}
__device__ __forceinline__ void stg_relaxed(uint4* p, uint32_t x, uint32_t y, uint32_t z, uint32_t w) {
    asm volatile("st.relaxed.gpu.global.v4.u32 [%0], {%1,%2,%3,%4};" ::"l"(p), "r"(x), "r"(y), "r"(z), "r"(w) : "memory");
}
__device__ __forceinline__ void stg_relaxed32(void* p, uint32_t x) { asm volatile("st.relaxed.gpu.global.u32 [%0], %1;" ::"l"(p), "r"(x) : "memory"); }
__device__ __forceinline__ bool has(const uint4& v, uint32_t m) { return v.x == m || v.y == m || v.z == m || v.w == m; }
__device__ __forceinline__ uint32_t hadd2v(uint32_t a, uint32_t b) {
    uint32_t r; asm volatile("add.rn.bf16x2 %0, %1, %2;" : "=r"(r) : "r"(a), "r"(b)); return r;
}

__device__ __forceinline__ void red8h(uint4* p, uint32_t x, uint32_t y, uint32_t z, uint32_t w) {
    asm volatile("red.relaxed.gpu.global.add.noftz.v4.f16x2 [%0], {%1,%2,%3,%4};" ::"l"(p), "r"(x), "r"(y), "r"(z), "r"(w) : "memory");
}
__device__ __forceinline__ uint4 lds128v(uint32_t a) {
    uint4 v; asm volatile("ld.volatile.shared.v4.b32 {%0,%1,%2,%3}, [%4];" : "=r"(v.x), "=r"(v.y), "=r"(v.z), "=r"(v.w) : "r"(a) : "memory"); return v;
}
__device__ __forceinline__ uint32_t brow(int r) { return RD_B + r * 80 + (r >> 3) * 64; }

constexpr int ACC_HI = 65536;
static_assert(offsetof(Scratch, acc_hi) <= ACC_HI && offsetof(Scratch, acc_hi) + sizeof(Scratch::acc_hi) >= ACC_HI + 32768, "scratch");
__device__ __forceinline__ uint32_t acc_line(int s, int k) {
    return (k >> 2) * 16384 + (k & 2) * 6144 + (k & 1) * 1024 + (s & 1) * 256 + (s & 2) * 1024 + (s >> 2) * ACC_HI;
}

__device__ __forceinline__ int first_row() { return (blockIdx.x & 14) ^ 8; }

enum { B_QK = 1, B_QN = 2, B_GRP = 3  , B_Q = 5, B_MERGE = 6, B_ALL = 7, B_MAX = 8  , B_WARP = 10, B_SLOW = 12, B_PARK = 13, B_CLEAN = 14, B_RDY = 15 };

__device__ __noinline__ void slow_rows(const char* __restrict__ f0, const char* __restrict__ f1, const __nv_bfloat16* __restrict__ q,
                                       const __nv_bfloat16* __restrict__ wq, const __nv_bfloat16* __restrict__ wk, const uint32_t sb)
{
    const int warp = threadIdx.x >> 5, lane = threadIdx.x & 31;
    float* const sm = reinterpret_cast<float*>(__cvta_shared_to_generic(sb + RD_W));
    for (int i = threadIdx.x; i < 2 * C; i += 128) sm[i] = __bfloat162float(q[first_row() * C + i]);
    bar_sync(B_SLOW, 128);
#pragma unroll 1
    for (int j = threadIdx.x; j < 2 * C; j += 128) {
        const float* const x = sm + j / C * C;
        float mu = 0.f, var = 0.f, s = 0.f;
#pragma unroll 1
        for (int i = 0; i < C; i++) mu += x[i];
        mu *= 1.f / C;
#pragma unroll 4
        for (int i = 0; i < C; i++) { var = fmaf(x[i] - mu, x[i] - mu, var); s = fmaf(x[i] - mu, __bfloat162float(wq[i * C + j % C]), s); }
        sm[4 * C + j] = s * rsq(var * (1.f / C) + 1e-5f);
    }
    bar_sync(B_SLOW, 128);
#pragma unroll 1
    for (int j = threadIdx.x; j < 2 * C; j += 128) {
        float s = 0.f;
#pragma unroll 4
        for (int i = 0; i < C; i++) s = fmaf(sm[4 * C + j / C * C + i], __bfloat162float(wk[j % C * C + i]), s);
        sm[j] = s * QSCALE;
    }
    bar_sync(B_SLOW, 128);
    float k[2][6], a[2][6], m[2], l[2];
#pragma unroll
    for (int r = 0; r < 2; r++) {
        m[r] = -INFINITY; l[r] = 0.f;
#pragma unroll
        for (int i = 0; i < 6; i++) { k[r][i] = sm[r * C + 64 * (i >> 1) + 2 * lane + (i & 1)]; a[r][i] = 0.f; }
    }
#pragma unroll 1
    for (int par = warp; par < W1 * W1; par += 4) {
        const uint32_t* p0 = reinterpret_cast<const uint32_t*>(f0 + (size_t)((par >> 8) * 2 * W0 + (par & 255) * 2) * (C * 2)) + lane;
        const uint32_t* p1 = reinterpret_cast<const uint32_t*>(f1 + (size_t)par * (C * 2)) + lane;
        uint32_t v[4][3];
#pragma unroll
        for (int i = 0; i < 3; i++)
#pragma unroll
            for (int j = 0; j < 4; j++) v[j][i] = hadd2(__ldg(p0 + ((j >> 1) * W0 + (j & 1)) * (C / 2) + 32 * i), __ldg(p1 + 32 * i));
#pragma unroll
        for (int j = 0; j < 4; j++) {
            float x[6], s1 = 0.f, s2 = 0.f, d[2] = {0.f, 0.f};
#pragma unroll
            for (int i = 0; i < 3; i++) { x[2 * i] = bflo(v[j][i]); x[2 * i + 1] = bfhi(v[j][i]); s1 += x[2 * i] + x[2 * i + 1]; }
#pragma unroll
            for (int o = 1; o < 32; o <<= 1) s1 += __shfl_xor_sync(~0u, s1, o);
#pragma unroll
            for (int i = 0; i < 6; i++) {
                x[i] -= s1 * (1.f / C); s2 = fmaf(x[i], x[i], s2);
#pragma unroll
                for (int r = 0; r < 2; r++) d[r] = fmaf(x[i], k[r][i], d[r]);
            }
#pragma unroll
            for (int o = 1; o < 32; o <<= 1) {
                s2 += __shfl_xor_sync(~0u, s2, o);
#pragma unroll
                for (int r = 0; r < 2; r++) d[r] += __shfl_xor_sync(~0u, d[r], o);
            }
            const float rs = rsq(s2 * (1.f / C) + 1e-5f);
#pragma unroll
            for (int r = 0; r < 2; r++) {
                const float nm = fmaxf(m[r], d[r] * rs), al = ex2(m[r] - nm), p = ex2(d[r] * rs - nm);
                m[r] = nm; l[r] = fmaf(l[r], al, p);
#pragma unroll
                for (int i = 0; i < 6; i++) a[r][i] = fmaf(a[r][i], al, x[i] * (p * rs));
            }
        }
    }
    bar_sync(B_SLOW, 128);
#pragma unroll
    for (int r = 0; r < 2; r++) {
        float* const o = sm + ((r * 4 + warp) * 32 + lane) * 8;
#pragma unroll
        for (int i = 0; i < 6; i++) o[i] = a[r][i];
        o[6] = l[r]; o[7] = m[r];
    }
    bar_sync(B_SLOW, 128);
    if (warp < 2) {
        const int r = warp;
        const float* const o = sm + (r * 128 + lane) * 8;
        float M = o[7], x[7] = {0.f, 0.f, 0.f, 0.f, 0.f, 0.f, 0.f};
#pragma unroll
        for (int w = 1; w < 4; w++) M = fmaxf(M, o[256 * w + 7]);
#pragma unroll
        for (int w = 0; w < 4; w++) {
            const float e = ex2(o[256 * w + 7] - M);
#pragma unroll
            for (int i = 0; i < 7; i++) x[i] = fmaf(o[256 * w + i], e, x[i]);
        }
        const float rl = 1.f / x[6];
        sts128(sb + RD_B2 + brow(8 * (lane >> 4) + 4 * r + (lane & 3)) + ((lane >> 2) & 3) * 16, packh(x[0] * rl, x[1] * rl), packh(x[2] * rl, x[3] * rl), packh(x[4] * rl, x[5] * rl), lane ? 0u : 0x3C00u);
    }
}

template <bool FIRST>
__device__ __forceinline__ void project(const uint32_t ar, const uint32_t br, const bool hi, const float ws0, const float ws1, const float qv0, const float qv1,
                                        __nv_bfloat16* op0, __nv_bfloat16* op1, Scratch* scr)
{
    uint4 wa[3][6], x[4];
#pragma unroll
    for (int i = 0; i < 18; i++) wa[i / 6][i % 6] = lds128v(ar + i * 512);
    if (FIRST) { bar_arrive(B_CLEAN, NTHREADS); bar_sync(B_RDY, 192); }
    else bar_sync(B_SLOW, 128);
    if (FIRST && threadIdx.x == 0) TSX(8, 0);
#pragma unroll
    for (int j = 0; j < 4; j++) x[j] = lds128v(br + 16 * j);
    float o[7][4];
#pragma unroll
    for (int j = 0; j < 7; j++) o[j][0] = o[j][1] = o[j][2] = o[j][3] = 0.f;
#pragma unroll
    for (int i = 0; i < 2; i++) {
        mmah(o[6], 0x3C00u, 0x3C00u, 0x3C00u, 0x3C00u, x[2 * i].w, x[2 * i + 1].w);
#pragma unroll
        for (int n = 0; n < 3; n++) mmah(o[2 * n + i], wa[n][2 * i].x, wa[n][2 * i].y, wa[n][2 * i].z, wa[n][2 * i].w, x[2 * i].x, x[2 * i].y);
#pragma unroll
        for (int n = 0; n < 3; n++) mmah(o[2 * n + 1 - i], wa[n][2 * i + 1].x, wa[n][2 * i + 1].y, wa[n][2 * i + 1].z, wa[n][2 * i + 1].w, x[2 * i + 1].x, x[2 * i + 1].y);
#pragma unroll
        for (int n = 0; n < 3; n++) mmah(o[2 * n + i], wa[n][4 + i].x, wa[n][4 + i].y, wa[n][4 + i].z, wa[n][4 + i].w, x[2 * i].z, x[2 * i + 1].z);
    }
    const float L = o[6][0] + o[6][1], r = rcp(L);
    const float y0 = hi ? (o[2][0] + o[2][3]) + (o[3][0] + o[3][3]) : (o[0][0] + o[0][3]) + (o[1][0] + o[1][3]), y1 = (o[4][0] + o[4][3]) + (o[5][0] + o[5][3]);
    const uint32_t y = pack2(fmaf(y0, r * ws0, qv0), fmaf(y1, r * ws1, qv1));
    asm volatile("{.reg .b16 l, h; mov.b32 {l, h}, %2; st.global.b16 [%0], l; st.global.b16 [%1], h;}" ::"l"(op0), "l"(op1), "r"(y) : "memory");
    if (FIRST && threadIdx.x == 0) TSD(11, y);
    if (FIRST)
        asm volatile("{.reg .pred p; .reg .f32 a; abs.f32 a, %1; setp.ge.f32 p, %0, 0f3B000000; setp.le.and.f32 p, %0, 0f45000000, p; setp.lt.and.f32 p, a, 0f7F800000, p;"
                     " vote.sync.all.pred p, p, 0xffffffff; @p exit;}" ::"f"(L), "f"(y0) : "memory");
}

__device__ __forceinline__ void reducer(const char* __restrict__ f0, const char* __restrict__ f1, const __nv_bfloat16* __restrict__ q, const __nv_bfloat16* __restrict__ wq, const __nv_bfloat16* __restrict__ wk,
                                        Scratch* scr, const __nv_bfloat16* __restrict__ wv, const __nv_bfloat16* __restrict__ wo,
                                        __nv_bfloat16* __restrict__ out, const uint32_t sb, const int GS)
{
    const int warp = threadIdx.x >> 5, lane = threadIdx.x & 31, b = blockIdx.x;
    const int g = lane >> 2, t = lane & 3;
    char* const ap = reinterpret_cast<char*>(g_acc);
    if (threadIdx.x == 256) TS(0);
    if (b < NSRC && warp < 8) {
        const uint32_t wqs = sb + RD_W, wbar = sb + RD_BAR;
        const int hr = lane >> 4, qt = (lane >> 2) & 3, sub = lane & 3;
        const uint32_t* qp = reinterpret_cast<const uint32_t*>(q + (warp + 8 * hr) * C + 48 * qt + 6 * sub);
        uint32_t qw[6];
#pragma unroll
        for (int j = 0; j < 3; j++) { qw[j] = __ldg(qp + j); qw[3 + j] = __ldg(qp + 12 + j); }
        if (lane == 0) { mbar_init(wbar + warp * 8, 1); asm volatile("fence.mbarrier_init.release.cluster;" ::: "memory"); mbar_expect(wbar + warp * 8, 9216);
            asm volatile("cp.async.bulk.shared::cluster.global.mbarrier::complete_tx::bytes [%0], [%1], 9216, [%2];"
                         ::"r"(wqs + warp * 9232), "l"(wq + 24 * warp * C), "r"(wbar + warp * 8) : "memory");
        }
        __syncwarp();
        if (threadIdx.x == 0) TSP(2, 0);
        float e[12];
#pragma unroll
        for (int j = 0; j < 6; j++) { e[2 * j] = bflo(qw[j]); e[2 * j + 1] = bfhi(qw[j]); }
        float sm = ((e[0] + e[1]) + (e[2] + e[3])) + ((e[4] + e[5]) + (e[6] + e[7])) + ((e[8] + e[9]) + (e[10] + e[11]));
#pragma unroll
        for (int o = 1; o < 16; o <<= 1) sm += __shfl_xor_sync(~0u, sm, o);
        if (threadIdx.x == 0) TSP(5, u(sm));
        float v0 = 0.f, v1 = 0.f;
#pragma unroll
        for (int j = 0; j < 12; j++) e[j] -= sm * (1.f / C);
#pragma unroll
        for (int j = 0; j < 6; j++) { v0 = fmaf(e[j], e[j], v0); v1 = fmaf(e[6 + j], e[6 + j], v1); }
        v0 += v1;
#pragma unroll
        for (int o = 1; o < 16; o <<= 1) v0 += __shfl_xor_sync(~0u, v0, o);
        const float rq = rsq(v0 * (1.f / C) + 1e-5f);
#pragma unroll
        for (int j = 0; j < 6; j++)
            sts32(sb + RD_QN + (3 * sub + (j >> 1)) * 512 + (4 * warp + qt) * 16 + (2 * (j & 1) + hr) * 4, pack2(e[j] * rq, e[6 + j] * rq));
        if (threadIdx.x == 0) TSP(8, 0);
        uint32_t wkf[2][3];
#pragma unroll
        for (int i = 0; i < 2; i++)
#pragma unroll
            for (int j = 0; j < 3; j++) wkf[i][j] = __ldg(reinterpret_cast<const uint32_t*>(wk + (16 * b + 8 * i + g) * C + 24 * warp + 8 * j + 2 * t));
        bar_sync(B_QN, 256);
        float acc[2][3][4];
#pragma unroll
        for (int i = 0; i < 3; i++)
#pragma unroll
            for (int e = 0; e < 4; e++) acc[0][i][e] = acc[1][i][e] = 0.f;
        const uint32_t ba = wqs + (lane & 7) * 9232 + (lane >> 3) * 384 + 48 * warp;
        uint4 a[12];
#pragma unroll
        for (int kk = 0; kk < 12; kk++) a[kk] = lds128(sb + RD_QN + kk * 512 + lane * 16);
        mbar_wait(wbar + (lane & 7) * 8, 0);
        __syncwarp();
        if (threadIdx.x == 0) TSP(4, 0);
#pragma unroll
        for (int kp = 0; kp < 6; kp++)
#pragma unroll
            for (int i = 0; i < 3; i++) {
                uint32_t bb[4];
                ldsm4t(bb, ba + kp * 1536 + i * 16);
                mma(acc[0][i], a[2 * kp].x, a[2 * kp].y, a[2 * kp].z, a[2 * kp].w, bb[0], bb[1]);
                mma(acc[1][i], a[2 * kp + 1].x, a[2 * kp + 1].y, a[2 * kp + 1].z, a[2 * kp + 1].w, bb[2], bb[3]);
            }
        if (threadIdx.x == 0) TSP(7, u(acc[1][2][3]));
        float kq[2][4] = {{0.f, 0.f, 0.f, 0.f}, {0.f, 0.f, 0.f, 0.f}};
#pragma unroll
        for (int j = 0; j < 3; j++) {
            const uint32_t a0 = pack2(acc[0][j][0] + acc[1][j][0], acc[0][j][1] + acc[1][j][1]), a1 = pack2(acc[0][j][2] + acc[1][j][2], acc[0][j][3] + acc[1][j][3]);
            mma8(kq[0], a0, a1, wkf[0][j]);
            mma8(kq[1], a0, a1, wkf[1][j]);
        }
        if (warp < 7) {
            sts128(sb + RD_KQ + warp * 1024 + lane * 16, u(kq[0][0]), u(kq[0][1]), u(kq[0][2]), u(kq[0][3]));
            sts128(sb + RD_KQ + warp * 1024 + 512 + lane * 16, u(kq[1][0]), u(kq[1][1]), u(kq[1][2]), u(kq[1][3]));
            bar_arrive(B_Q, 256);
        } else {
            bar_sync(B_Q, 256);
#pragma unroll
            for (int w = 0; w < 7; w++)
#pragma unroll
                for (int i = 0; i < 2; i++) {
                    const uint4 o = lds128(sb + RD_KQ + w * 1024 + i * 512 + lane * 16);
                    kq[i][0] += f(o.x); kq[i][1] += f(o.y); kq[i][2] += f(o.z); kq[i][3] += f(o.w);
                }
            stg_relaxed(g_qk + b * 32 + lane, ~pack2(kq[0][0] * QSCALE, kq[0][1] * QSCALE), ~pack2(kq[0][2] * QSCALE, kq[0][3] * QSCALE),
                        ~pack2(kq[1][0] * QSCALE, kq[1][1] * QSCALE), ~pack2(kq[1][2] * QSCALE, kq[1][3] * QSCALE));
            if (lane == 0) TS(10);
        }
    } else if (warp == 8 && !(b & 1)) {
#pragma unroll
        for (int i = 0; i < 2; i++) stg_relaxed(reinterpret_cast<uint4*>(ap + acc_line(b >> 1, 4 * i + (lane >> 3))) + (lane & 7), 0, 0, 0, 0);
        __threadfence();
    } else if (b >= NSRC) {
        if (b == NSRC && warp == 0) stg_relaxed32(g_mmax + lane, 0);
        const unsigned c0 = clock32();
        for (int it = 0; it < 8; it++) {
            __nanosleep(500);
            if (clock32() - c0 > 4400) break;
        }
    }
    bar_sync(B_ALL, NTHREADS);

#pragma unroll 1
    for (int r = 0; r < 3; r++) {
        uint4 v[8];
#pragma unroll
        for (int k = 0; k < 8; k++) {
            const int idx = (8 * r + k) * 384 + threadIdx.x;
            v[k] = __ldg(reinterpret_cast<const uint4*>(idx < 4608 ? wv : wo - C * C) + idx);
        }
#pragma unroll
        for (int k = 0; k < 8; k++) {
            const int idx = (8 * r + k) * 384 + threadIdx.x, row = idx / 24;
            sts128(sb + RD_W + row * WROW + (idx - 24 * row) * 16, v[k].x, v[k].y, v[k].z, v[k].w);
        }
    }
    bar_sync(B_ALL, NTHREADS);
    if (warp < 6) {
        const int col = 96 * (b & 1) + 16 * warp;
        float d[24][4];
#pragma unroll
        for (int i = 0; i < 24; i++) d[i][0] = d[i][1] = d[i][2] = d[i][3] = 0.f;
        const int mi = lane >> 3, r = lane & 7;
        const uint32_t aa = sb + RD_W + (C + (mi >> 1) * 8 + r) * WROW + (col + (mi & 1) * 8) * 2;
        const uint32_t ba = sb + RD_W + ((mi >> 1) * 8 + r) * WROW + (mi & 1) * 16;
#pragma unroll 1
        for (int kk = 0; kk < 12; kk++) {
            uint32_t a[4];
            ldsm4t(a, aa + kk * 16 * WROW);
#pragma unroll
            for (int i = 0; i < 12; i++) {
                uint32_t bb[4];
                ldsm4(bb, ba + i * 16 * WROW + kk * 32);
                mma(d[2 * i], a[0], a[1], a[2], a[3], bb[0], bb[1]);
                mma(d[2 * i + 1], a[0], a[1], a[2], a[3], bb[2], bb[3]);
            }
        }
        float c0 = 0.f, c1 = 0.f, m0 = 0.f, m1 = 0.f;
#pragma unroll
        for (int i = 0; i < 24; i++) { c0 += d[i][0] + d[i][1]; c1 += d[i][2] + d[i][3]; }
        c0 += __shfl_xor_sync(~0u, c0, 1); c1 += __shfl_xor_sync(~0u, c1, 1);
        c0 += __shfl_xor_sync(~0u, c0, 2); c1 += __shfl_xor_sync(~0u, c1, 2);
        c0 *= 1.f / C; c1 *= 1.f / C;
#pragma unroll
        for (int i = 0; i < 24; i++) {
            d[i][0] -= c0; d[i][1] -= c0; d[i][2] -= c1; d[i][3] -= c1;
            m0 = fmaxf(m0, fmaxf(fabsf(d[i][0]), fabsf(d[i][1]))); m1 = fmaxf(m1, fmaxf(fabsf(d[i][2]), fabsf(d[i][3])));
        }
        m0 = fmaxf(m0, __shfl_xor_sync(~0u, m0, 1)); m1 = fmaxf(m1, __shfl_xor_sync(~0u, m1, 1));
        m0 = fmaxf(m0, __shfl_xor_sync(~0u, m0, 2)); m1 = fmaxf(m1, __shfl_xor_sync(~0u, m1, 2));
        const uint32_t e0 = min(max(u(m0) >> 23, 12u), 254u), e1 = min(max(u(m1) >> 23, 12u), 254u);
        const float s0 = f((265u - e0) << 23), s1 = f((265u - e1) << 23);
        const bool k0 = fabsf(c0) < INFINITY, k1 = fabsf(c1) < INFINITY;
#pragma unroll
        for (int j = 0; j < 6; j++) {
            const int n[4] = {j < 4 ? j : 8 + 2 * j, j < 4 ? 4 + j : 12 + 2 * j, j < 4 ? 8 + j : 9 + 2 * j, j < 4 ? 12 + j : 13 + 2 * j};
            uint32_t a[2][4];
#pragma unroll
            for (int e = 0; e < 4; e++) {
                a[0][e] = k0 ? packh(d[n[e]][0] * s0, d[n[e]][1] * s0) : 0u;
                a[1][e] = k1 ? packh(d[n[e]][2] * s1, d[n[e]][3] * s1) : 0u;
            }
#pragma unroll
            for (int e = 0; e < 2; e++) sts128(sb + RD_A + ((2 * warp + e) * 6 + j) * 512 + lane * 16, a[e][0], a[e][1], a[e][2], a[e][3]);
        }
        sts32(sb + RD_WS + 2 * warp * 128 + lane * 4, k0 ? (e0 - 11u) << 23 : u(c0));
        sts32(sb + RD_WS + (2 * warp + 1) * 128 + lane * 4, k1 ? (e1 - 11u) << 23 : u(c1));
        if (warp < 4) bar_sync(B_PARK, 192); else bar_arrive(B_PARK, 192);
        if (threadIdx.x == 0) TSE(6);
    }
    if (warp >= 4) {
        if (threadIdx.x == 128) {
            uint32_t m;
            for (int it = 0;; it++) {
                const int left = NT - 2 * NST * GS - (int)ldg_relaxed32(g_ctr);
                m = ldg_relaxed32(g_mmax + b);
                if (left <= REFT && m) break;
                if (left <= 0) { m = 0x80000000u; break; }
                if (it > SPIN_LIMIT) __trap();
                __nanosleep(300);
            }
            if (b & 1) for (int it = 0;; it++) {
                uint32_t r;
                asm volatile("ld.acquire.gpu.global.u32 %0, [%1];" : "=r"(r) : "l"(g_mref + b - 1) : "memory");
                if (r) break;
                if (it > SPIN_LIMIT) __trap();
            }
            asm volatile("st.release.gpu.global.u32 [%0], %1;" ::"l"(g_mref + b), "r"(~u(f(m >> 31 ? m ^ 0x80000000u : ~m) + 8.f)) : "memory");
            TSE(7);
        }
        __syncwarp();
        if (warp == 4) {
            uint4* p0 = g_qk + min(b, NSRC - 1) * 32 + lane;
            unsigned* p1 = lane == 1 && b == NSRC ? g_ctr : g_mref + b;
            asm volatile("" : "+l"(p0), "+l"(p1));
            bar_arrive(B_CLEAN, NTHREADS);
            bar_sync(B_RDY, 192);
            *p0 = make_uint4(0, 0, 0, 0);
            *p1 = 0;
            return;
        }
        bar_sync(B_CLEAN, NTHREADS);
        if (warp >= 5 + NPW) return;
        const uint4* const pa = reinterpret_cast<const uint4*>(ap + acc_line(b >> 1, lane >> 3)) + (lane & 7);
        const uint32_t bw = opaque(sb + brow(lane & 7) + (lane >> 3) * 16);
        const uint32_t n0 = packh(0.f, (float)GS), nstart = packh(0.f, (float)POLLN);
        for (int it = 0; ldg_relaxed32(ap + acc_line(b >> 1, 0) + 12) < nstart; it++)
            if (it > SPIN_LIMIT) __trap();
        for (const unsigned c = clock32(); clock32() - c < (warp - 5) * PGAP;) {}
        for (int it = 0;; it++) {
            const uint4 a0 = ldg_relaxed(pa), b0 = ldg_relaxed(pa + 1024);
            if (it > SPIN_LIMIT) __trap();
            bar_sync(B_WARP, 32);
            asm volatile("{.reg .pred p, q; .reg .b32 a; setp.ge.u32 p, %5, %10; setp.ge.and.u32 p, %9, %10, p; vote.sync.all.pred q, p, 0xffffffff; selp.b32 a, %0, %1, p;"
                         " st.shared.v4.b32 [a], {%2,%3,%4,%5}; st.shared.v4.b32 [a + 704], {%6,%7,%8,%9}; @q bar.arrive 15, 192; @q exit;}"
                         ::"r"(bw), "r"(bw - (RD_B - RD_QN)), "r"(a0.x), "r"(a0.y), "r"(a0.z), "r"(a0.w), "r"(b0.x), "r"(b0.y), "r"(b0.z), "r"(b0.w), "r"(n0) : "memory");
        }
    }
    const uint32_t br = opaque(sb + brow(8 * (g & 1) + 2 * (g & 2) + t));
    const bool hi = t >= 2;
    const int oi = (first_row() + (t & 1)) * C + 96 * (b & 1) + 24 * warp + g;
    const float qv0 = __bfloat162float(q[oi + 4 * (t & 2)]), qv1 = __bfloat162float(q[oi + 16]);
    const float ws0 = f(lds32(sb + RD_WS + (3 * warp + (t >> 1)) * 128 + lane * 4)), ws1 = f(lds32(sb + RD_WS + (3 * warp + 2) * 128 + lane * 4));
    __nv_bfloat16* op0 = out + oi + 4 * (t & 2), * op1 = out + oi + 16;
    asm volatile("" : "+l"(op0), "+l"(op1));
    const uint32_t ar = sb + RD_A + warp * 18 * 512 + lane * 16;
    project<true>(ar, br, hi, ws0, ws1, qv0, qv1, op0, op1, scr);
    slow_rows(f0, f1, q, wq, wk, sb);
    project<false>(ar, br + RD_B2, hi, ws0, ws1, qv0, qv1, op0, op1, scr);
}

__global__ void __launch_bounds__(NTHREADS, 1)
attn_main(const char* __restrict__ f0, const char* __restrict__ f1,
          const __nv_bfloat16* __restrict__ q, const __nv_bfloat16* __restrict__ wq, const __nv_bfloat16* __restrict__ wk, Scratch* scr,
          const __nv_bfloat16* __restrict__ wv, const __nv_bfloat16* __restrict__ wo, __nv_bfloat16* __restrict__ out,
          const __grid_constant__ CUtensorMap m0, const __grid_constant__ CUtensorMap m1)
{
    extern __shared__ char smem_raw[];
    const uint32_t sb = (s2u(smem_raw) + 1023u) & ~1023u;
    const int G = gridDim.x - NRD;
    const int b = blockIdx.x - NRD;
    if (threadIdx.x == 0 && b >= 0 && f0 != nullptr) {
        const char* a = f0 + (uint32_t)(b * (4 * TP * C * 2) + (b >> 4) * (W0 * C * 2));
        prefetch_l2(a, 4 * TP * C * 2);
        prefetch_l2(a + W0 * C * 2, 4 * TP * C * 2);
        prefetch_l2(f1 + b * (2 * TP * C * 2), 2 * TP * C * 2);
        prefetch_l2((const char*)(b % (2 * WSL) < WSL ? wq : wk) + b % WSL * (C * C * 2 / WSL), C * C * 2 / WSL);
    }
    if (b < 0) { reducer(f0, f1, q, wq, wk, scr, wv, wo, out, sb, G); return; }
    const int warp = __shfl_sync(~0u, threadIdx.x >> 5, 0), lane = laneid();
    const int g = lane >> 2, t = lane & 3;

    if (warp >= 8) {
        if (warp < 10) {
            const int p = warp - 8;
            const unsigned c0 = clock32();
            const uint32_t sbp = opaque(sb), bar = sbp + SM_BAR + p * 8;
            uint64_t pol; asm volatile("createpolicy.fractional.L2::evict_first.b64 %0, 1.0;" : "=l"(pol));
            if (elect()) {
                if (p == 0) TS(0);
                asm volatile("prefetch.tensormap [%0];" ::"l"(p ? &m1 : &m0) : "memory");
#pragma unroll
                for (int n = 0; n < NI; n++) mbar_init(bar + n * 16, 2);
                asm volatile("fence.mbarrier_init.release.cluster;" ::: "memory");
#pragma unroll
                for (int n = 0; n < NI; n++) {
                    mbar_expect(bar + n * 16, STAGE);
                    issue_tile(&m0, &m1, sbp, p + 2 * n, 2 * b + p + 2 * n * G, pol);
                    TR(0, 2 * n + p);
                    sts32(sbp + SM_FLAG + (p + 2 * n) * 4, 0);
                    mbar_arrive(bar + n * 16);
                }
#pragma unroll
                for (int n = 0; n < NS / 2; n++) {
                    if (n >= NI) mbar_init(bar + n * 16, 2);
                    mbar_init(bar + NS * 8 + n * 16, 1);
                }
                if (p == 0) mbar_init(sbp + SM_REF, 1);
                asm volatile("fence.mbarrier_init.release.cluster;" ::: "memory");
            }
            __syncwarp();
            bar_arrive(B_QK, NTHREADS);
            if (elect()) {
                int tl = 2 * b + p + 2 * NI * G;
                int s = p + 2 * NI; uint32_t ph = 1;
                int sa = p, na = 0; uint32_t pa = 0;
                bool late = false;
                for (int n = NI;; n++) {
                    const int d = n < NRAMP ? D0 : (tl >= NT - (TA) ? 1 : D1);
                    mbar_wait(sbp + SM_BAR + (NS + s) * 8, ph);
                    mbar_expect(sbp + SM_BAR + s * 8, STAGE);
                    if (n < NPACE) while (clock32() - c0 < (n ? T1 + (2 * (n - 1) + p) * TG : T0)) {}
                    while (n - na >= d) {
                        mbar_wait(sbp + SM_BAR + sa * 8, pa);
                        if (na < NS / 2) TR(1, 2 * na + p);
                        na++; sa += 2;
                        if (sa >= NS) { sa -= NS; pa ^= 1; }
                    }
                    issue_tile(&m0, &m1, sbp, s, tl, pol);
                    TR(0, 2 * n + p);
                    int nxt = tl + 2 * G;
                    if (n >= NST - 1) nxt = grab_tile(g_ctr) + 2 * NST * G;
                    const bool last = nxt >= NT;
                    uint32_t flag = last;
                    if (!late && nxt >= NT - MAXT - 16 * b) { late = true; flag |= 2; }
                    if (last) mbar_wait(sbp + SM_REF, 0);
                    sts32(sbp + SM_FLAG + s * 4, flag);
                    mbar_arrive(sbp + SM_BAR + s * 8);
                    if (last) break;
                    s += 2;
                    if (s >= NS) { s -= NS; ph ^= 1; }
                    tl = nxt;
                }
                if (p) TSE(5);
            }
            return;
        }
        const int h = threadIdx.x - 320;
        uint4 v[6];
        for (int it = 0;; it++) {
            bool miss = false;
#pragma unroll
            for (int k = 0; k < 6; k++) v[k] = ldg_relaxed(g_qk + k * 64 + h);
#pragma unroll
            for (int k = 0; k < 6; k++) miss |= has(v[k], 0);
            if (!miss) break;
            if (it > SPIN_LIMIT) __trap();
            if (it == 0) __nanosleep(QSLEEP);
        }
#pragma unroll
        for (int k = 0; k < 6; k++) sts128(sb + SM_QK + (k * 64 + h) * 16, ~v[k].x, ~v[k].y, ~v[k].z, ~v[k].w);
        __syncwarp();
        bar_sync(B_QK, NTHREADS);
        if (warp == 11) return;
        uint32_t r = 1;
        for (int it = 0;; it++) {
            __nanosleep(500);
            if (lane < NQ) asm volatile("ld.acquire.gpu.global.u32 %0, [%1];" : "=r"(r) : "l"(g_mref + lane) : "memory");
            if (__all_sync(~0u, r != 0)) break;
            if (it > SPIN_LIMIT) __trap();
        }
        if (lane < NQ) sts32(sb + SM_M + lane * 4, ~r);
        __syncwarp();
        if (lane == 0) { mbar_arrive(sb + SM_REF); TSE(7); }
        return;
    }

    const int grp = warp >> 2, cw = warp & 3;
    const int xp = lane & 7, mi = lane >> 3;
    const uint32_t offS1 = opaque(12288 + xp * 128 + ((mi ^ xp) << 4)), offS1x = opaque(offS1 ^ 64);
    const uint32_t offS0 = opaque(offS1 - 12288 + cw * 3072), offS0x = opaque(offS0 ^ 64);
    const uint32_t offT = opaque(mi * 3072 + xp * 128 + (((cw + 4 * grp) ^ xp) << 4)), offTx = opaque(offT ^ 64);
    const uint32_t offU = opaque(12288 + (mi % 3) * 1024 + xp * 128 + (((cw + 4 * (grp ^ (mi / 3))) ^ xp) << 4));
    const uint32_t offV = opaque(12288 + (1 + (mi & 1)) * 1024 + xp * 128 + (((cw + 4 * (grp ^ 1)) ^ xp) << 4));
    const int shl = opaque(9 * t), shl4 = opaque(9 * t + 4);
    const uint32_t pw = opaque((cw >> 1) * 512 + lane * 16 + (cw & 1) * 8), muw = opaque(1024 + t * 16 + cw * 4);
    const uint32_t prd = opaque(lane * 16), mur = opaque(1024 + t * 16), mof = g * 4;
    uint32_t pb0 = sb + SM_P + grp * 2 * PBUF;
    const uint32_t pbx = pb0 ^ (pb0 + PBUF);
    const bool odd = g & 1;
    const int barid = B_GRP + grp;
    const bool elected = cw == 3 && lane == 0;

    uint32_t qa[48];
    float r_lo, r_hi;
    bar_sync(B_QK, NTHREADS);
    {
        float rr[2][4] = {{0.f, 0.f, 0.f, 0.f}, {0.f, 0.f, 0.f, 0.f}};
#pragma unroll
        for (int kk = 0; kk < 12; kk++) {
            const uint4 v = lds128(sb + SM_QK + kk * 512 + lane * 16);
            qa[4 * kk] = v.x; qa[4 * kk + 1] = v.y; qa[4 * kk + 2] = v.z; qa[4 * kk + 3] = v.w;
            mma(rr[kk & 1], v.x, v.y, v.z, v.w, ONES, ONES);
        }
        r_lo = rr[0][0] + rr[1][0]; r_hi = rr[0][2] + rr[1][2];
    }
    if (threadIdx.x == 0) TS(1);

    float acc[6][4];
#pragma unroll
    for (int i = 0; i < 6; i++) acc[i][0] = acc[i][1] = acc[i][2] = acc[i][3] = 0.f;
    float m_lo = -INFINITY, m_hi = -INFINITY, l_lo = 0.f, l_hi = 0.f;
    float cm[4] = {0.f, 0.f, 0.f, 0.f};
    uint32_t xt[6][4], yt[6]; uint4 pa, pb, mv;
    uint4* dst = reinterpret_cast<uint4*>(reinterpret_cast<char*>(g_acc) + acc_line(g >> 1, warp) + (lane & 7) * 16);
    asm volatile("" : "+l"(dst));
    const uint32_t xof = __shfl_sync(~0u, 512 - lane * 8, lane);
    uint32_t ref_lo = 0, ref_hi = 0;
    const uint32_t mad = __shfl_sync(~0u, sb + SM_M + mof, lane);
    uint32_t one[2];
#pragma unroll
    for (int i = 0; i < 2; i++) one[i] = __shfl_sync(~0u, ONES + ((lane + i) >> (G >> 16) >> 16), lane);
    uint32_t st = sb + SM_STAGES + grp * STAGE;
    int s = grp; uint32_t ph = 0;
    while (true) {
        mbar_wait(sb + SM_BAR + s * 8, ph);
        PH(0, 0);
        const uint32_t stop = lds32(sb + SM_FLAG + s * 4);
        float sc[2][4], gr[2][4];
#pragma unroll
        for (int e = 0; e < 4; e++) sc[0][e] = sc[1][e] = gr[0][e] = gr[1][e] = 0.f;
#pragma unroll
        for (int qq = 0; qq < 6; qq++) {
            uint32_t x[4], y[4];
            ldsm4(x, st + (qq & 1 ? offS0x : offS0) + (qq >> 1) * 1024);
            ldsm4(y, st + (qq & 1 ? offS1x : offS1) + (qq >> 1) * 1024);
            uint32_t z[4];
#pragma unroll
            for (int e = 0; e < 4; e++) asm("fma.rn.bf16x2 %0, %1, %2, %3;" : "=r"(z[e]) : "r"(x[e]), "r"(one[e & 1]), "r"(y[e]));
#pragma unroll
            for (int e = 0; e < 4; e++) x[e] = hadd2(x[e], y[e]);
            mma(gr[0], z[0], one[0], z[1], one[1], x[0], x[1]);
            mma(gr[1], z[2], one[0], z[3], one[1], x[2], x[3]);
            mma(sc[0], qa[8 * qq], qa[8 * qq + 1], qa[8 * qq + 2], qa[8 * qq + 3], x[0], x[1]);
            mma(sc[1], qa[8 * qq + 4], qa[8 * qq + 5], qa[8 * qq + 6], qa[8 * qq + 7], x[2], x[3]);
        }
        ldsm4t(yt, st + offU);
        ldsm2t(yt + 4, st + offV);
#pragma unroll
        for (int i = 0; i < 6; i++) ldsm4t(xt[i], st + (i < 3 ? offT : offTx) + (i % 3) * 1024);

        const float mu0 = (gr[0][2] + gr[1][2]) * (1.f / C), mu1 = (gr[0][3] + gr[1][3]) * (1.f / C);
        const float mu = odd ? mu1 : mu0, ss = odd ? gr[0][1] + gr[1][1] : gr[0][0] + gr[1][0];
        const float rs = rsq(fmaxf(fmaf(-mu, mu, fmaf(ss, 1.f / C, 1e-5f)), 1e-5f));
        const float rs0 = __shfl_sync(~0u, rs, shl), rs1 = __shfl_sync(~0u, rs, shl4);
        const float u0 = fmaf(-mu0, r_lo, sc[0][0] + sc[1][0]), u1 = fmaf(-mu1, r_lo, sc[0][1] + sc[1][1]);
        const float u2 = fmaf(-mu0, r_hi, sc[0][2] + sc[1][2]), u3 = fmaf(-mu1, r_hi, sc[0][3] + sc[1][3]);
        const float d0 = fmaf(u0, rs0, -m_lo), d1 = fmaf(u1, rs1, -m_lo), d2 = fmaf(u2, rs0, -m_hi), d3 = fmaf(u3, rs1, -m_hi);
        PH(1, u(d0 + d2));
        float p0 = ex2(d0), p1 = ex2(d1), p2 = ex2(d2), p3 = ex2(d3);
        sts64(pb0 + pw, pack2(p0 * rs0, p1 * rs1), pack2(p2 * rs0, p3 * rs1));
        if (lane < 4) sts32(pb0 + muw, pack2(mu0, mu1));
        asm volatile("{.reg .pred p; setp.ne.u32 p, %2, 0; @p ld.shared.b32 %0, [%3]; @p ld.shared.b32 %1, [%3+32];}" : "+r"(ref_lo), "+r"(ref_hi) : "r"(stop & 1), "r"(mad) : "memory");
        const bool over = bar_any(barid, 128, fmaxf(fmaxf(d0, d1), fmaxf(d2, d3)) > LAZY);
        PH(3, 0);
        pa = lds128(pb0 + prd); pb = lds128(pb0 + prd + 512); mv = lds128(pb0 + mur);
        if (stop & 1) { l_lo += p0 + p1; l_hi += p2 + p3; break; }
        if (elected) mbar_arrive(sb + SM_BAR + (NS + s) * 8);
        if (__builtin_expect(over, 0)) {
            const int ln = laneid(), g = ln >> 2, t = ln & 3;
            const float s0 = u0 * rs0, s1 = u1 * rs1, s2 = u2 * rs0, s3 = u3 * rs1;
            float xl = fmaxf(s0, s1), xh = fmaxf(s2, s3);
            xl = fmaxf(xl, __shfl_xor_sync(~0u, xl, 1)); xh = fmaxf(xh, __shfl_xor_sync(~0u, xh, 1));
            xl = fmaxf(xl, __shfl_xor_sync(~0u, xl, 2)); xh = fmaxf(xh, __shfl_xor_sync(~0u, xh, 2));
            if (t < 2) sts32(sb + SM_MX + grp * 256 + ((g + 8 * t) * 4 + cw) * 4, u(t ? xh : xl));
            bar_sync(B_MAX + grp, 128);
            const uint4 ml4 = lds128(sb + SM_MX + grp * 256 + g * 16), mh4 = lds128(sb + SM_MX + grp * 256 + g * 16 + 128);
            const float nl = fmaxf(fmaxf(fmaxf(f(ml4.x), f(ml4.y)), fmaxf(f(ml4.z), f(ml4.w))), m_lo);
            const float nh = fmaxf(fmaxf(fmaxf(f(mh4.x), f(mh4.y)), fmaxf(f(mh4.z), f(mh4.w))), m_hi);
            p0 = ex2(s0 - nl); p1 = ex2(s1 - nl); p2 = ex2(s2 - nh); p3 = ex2(s3 - nh);
            sts64(pb0 + pw, pack2(p0 * rs0, p1 * rs1), pack2(p2 * rs0, p3 * rs1));
            const float al = ex2(m_lo - nl), ah = ex2(m_hi - nh);
            m_lo = nl; m_hi = nh;
            l_lo *= al; l_hi *= ah; cm[0] *= al; cm[2] *= ah;
#pragma unroll
            for (int i = 0; i < 6; i++) { acc[i][0] *= al; acc[i][1] *= al; acc[i][2] *= ah; acc[i][3] *= ah; }
            bar_sync(B_MAX + grp, 128);
            pa = lds128(pb0 + prd); pb = lds128(pb0 + prd + 512);
        }
        l_lo += p0 + p1; l_hi += p2 + p3;
#pragma unroll
        for (int i = 0; i < 6; i++) mma(acc[i], pa.x, pa.y, pa.z, pa.w, hadd2v(xt[i][0], yt[i]), hadd2v(xt[i][1], yt[i]));
        mma(cm, pa.x, pa.y, pa.z, pa.w, mv.x, mv.y);
#pragma unroll
        for (int i = 0; i < 6; i++) mma(acc[i], pb.x, pb.y, pb.z, pb.w, hadd2v(xt[i][2], yt[i]), hadd2v(xt[i][3], yt[i]));
        mma(cm, pb.x, pb.y, pb.z, pb.w, mv.z, mv.w);
        PH(4, u(acc[5][0]));
        if (stop) {
            const int ln = laneid(), g = ln >> 2, t = ln & 3;
            float a = l_lo + __shfl_xor_sync(~0u, l_lo, 1), c = l_hi + __shfl_xor_sync(~0u, l_hi, 1);
            a += __shfl_xor_sync(~0u, a, 2); c += __shfl_xor_sync(~0u, c, 2);
            const uint32_t m = u((t ? m_hi : m_lo) + lg2(fmaxf(t ? c : a, 1.f)));
            if (t < 2) asm volatile("red.relaxed.gpu.global.max.u32 [%0], %1;" ::"l"(g_mmax + g + 8 * t), "r"(m >> 31 ? ~m : m | 0x80000000u) : "memory");
        }
        pb0 ^= pbx;
        s += 2;
        st += 2 * STAGE;
        if (s >= NS) { s -= NS; ph ^= 1; st -= NS * STAGE; }
        asm volatile("" : "+r"(st));
    }
    const float al = ex2(m_lo - f(ref_lo)), ah = ex2(m_hi - f(ref_hi));
    mma(cm, pa.x, pa.y, pa.z, pa.w, mv.x, mv.y);
#pragma unroll
    for (int i = 3; i < 6; i++) mma(acc[i], pa.x, pa.y, pa.z, pa.w, hadd2v(xt[i][0], yt[i]), hadd2v(xt[i][1], yt[i]));
    mma(cm, pb.x, pb.y, pb.z, pb.w, mv.z, mv.w);
#pragma unroll
    for (int i = 3; i < 6; i++) mma(acc[i], pb.x, pb.y, pb.z, pb.w, hadd2v(xt[i][2], yt[i]), hadd2v(xt[i][3], yt[i]));
#pragma unroll
    for (int i = 0; i < 3; i++) mma(acc[i], pa.x, pa.y, pa.z, pa.w, hadd2v(xt[i][0], yt[i]), hadd2v(xt[i][1], yt[i]));
#pragma unroll
    for (int i = 0; i < 3; i++) mma(acc[i], pb.x, pb.y, pb.z, pb.w, hadd2v(xt[i][2], yt[i]), hadd2v(xt[i][3], yt[i]));
    if (threadIdx.x == grp * 128) TSE(2 + grp);
    if (threadIdx.x == grp * 128 + 96) TSX(2 + grp, u(acc[5][0]));

    const uint32_t xw = sb + SM_STAGES + grp * STAGE + cw * 768 + prd, xr = sb + SM_STAGES + (grp ^ 1) * STAGE + cw * 768 + prd;
    const float cl = -cm[0] * al, ch = -cm[2] * ah;
    uint32_t hl[6], hh[6];
#pragma unroll
    for (int i = 3; i < 6; i++) { hl[i] = packh(fmaf(acc[i][0], al, cl), fmaf(acc[i][1], al, cl)); hh[i] = packh(fmaf(acc[i][2], ah, ch), fmaf(acc[i][3], ah, ch)); }
    sts128(xw, hl[3], hl[4], hl[5], hh[3]);
    sts64(xw + xof, hh[4], hh[5]);
#pragma unroll
    for (int i = 0; i < 3; i++) { hl[i] = packh(fmaf(acc[i][0], al, cl), fmaf(acc[i][1], al, cl)); hh[i] = packh(fmaf(acc[i][2], ah, ch), fmaf(acc[i][3], ah, ch)); }
    const uint32_t w_lo = packh(l_lo * al, 1.f), w_hi = packh(l_hi * ah, 1.f);
    bar_sync(B_MERGE, 256);
    if (threadIdx.x == 224) TSX(4, 0);
    const uint4 o = lds128(xr);
    const uint2 o2 = lds64(xr + xof);
    red8h(dst + ACC_HI / 16, haddh(hl[0], o.x), haddh(hl[1], o.y), haddh(hl[2], o.z), w_lo);
    for (const unsigned c = clock32(); clock32() - c < RDEL;) {}
    red8h(dst, haddh(hh[0], o.w), haddh(hh[1], o2.x), haddh(hh[2], o2.y), w_hi);
    if (threadIdx.x == 0) TSE(4);
    if (threadIdx.x == 224) TSX(9, 0);
}

typedef CUresult (*EncodeFn)(CUtensorMap*, CUtensorMapDataType, cuuint32_t, void*, const cuuint64_t*, const cuuint64_t*,
                             const cuuint32_t*, const cuuint32_t*, CUtensorMapInterleave, CUtensorMapSwizzle,
                             CUtensorMapL2promotion, CUtensorMapFloatOOBfill);

}

extern "C" void kernel_launch(void* const* d_in, const int* in_sizes, int n_in, void* d_out, int out_size) {
    const __nv_bfloat16* q = (const __nv_bfloat16*)d_in[0];
    char* f0 = (char*)d_in[1];
    char* f1 = (char*)d_in[2];
    const __nv_bfloat16* wq = (const __nv_bfloat16*)d_in[3];
    const __nv_bfloat16* wk = (const __nv_bfloat16*)d_in[4];
    const __nv_bfloat16* wv = (const __nv_bfloat16*)d_in[5];
    const __nv_bfloat16* wo = (const __nv_bfloat16*)d_in[6];

    static EncodeFn enc = nullptr;
    static int grid = 0;
    static Scratch* scr = nullptr;
    if (!enc) {
        void* fn = nullptr; cudaDriverEntryPointQueryResult qr;
        cudaGetDriverEntryPoint("cuTensorMapEncodeTiled", &fn, cudaEnableDefault, &qr);
        enc = (EncodeFn)fn;
        cudaGetSymbolAddress((void**)&scr, g_scratch);
        int dev = 0, sms = 0;
        cudaGetDevice(&dev);
        cudaDeviceGetAttribute(&sms, cudaDevAttrMultiProcessorCount, dev);
        grid = sms < MAXG ? sms : MAXG;
        cudaFuncSetAttribute(attn_main, cudaFuncAttributeMaxDynamicSharedMemorySize, SMEM_BYTES);
    }
    CUtensorMap m0, m1;
    {
        cuuint64_t dims[5] = {64, W1, 3, 2, W0};
        cuuint64_t str[4] = {2 * C * 2, 128, C * 2, (cuuint64_t)W0 * C * 2};
        cuuint32_t box[5] = {64, TP, 3, 2, 2}, es[5] = {1, 1, 1, 1, 1};
        enc(&m0, CU_TENSOR_MAP_DATA_TYPE_BFLOAT16, 5, f0, dims, str, box, es, CU_TENSOR_MAP_INTERLEAVE_NONE,
            CU_TENSOR_MAP_SWIZZLE_128B, CU_TENSOR_MAP_L2_PROMOTION_NONE, CU_TENSOR_MAP_FLOAT_OOB_FILL_NONE);
    }
    {
        cuuint64_t dims[4] = {64, W1, 3, W1};
        cuuint64_t str[3] = {C * 2, 128, (cuuint64_t)W1 * C * 2};
        cuuint32_t box[4] = {64, TP, 3, 1}, es[4] = {1, 1, 1, 1};
        enc(&m1, CU_TENSOR_MAP_DATA_TYPE_BFLOAT16, 4, f1, dims, str, box, es, CU_TENSOR_MAP_INTERLEAVE_NONE,
            CU_TENSOR_MAP_SWIZZLE_128B, CU_TENSOR_MAP_L2_PROMOTION_NONE, CU_TENSOR_MAP_FLOAT_OOB_FILL_NONE);
    }
    attn_main<<<grid, NTHREADS, SMEM_BYTES, cudaStreamPerThread>>>(f0, f1, q, wq, wk, scr, wv, wo, (__nv_bfloat16*)d_out, m0, m1);
}
```

```cpp
#include <cuda_runtime.h>
#include <cuda_bf16.h>
#include <cuda.h>
#include <stdint.h>
#include <stddef.h>

namespace {

constexpr int C = 192;
constexpr int NQ = 16;
constexpr int W0 = 512;
constexpr int W1 = 256;
constexpr int TP = 8;
constexpr int NT = W1 * W1 / TP;
constexpr int STAGE = TP * 5 * C * 2;
#define NS 14
#define D0 3
#define D1 2
#define NRAMP 5
#define TA (p ? NT : 100 + 6 * b)
#define QSLEEP 700
#define WSL 32
#define MAXT 3000
#define REFT 1800
#define POLLN 1
#define PGAP 120
#define NPW 4
#define LAZY 12.f
#define RDEL 20
#define NST 4
#define NI 1
#define NPACE 5
#define T0 0
#define T1 1000
#define TG 960
static_assert(NST > D0, "the first dynamic tile index must not delay the start");
constexpr int NTHREADS = 384;
constexpr int MAXG = 132;
constexpr int NRD = NQ;
constexpr int NSRC = 12;
constexpr int SPIN_LIMIT = 1 << 22;

constexpr int SM_STAGES = 0;
constexpr int SM_P = NS * STAGE;
constexpr int PBUF = 1088;
constexpr int SM_QK = SM_P + 4 * PBUF;
constexpr int SM_MX = SM_QK + 6144;
constexpr int SM_M = SM_MX + 512;
constexpr int SM_BAR = SM_M + 64;
constexpr int SM_REF = SM_BAR + 16 * NS;
constexpr int SM_FLAG = SM_REF + 8;
constexpr int SM_TOTAL = SM_FLAG + 4 * NS;
constexpr int SMEM_BYTES = SM_TOTAL + 1024;
static_assert(SMEM_BYTES <= 232448, "smem");
constexpr int WROW = 400;
constexpr int RD_W = 0;
constexpr int RD_QN = 2 * C * WROW;
constexpr int RD_KQ = RD_QN + 6144;
constexpr int RD_B = RD_KQ + 7168;
constexpr int RD_B2 = 17 * 80;
constexpr int RD_BAR = RD_B + 2 * RD_B2;
constexpr int RD_A = RD_BAR + 64;
constexpr int RD_WS = RD_A + 12 * 6 * 512;
static_assert(RD_WS + 12 * 128 <= SM_TOTAL, "smem");

struct Scratch {
    uint4 acc[2816];
    uint4 qk[NSRC * 32];
    unsigned ctr[32];
    unsigned mmax[32];
    unsigned mref[32];
    uint4 acc_hi[4096];
};
__device__ __align__(131072) Scratch g_scratch;
#define g_acc (scr->acc)
#define g_qk (scr->qk)
#define g_ctr (scr->ctr)
#define g_mmax (scr->mmax)
#define g_mref (scr->mref)
#define g_ts (scr->ts)
#define g_tr (scr->tr)
#define TR(k, i) do {} while (0)
#define TS(i) do {} while (0)
#define TSD(i, dep) do {} while (0)
#define TSX(i, dep) do {} while (0)
#define TSP(i, dep) do {} while (0)
#define TSE(i) TS(i)
#define CK_(i, dep) do {} while (0)
#define PH(i, dep) do {} while (0)

__device__ __forceinline__ uint32_t s2u(const void* p) { return (uint32_t)__cvta_generic_to_shared(p); }
__device__ __forceinline__ void mbar_init(uint32_t a, int c) { asm volatile("mbarrier.init.shared::cta.b64 [%0], %1;" ::"r"(a), "r"(c) : "memory"); }
__device__ __forceinline__ void mbar_expect(uint32_t a, uint32_t b) { asm volatile("mbarrier.arrive.expect_tx.shared::cta.b64 _, [%0], %1;" ::"r"(a), "r"(b) : "memory"); }
__device__ __forceinline__ void mbar_arrive(uint32_t a) { asm volatile("mbarrier.arrive.shared::cta.b64 _, [%0];" ::"r"(a) : "memory"); }
__device__ __forceinline__ void mbar_wait(uint32_t a, uint32_t ph) {
    uint32_t ok; int it = 0;
    do {
        asm volatile("{.reg .pred p; mbarrier.try_wait.parity.shared::cta.b64 p, [%1], %2; selp.u32 %0,1,0,p;}" : "=r"(ok) : "r"(a), "r"(ph) : "memory");
        if (++it > SPIN_LIMIT) __trap();
    } while (!ok);
}
__device__ __forceinline__ bool elect() {
    uint32_t r; asm volatile("{.reg .pred p; elect.sync _|p, 0xffffffff; selp.u32 %0, 1, 0, p;}" : "=r"(r)); return r;
}
__device__ __forceinline__ void bar_sync(int id, int n) { asm volatile("bar.sync %0, %1;" ::"r"(id), "r"(n) : "memory"); }
__device__ __forceinline__ bool bar_any(int id, int n, bool c) {
    uint32_t r;
    asm volatile("{.reg .pred p, q; setp.ne.u32 q, %3, 0; bar.red.or.pred p, %1, %2, q; selp.u32 %0, 1, 0, p;}" : "=r"(r) : "r"(id), "r"(n), "r"((uint32_t)c) : "memory");
    return r;
}
__device__ __forceinline__ void bar_arrive(int id, int n) { asm volatile("bar.arrive %0, %1;" ::"r"(id), "r"(n) : "memory"); }
__device__ __forceinline__ void ldsm4(uint32_t* r, uint32_t a) {
    asm volatile("ldmatrix.sync.aligned.m8n8.x4.shared.b16 {%0,%1,%2,%3}, [%4];" : "=r"(r[0]), "=r"(r[1]), "=r"(r[2]), "=r"(r[3]) : "r"(a) : "memory");
}
__device__ __forceinline__ void ldsm4t(uint32_t* r, uint32_t a) {
    asm volatile("ldmatrix.sync.aligned.m8n8.x4.trans.shared.b16 {%0,%1,%2,%3}, [%4];" : "=r"(r[0]), "=r"(r[1]), "=r"(r[2]), "=r"(r[3]) : "r"(a) : "memory");
}
__device__ __forceinline__ void ldsm2t(uint32_t* r, uint32_t a) {
    asm volatile("ldmatrix.sync.aligned.m8n8.x2.trans.shared.b16 {%0,%1}, [%2];" : "=r"(r[0]), "=r"(r[1]) : "r"(a) : "memory");
}
__device__ __forceinline__ void mma(float* d, uint32_t a0, uint32_t a1, uint32_t a2, uint32_t a3, uint32_t b0, uint32_t b1) {
    asm("mma.sync.aligned.m16n8k16.row.col.f32.bf16.bf16.f32 {%0,%1,%2,%3}, {%4,%5,%6,%7}, {%8,%9}, {%0,%1,%2,%3};"
        : "+f"(d[0]), "+f"(d[1]), "+f"(d[2]), "+f"(d[3]) : "r"(a0), "r"(a1), "r"(a2), "r"(a3), "r"(b0), "r"(b1));
}
__device__ __forceinline__ void mmah(float* d, uint32_t a0, uint32_t a1, uint32_t a2, uint32_t a3, uint32_t b0, uint32_t b1) {
    asm("mma.sync.aligned.m16n8k16.row.col.f32.f16.f16.f32 {%0,%1,%2,%3}, {%4,%5,%6,%7}, {%8,%9}, {%0,%1,%2,%3};"
        : "+f"(d[0]), "+f"(d[1]), "+f"(d[2]), "+f"(d[3]) : "r"(a0), "r"(a1), "r"(a2), "r"(a3), "r"(b0), "r"(b1));
}
__device__ __forceinline__ void mma8(float* d, uint32_t a0, uint32_t a1, uint32_t b0) {
    asm("mma.sync.aligned.m16n8k8.row.col.f32.bf16.bf16.f32 {%0,%1,%2,%3}, {%4,%5}, {%6}, {%0,%1,%2,%3};"
        : "+f"(d[0]), "+f"(d[1]), "+f"(d[2]), "+f"(d[3]) : "r"(a0), "r"(a1), "r"(b0));
}
__device__ __forceinline__ uint32_t hadd2(uint32_t a, uint32_t b) {
    uint32_t r; asm("add.rn.bf16x2 %0, %1, %2;" : "=r"(r) : "r"(a), "r"(b)); return r;
}
__device__ __forceinline__ uint32_t pack2(float lo, float hi) {
    uint32_t r; asm("cvt.rn.bf16x2.f32 %0, %1, %2;" : "=r"(r) : "f"(hi), "f"(lo)); return r;
}
__device__ __forceinline__ uint32_t packh(float lo, float hi) {
    uint32_t r; asm("cvt.rn.f16x2.f32 %0, %1, %2;" : "=r"(r) : "f"(hi), "f"(lo)); return r;
}
__device__ __forceinline__ float bflo(uint32_t v) { return __uint_as_float(v << 16); }
__device__ __forceinline__ float bfhi(uint32_t v) { return __uint_as_float(v & 0xffff0000u); }
__device__ __forceinline__ float ex2(float x) { float r; asm("ex2.approx.ftz.f32 %0, %1;" : "=f"(r) : "f"(x)); return r; }
__device__ __forceinline__ void sts128(uint32_t a, uint32_t x, uint32_t y, uint32_t z, uint32_t w) {
    asm volatile("st.shared.v4.b32 [%0], {%1,%2,%3,%4};" ::"r"(a), "r"(x), "r"(y), "r"(z), "r"(w) : "memory");
}
__device__ __forceinline__ void sts64(uint32_t a, uint32_t x, uint32_t y) {
    asm volatile("st.shared.v2.b32 [%0], {%1,%2};" ::"r"(a), "r"(x), "r"(y) : "memory");
}
__device__ __forceinline__ void sts32(uint32_t a, uint32_t x) { asm volatile("st.shared.b32 [%0], %1;" ::"r"(a), "r"(x) : "memory"); }
__device__ __forceinline__ uint4 lds128(uint32_t a) {
    uint4 v; asm volatile("ld.shared.v4.b32 {%0,%1,%2,%3}, [%4];" : "=r"(v.x), "=r"(v.y), "=r"(v.z), "=r"(v.w) : "r"(a) : "memory"); return v;
}
__device__ __forceinline__ uint2 lds64(uint32_t a) {
    uint2 v; asm volatile("ld.shared.v2.b32 {%0,%1}, [%2];" : "=r"(v.x), "=r"(v.y) : "r"(a) : "memory"); return v;
}
__device__ __forceinline__ uint32_t haddh(uint32_t a, uint32_t b) {
    uint32_t r; asm("add.rn.f16x2 %0, %1, %2;" : "=r"(r) : "r"(a), "r"(b)); return r;
}
__device__ __forceinline__ uint32_t lds32(uint32_t a) { uint32_t v; asm volatile("ld.shared.b32 %0, [%1];" : "=r"(v) : "r"(a) : "memory"); return v; }
__device__ __forceinline__ int grab_tile(unsigned* ctr) {
    int v; asm volatile("atom.relaxed.gpu.global.inc.u32 %0, [%1], 0x7fffffff;" : "=r"(v) : "l"(ctr) : "memory"); return v;
}
__device__ __forceinline__ uint32_t opaque(uint32_t v) { uint32_t r; asm volatile("mov.b32 %0, %1;" : "=r"(r) : "r"(v)); return r; }
__device__ __forceinline__ int laneid() { int r; asm volatile("mov.u32 %0, %%laneid;" : "=r"(r)); return r; }
__device__ __forceinline__ unsigned clock32() { unsigned c; asm volatile("mov.u32 %0, %%clock;" : "=r"(c)); return c; }
__device__ __forceinline__ float rsq(float x) { float r; asm("rsqrt.approx.ftz.f32 %0, %1;" : "=f"(r) : "f"(x)); return r; }
__device__ __forceinline__ float rcp(float x) { float r; asm("rcp.approx.ftz.f32 %0, %1;" : "=f"(r) : "f"(x)); return r; }
__device__ __forceinline__ float lg2(float x) { float r; asm("lg2.approx.ftz.f32 %0, %1;" : "=f"(r) : "f"(x)); return r; }
__device__ __forceinline__ float f(uint32_t v) { return __uint_as_float(v); }
__device__ __forceinline__ uint32_t u(float v) { return __float_as_uint(v); }

constexpr uint32_t ONES = 0x3F803F80u;
constexpr float QSCALE = 0.07216878364870322f * 1.4426950408889634f;

__device__ __forceinline__ void issue_tile(const CUtensorMap* m0, const CUtensorMap* m1, uint32_t sb, int s, int tl, uint64_t pol) {
    const uint32_t full = sb + SM_BAR + s * 8, dst = sb + SM_STAGES + s * STAGE;
    const int par = tl * TP, y = par >> 8, x = par & 255;
    asm volatile("cp.async.bulk.tensor.5d.shared::cluster.global.mbarrier::complete_tx::bytes.L2::cache_hint [%0], [%1, {%3,%4,%3,%3,%5}], [%2], %6;"
                 ::"r"(dst), "l"(m0), "r"(full), "r"(0), "r"(x), "r"(2 * y), "l"(pol) : "memory");
    asm volatile("cp.async.bulk.tensor.4d.shared::cluster.global.mbarrier::complete_tx::bytes.L2::cache_hint [%0], [%1, {%3,%4,%3,%5}], [%2], %6;"
                 ::"r"(dst + TP * 4 * C * 2), "l"(m1), "r"(full), "r"(0), "r"(x), "r"(y), "l"(pol) : "memory");
}

__device__ __forceinline__ void prefetch_l2(const void* a, int n) { asm volatile("cp.async.bulk.prefetch.L2.global [%0], %1;" ::"l"(a), "r"(n) : "memory"); }
__device__ __forceinline__ void prefetch_line(const void* a) { asm volatile("prefetch.global.L2 [%0];" ::"l"(a) : "memory"); }
__device__ __forceinline__ uint4 ldg_relaxed(const uint4* p) {
    uint4 v; asm volatile("ld.relaxed.gpu.global.v4.u32 {%0,%1,%2,%3}, [%4];" : "=r"(v.x), "=r"(v.y), "=r"(v.z), "=r"(v.w) : "l"(p) : "memory"); return v;
}
__device__ __forceinline__ uint32_t ldg_relaxed32(const void* p) {
    uint32_t v; asm volatile("ld.relaxed.gpu.global.u32 %0, [%1];" : "=r"(v) : "l"(p) : "memory"); return v;
}
__device__ __forceinline__ void stg_relaxed(uint4* p, uint32_t x, uint32_t y, uint32_t z, uint32_t w) {
    asm volatile("st.relaxed.gpu.global.v4.u32 [%0], {%1,%2,%3,%4};" ::"l"(p), "r"(x), "r"(y), "r"(z), "r"(w) : "memory");
}
__device__ __forceinline__ void stg_relaxed32(void* p, uint32_t x) { asm volatile("st.relaxed.gpu.global.u32 [%0], %1;" ::"l"(p), "r"(x) : "memory"); }
__device__ __forceinline__ bool has(const uint4& v, uint32_t m) { return v.x == m || v.y == m || v.z == m || v.w == m; }
__device__ __forceinline__ uint32_t hadd2v(uint32_t a, uint32_t b) {
    uint32_t r; asm volatile("add.rn.bf16x2 %0, %1, %2;" : "=r"(r) : "r"(a), "r"(b)); return r;
}

__device__ __forceinline__ void red8h(uint4* p, uint32_t x, uint32_t y, uint32_t z, uint32_t w) {
    asm volatile("red.relaxed.gpu.global.add.noftz.v4.f16x2 [%0], {%1,%2,%3,%4};" ::"l"(p), "r"(x), "r"(y), "r"(z), "r"(w) : "memory");
}
__device__ __forceinline__ uint4 lds128v(uint32_t a) {
    uint4 v; asm volatile("ld.volatile.shared.v4.b32 {%0,%1,%2,%3}, [%4];" : "=r"(v.x), "=r"(v.y), "=r"(v.z), "=r"(v.w) : "r"(a) : "memory"); return v;
}
__device__ __forceinline__ uint32_t brow(int r) { return RD_B + r * 80 + (r >> 3) * 64; }

constexpr int ACC_HI = 65536;
static_assert(offsetof(Scratch, acc_hi) <= ACC_HI && offsetof(Scratch, acc_hi) + sizeof(Scratch::acc_hi) >= ACC_HI + 32768, "scratch");
__device__ __forceinline__ uint32_t acc_line(int s, int k) {
    return (k >> 2) * 16384 + (k & 2) * 6144 + (k & 1) * 1024 + (s & 1) * 256 + (s & 2) * 1024 + (s >> 2) * ACC_HI;
}

__device__ __forceinline__ int first_row() { return (blockIdx.x & 14) ^ 8; }

enum { B_QK = 1, B_QN = 2, B_GRP = 3  , B_Q = 5, B_MERGE = 6, B_ALL = 7, B_MAX = 8  , B_WARP = 10, B_SLOW = 12, B_PARK = 13, B_CLEAN = 14, B_RDY = 15 };

__device__ __noinline__ void slow_rows(const char* __restrict__ f0, const char* __restrict__ f1, const __nv_bfloat16* __restrict__ q,
                                       const __nv_bfloat16* __restrict__ wq, const __nv_bfloat16* __restrict__ wk, const uint32_t sb)
{
    const int warp = threadIdx.x >> 5, lane = threadIdx.x & 31;
    float* const sm = reinterpret_cast<float*>(__cvta_shared_to_generic(sb + RD_W));
    for (int i = threadIdx.x; i < 2 * C; i += 128) sm[i] = __bfloat162float(q[first_row() * C + i]);
    bar_sync(B_SLOW, 128);
#pragma unroll 1
    for (int j = threadIdx.x; j < 2 * C; j += 128) {
        const float* const x = sm + j / C * C;
        float mu = 0.f, var = 0.f, s = 0.f;
#pragma unroll 1
        for (int i = 0; i < C; i++) mu += x[i];
        mu *= 1.f / C;
#pragma unroll 4
        for (int i = 0; i < C; i++) { var = fmaf(x[i] - mu, x[i] - mu, var); s = fmaf(x[i] - mu, __bfloat162float(wq[i * C + j % C]), s); }
        sm[4 * C + j] = s * rsq(var * (1.f / C) + 1e-5f);
    }
    bar_sync(B_SLOW, 128);
#pragma unroll 1
    for (int j = threadIdx.x; j < 2 * C; j += 128) {
        float s = 0.f;
#pragma unroll 4
        for (int i = 0; i < C; i++) s = fmaf(sm[4 * C + j / C * C + i], __bfloat162float(wk[j % C * C + i]), s);
        sm[j] = s * QSCALE;
    }
    bar_sync(B_SLOW, 128);
    float k[2][6], a[2][6], m[2], l[2];
#pragma unroll
    for (int r = 0; r < 2; r++) {
        m[r] = -INFINITY; l[r] = 0.f;
#pragma unroll
        for (int i = 0; i < 6; i++) { k[r][i] = sm[r * C + 64 * (i >> 1) + 2 * lane + (i & 1)]; a[r][i] = 0.f; }
    }
#pragma unroll 1
    for (int par = warp; par < W1 * W1; par += 4) {
        const uint32_t* p0 = reinterpret_cast<const uint32_t*>(f0 + (size_t)((par >> 8) * 2 * W0 + (par & 255) * 2) * (C * 2)) + lane;
        const uint32_t* p1 = reinterpret_cast<const uint32_t*>(f1 + (size_t)par * (C * 2)) + lane;
        uint32_t v[4][3];
#pragma unroll
        for (int i = 0; i < 3; i++)
#pragma unroll
            for (int j = 0; j < 4; j++) v[j][i] = hadd2(__ldg(p0 + ((j >> 1) * W0 + (j & 1)) * (C / 2) + 32 * i), __ldg(p1 + 32 * i));
#pragma unroll
        for (int j = 0; j < 4; j++) {
            float x[6], s1 = 0.f, s2 = 0.f, d[2] = {0.f, 0.f};
#pragma unroll
            for (int i = 0; i < 3; i++) { x[2 * i] = bflo(v[j][i]); x[2 * i + 1] = bfhi(v[j][i]); s1 += x[2 * i] + x[2 * i + 1]; }
#pragma unroll
            for (int o = 1; o < 32; o <<= 1) s1 += __shfl_xor_sync(~0u, s1, o);
#pragma unroll
            for (int i = 0; i < 6; i++) {
                x[i] -= s1 * (1.f / C); s2 = fmaf(x[i], x[i], s2);
#pragma unroll
                for (int r = 0; r < 2; r++) d[r] = fmaf(x[i], k[r][i], d[r]);
            }
#pragma unroll
            for (int o = 1; o < 32; o <<= 1) {
                s2 += __shfl_xor_sync(~0u, s2, o);
#pragma unroll
                for (int r = 0; r < 2; r++) d[r] += __shfl_xor_sync(~0u, d[r], o);
            }
            const float rs = rsq(s2 * (1.f / C) + 1e-5f);
#pragma unroll
            for (int r = 0; r < 2; r++) {
                const float nm = fmaxf(m[r], d[r] * rs), al = ex2(m[r] - nm), p = ex2(d[r] * rs - nm);
                m[r] = nm; l[r] = fmaf(l[r], al, p);
#pragma unroll
                for (int i = 0; i < 6; i++) a[r][i] = fmaf(a[r][i], al, x[i] * (p * rs));
            }
        }
    }
    bar_sync(B_SLOW, 128);
#pragma unroll
    for (int r = 0; r < 2; r++) {
        float* const o = sm + ((r * 4 + warp) * 32 + lane) * 8;
#pragma unroll
        for (int i = 0; i < 6; i++) o[i] = a[r][i];
        o[6] = l[r]; o[7] = m[r];
    }
    bar_sync(B_SLOW, 128);
    if (warp < 2) {
        const int r = warp;
        const float* const o = sm + (r * 128 + lane) * 8;
        float M = o[7], x[7] = {0.f, 0.f, 0.f, 0.f, 0.f, 0.f, 0.f};
#pragma unroll
        for (int w = 1; w < 4; w++) M = fmaxf(M, o[256 * w + 7]);
#pragma unroll
        for (int w = 0; w < 4; w++) {
            const float e = ex2(o[256 * w + 7] - M);
#pragma unroll
            for (int i = 0; i < 7; i++) x[i] = fmaf(o[256 * w + i], e, x[i]);
        }
        const float rl = 1.f / x[6];
        sts128(sb + RD_B2 + brow(8 * (lane >> 4) + 4 * r + (lane & 3)) + ((lane >> 2) & 3) * 16, packh(x[0] * rl, x[1] * rl), packh(x[2] * rl, x[3] * rl), packh(x[4] * rl, x[5] * rl), lane ? 0u : 0x3C00u);
    }
}

template <bool FIRST>
__device__ __forceinline__ void project(const uint32_t ar, const uint32_t br, const bool hi, const float ws0, const float ws1, const float qv0, const float qv1,
                                        __nv_bfloat16* op0, __nv_bfloat16* op1, Scratch* scr)
{
    uint4 wa[3][6], x[4];
#pragma unroll
    for (int i = 0; i < 18; i++) wa[i / 6][i % 6] = lds128v(ar + i * 512);
    if (FIRST) { bar_arrive(B_CLEAN, NTHREADS); bar_sync(B_RDY, 192); }
    else bar_sync(B_SLOW, 128);
    if (FIRST && threadIdx.x == 0) TSX(8, 0);
#pragma unroll
    for (int j = 0; j < 4; j++) x[j] = lds128v(br + 16 * j);
    float o[7][4];
#pragma unroll
    for (int j = 0; j < 7; j++) o[j][0] = o[j][1] = o[j][2] = o[j][3] = 0.f;
#pragma unroll
    for (int i = 0; i < 2; i++) {
        mmah(o[6], 0x3C00u, 0x3C00u, 0x3C00u, 0x3C00u, x[2 * i].w, x[2 * i + 1].w);
#pragma unroll
        for (int n = 0; n < 3; n++) mmah(o[2 * n + i], wa[n][2 * i].x, wa[n][2 * i].y, wa[n][2 * i].z, wa[n][2 * i].w, x[2 * i].x, x[2 * i].y);
#pragma unroll
        for (int n = 0; n < 3; n++) mmah(o[2 * n + 1 - i], wa[n][2 * i + 1].x, wa[n][2 * i + 1].y, wa[n][2 * i + 1].z, wa[n][2 * i + 1].w, x[2 * i + 1].x, x[2 * i + 1].y);
#pragma unroll
        for (int n = 0; n < 3; n++) mmah(o[2 * n + i], wa[n][4 + i].x, wa[n][4 + i].y, wa[n][4 + i].z, wa[n][4 + i].w, x[2 * i].z, x[2 * i + 1].z);
    }
    const float L = o[6][0] + o[6][1], r = rcp(L);
    const float y0 = hi ? (o[2][0] + o[2][3]) + (o[3][0] + o[3][3]) : (o[0][0] + o[0][3]) + (o[1][0] + o[1][3]), y1 = (o[4][0] + o[4][3]) + (o[5][0] + o[5][3]);
    const uint32_t y = pack2(fmaf(y0, r * ws0, qv0), fmaf(y1, r * ws1, qv1));
    asm volatile("{.reg .b16 l, h; mov.b32 {l, h}, %2; st.global.b16 [%0], l; st.global.b16 [%1], h;}" ::"l"(op0), "l"(op1), "r"(y) : "memory");
    if (FIRST && threadIdx.x == 0) TSD(11, y);
    if (FIRST)
        asm volatile("{.reg .pred p; .reg .f32 a; abs.f32 a, %1; setp.ge.f32 p, %0, 0f3B000000; setp.le.and.f32 p, %0, 0f45000000, p; setp.lt.and.f32 p, a, 0f7F800000, p;"
                     " vote.sync.all.pred p, p, 0xffffffff; @p exit;}" ::"f"(L), "f"(y0) : "memory");
}

__device__ __forceinline__ void reducer(const char* __restrict__ f0, const char* __restrict__ f1, const __nv_bfloat16* __restrict__ q, const __nv_bfloat16* __restrict__ wq, const __nv_bfloat16* __restrict__ wk,
                                        Scratch* scr, const __nv_bfloat16* __restrict__ wv, const __nv_bfloat16* __restrict__ wo,
                                        __nv_bfloat16* __restrict__ out, const uint32_t sb, const int GS)
{
    const int warp = threadIdx.x >> 5, lane = threadIdx.x & 31, b = blockIdx.x;
    const int g = lane >> 2, t = lane & 3;
    char* const ap = reinterpret_cast<char*>(g_acc);
    if (threadIdx.x == 256) TS(0);
    if (b < NSRC && warp < 8) {
        const uint32_t wqs = sb + RD_W, wbar = sb + RD_BAR;
        const int hr = lane >> 4, qt = (lane >> 2) & 3, sub = lane & 3;
        const uint32_t* qp = reinterpret_cast<const uint32_t*>(q + (warp + 8 * hr) * C + 48 * qt + 6 * sub);
        uint32_t qw[6];
#pragma unroll
        for (int j = 0; j < 3; j++) { qw[j] = __ldg(qp + j); qw[3 + j] = __ldg(qp + 12 + j); }
        if (lane == 0) { mbar_init(wbar + warp * 8, 1); asm volatile("fence.mbarrier_init.release.cluster;" ::: "memory"); mbar_expect(wbar + warp * 8, 9216);
            asm volatile("cp.async.bulk.shared::cluster.global.mbarrier::complete_tx::bytes [%0], [%1], 9216, [%2];"
                         ::"r"(wqs + warp * 9232), "l"(wq + 24 * warp * C), "r"(wbar + warp * 8) : "memory");
        }
        __syncwarp();
        if (threadIdx.x == 0) TSP(2, 0);
        float e[12];
#pragma unroll
        for (int j = 0; j < 6; j++) { e[2 * j] = bflo(qw[j]); e[2 * j + 1] = bfhi(qw[j]); }
        float sm = ((e[0] + e[1]) + (e[2] + e[3])) + ((e[4] + e[5]) + (e[6] + e[7])) + ((e[8] + e[9]) + (e[10] + e[11]));
#pragma unroll
        for (int o = 1; o < 16; o <<= 1) sm += __shfl_xor_sync(~0u, sm, o);
        if (threadIdx.x == 0) TSP(5, u(sm));
        float v0 = 0.f, v1 = 0.f;
#pragma unroll
        for (int j = 0; j < 12; j++) e[j] -= sm * (1.f / C);
#pragma unroll
        for (int j = 0; j < 6; j++) { v0 = fmaf(e[j], e[j], v0); v1 = fmaf(e[6 + j], e[6 + j], v1); }
        v0 += v1;
#pragma unroll
        for (int o = 1; o < 16; o <<= 1) v0 += __shfl_xor_sync(~0u, v0, o);
        const float rq = rsq(v0 * (1.f / C) + 1e-5f);
#pragma unroll
        for (int j = 0; j < 6; j++)
            sts32(sb + RD_QN + (3 * sub + (j >> 1)) * 512 + (4 * warp + qt) * 16 + (2 * (j & 1) + hr) * 4, pack2(e[j] * rq, e[6 + j] * rq));
        if (threadIdx.x == 0) TSP(8, 0);
        uint32_t wkf[2][3];
#pragma unroll
        for (int i = 0; i < 2; i++)
#pragma unroll
            for (int j = 0; j < 3; j++) wkf[i][j] = __ldg(reinterpret_cast<const uint32_t*>(wk + (16 * b + 8 * i + g) * C + 24 * warp + 8 * j + 2 * t));
        bar_sync(B_QN, 256);
        float acc[2][3][4];
#pragma unroll
        for (int i = 0; i < 3; i++)
#pragma unroll
            for (int e = 0; e < 4; e++) acc[0][i][e] = acc[1][i][e] = 0.f;
        const uint32_t ba = wqs + (lane & 7) * 9232 + (lane >> 3) * 384 + 48 * warp;
        uint4 a[12];
#pragma unroll
        for (int kk = 0; kk < 12; kk++) a[kk] = lds128(sb + RD_QN + kk * 512 + lane * 16);
        mbar_wait(wbar + (lane & 7) * 8, 0);
        __syncwarp();
        if (threadIdx.x == 0) TSP(4, 0);
#pragma unroll
        for (int kp = 0; kp < 6; kp++)
#pragma unroll
            for (int i = 0; i < 3; i++) {
                uint32_t bb[4];
                ldsm4t(bb, ba + kp * 1536 + i * 16);
                mma(acc[0][i], a[2 * kp].x, a[2 * kp].y, a[2 * kp].z, a[2 * kp].w, bb[0], bb[1]);
                mma(acc[1][i], a[2 * kp + 1].x, a[2 * kp + 1].y, a[2 * kp + 1].z, a[2 * kp + 1].w, bb[2], bb[3]);
            }
        if (threadIdx.x == 0) TSP(7, u(acc[1][2][3]));
        float kq[2][4] = {{0.f, 0.f, 0.f, 0.f}, {0.f, 0.f, 0.f, 0.f}};
#pragma unroll
        for (int j = 0; j < 3; j++) {
            const uint32_t a0 = pack2(acc[0][j][0] + acc[1][j][0], acc[0][j][1] + acc[1][j][1]), a1 = pack2(acc[0][j][2] + acc[1][j][2], acc[0][j][3] + acc[1][j][3]);
            mma8(kq[0], a0, a1, wkf[0][j]);
            mma8(kq[1], a0, a1, wkf[1][j]);
        }
        if (warp < 7) {
            sts128(sb + RD_KQ + warp * 1024 + lane * 16, u(kq[0][0]), u(kq[0][1]), u(kq[0][2]), u(kq[0][3]));
            sts128(sb + RD_KQ + warp * 1024 + 512 + lane * 16, u(kq[1][0]), u(kq[1][1]), u(kq[1][2]), u(kq[1][3]));
            bar_arrive(B_Q, 256);
        } else {
            bar_sync(B_Q, 256);
#pragma unroll
            for (int w = 0; w < 7; w++)
#pragma unroll
                for (int i = 0; i < 2; i++) {
                    const uint4 o = lds128(sb + RD_KQ + w * 1024 + i * 512 + lane * 16);
                    kq[i][0] += f(o.x); kq[i][1] += f(o.y); kq[i][2] += f(o.z); kq[i][3] += f(o.w);
                }
            stg_relaxed(g_qk + b * 32 + lane, ~pack2(kq[0][0] * QSCALE, kq[0][1] * QSCALE), ~pack2(kq[0][2] * QSCALE, kq[0][3] * QSCALE),
                        ~pack2(kq[1][0] * QSCALE, kq[1][1] * QSCALE), ~pack2(kq[1][2] * QSCALE, kq[1][3] * QSCALE));
            if (lane == 0) TS(10);
        }
    } else if (warp == 8 && !(b & 1)) {
#pragma unroll
        for (int i = 0; i < 2; i++) stg_relaxed(reinterpret_cast<uint4*>(ap + acc_line(b >> 1, 4 * i + (lane >> 3))) + (lane & 7), 0, 0, 0, 0);
        __threadfence();
    } else if (b >= NSRC) {
        if (b == NSRC && warp == 0) stg_relaxed32(g_mmax + lane, 0);
        const unsigned c0 = clock32();
        for (int it = 0; it < 8; it++) {
            __nanosleep(500);
            if (clock32() - c0 > 4400) break;
        }
    }
    bar_sync(B_ALL, NTHREADS);

#pragma unroll 1
    for (int r = 0; r < 3; r++) {
        uint4 v[8];
#pragma unroll
        for (int k = 0; k < 8; k++) {
            const int idx = (8 * r + k) * 384 + threadIdx.x;
            v[k] = __ldg(reinterpret_cast<const uint4*>(idx < 4608 ? wv : wo - C * C) + idx);
        }
#pragma unroll
        for (int k = 0; k < 8; k++) {
            const int idx = (8 * r + k) * 384 + threadIdx.x, row = idx / 24;
            sts128(sb + RD_W + row * WROW + (idx - 24 * row) * 16, v[k].x, v[k].y, v[k].z, v[k].w);
        }
    }
    bar_sync(B_ALL, NTHREADS);
    if (warp < 6) {
        const int col = 96 * (b & 1) + 16 * warp;
        float d[24][4];
#pragma unroll
        for (int i = 0; i < 24; i++) d[i][0] = d[i][1] = d[i][2] = d[i][3] = 0.f;
        const int mi = lane >> 3, r = lane & 7;
        const uint32_t aa = sb + RD_W + (C + (mi >> 1) * 8 + r) * WROW + (col + (mi & 1) * 8) * 2;
        const uint32_t ba = sb + RD_W + ((mi >> 1) * 8 + r) * WROW + (mi & 1) * 16;
#pragma unroll 1
        for (int kk = 0; kk < 12; kk++) {
            uint32_t a[4];
            ldsm4t(a, aa + kk * 16 * WROW);
#pragma unroll
            for (int i = 0; i < 12; i++) {
                uint32_t bb[4];
                ldsm4(bb, ba + i * 16 * WROW + kk * 32);
                mma(d[2 * i], a[0], a[1], a[2], a[3], bb[0], bb[1]);
                mma(d[2 * i + 1], a[0], a[1], a[2], a[3], bb[2], bb[3]);
            }
        }
        float c0 = 0.f, c1 = 0.f, m0 = 0.f, m1 = 0.f;
#pragma unroll
        for (int i = 0; i < 24; i++) { c0 += d[i][0] + d[i][1]; c1 += d[i][2] + d[i][3]; }
        c0 += __shfl_xor_sync(~0u, c0, 1); c1 += __shfl_xor_sync(~0u, c1, 1);
        c0 += __shfl_xor_sync(~0u, c0, 2); c1 += __shfl_xor_sync(~0u, c1, 2);
        c0 *= 1.f / C; c1 *= 1.f / C;
#pragma unroll
        for (int i = 0; i < 24; i++) {
            d[i][0] -= c0; d[i][1] -= c0; d[i][2] -= c1; d[i][3] -= c1;
            m0 = fmaxf(m0, fmaxf(fabsf(d[i][0]), fabsf(d[i][1]))); m1 = fmaxf(m1, fmaxf(fabsf(d[i][2]), fabsf(d[i][3])));
        }
        m0 = fmaxf(m0, __shfl_xor_sync(~0u, m0, 1)); m1 = fmaxf(m1, __shfl_xor_sync(~0u, m1, 1));
        m0 = fmaxf(m0, __shfl_xor_sync(~0u, m0, 2)); m1 = fmaxf(m1, __shfl_xor_sync(~0u, m1, 2));
        const uint32_t e0 = min(max(u(m0) >> 23, 12u), 254u), e1 = min(max(u(m1) >> 23, 12u), 254u);
        const float s0 = f((265u - e0) << 23), s1 = f((265u - e1) << 23);
        const bool k0 = fabsf(c0) < INFINITY, k1 = fabsf(c1) < INFINITY;
#pragma unroll
        for (int j = 0; j < 6; j++) {
            const int n[4] = {j < 4 ? j : 8 + 2 * j, j < 4 ? 4 + j : 12 + 2 * j, j < 4 ? 8 + j : 9 + 2 * j, j < 4 ? 12 + j : 13 + 2 * j};
            uint32_t a[2][4];
#pragma unroll
            for (int e = 0; e < 4; e++) {
                a[0][e] = k0 ? packh(d[n[e]][0] * s0, d[n[e]][1] * s0) : 0u;
                a[1][e] = k1 ? packh(d[n[e]][2] * s1, d[n[e]][3] * s1) : 0u;
            }
#pragma unroll
            for (int e = 0; e < 2; e++) sts128(sb + RD_A + ((2 * warp + e) * 6 + j) * 512 + lane * 16, a[e][0], a[e][1], a[e][2], a[e][3]);
        }
        sts32(sb + RD_WS + 2 * warp * 128 + lane * 4, k0 ? (e0 - 11u) << 23 : u(c0));
        sts32(sb + RD_WS + (2 * warp + 1) * 128 + lane * 4, k1 ? (e1 - 11u) << 23 : u(c1));
        if (warp < 4) bar_sync(B_PARK, 192); else bar_arrive(B_PARK, 192);
        if (threadIdx.x == 0) TSE(6);
    }
    if (warp >= 4) {
        if (threadIdx.x == 128) {
            uint32_t m;
            for (int it = 0;; it++) {
                const int left = NT - 2 * NST * GS - (int)ldg_relaxed32(g_ctr);
                m = ldg_relaxed32(g_mmax + b);
                if (left <= REFT && m) break;
                if (left <= 0) { m = 0x80000000u; break; }
                if (it > SPIN_LIMIT) __trap();
                __nanosleep(300);
            }
            if (b & 1) for (int it = 0;; it++) {
                uint32_t r;
                asm volatile("ld.acquire.gpu.global.u32 %0, [%1];" : "=r"(r) : "l"(g_mref + b - 1) : "memory");
                if (r) break;
                if (it > SPIN_LIMIT) __trap();
            }
            asm volatile("st.release.gpu.global.u32 [%0], %1;" ::"l"(g_mref + b), "r"(~u(f(m >> 31 ? m ^ 0x80000000u : ~m) + 8.f)) : "memory");
            TSE(7);
        }
        __syncwarp();
        if (warp == 4) {
            uint4* p0 = g_qk + min(b, NSRC - 1) * 32 + lane;
            unsigned* p1 = lane == 1 && b == NSRC ? g_ctr : g_mref + b;
            asm volatile("" : "+l"(p0), "+l"(p1));
            bar_arrive(B_CLEAN, NTHREADS);
            bar_sync(B_RDY, 192);
            *p0 = make_uint4(0, 0, 0, 0);
            *p1 = 0;
            return;
        }
        bar_sync(B_CLEAN, NTHREADS);
        if (warp >= 5 + NPW) return;
        const uint4* const pa = reinterpret_cast<const uint4*>(ap + acc_line(b >> 1, lane >> 3)) + (lane & 7);
        const uint32_t bw = opaque(sb + brow(lane & 7) + (lane >> 3) * 16);
        const uint32_t n0 = packh(0.f, (float)GS), nstart = packh(0.f, (float)POLLN);
        for (int it = 0; ldg_relaxed32(ap + acc_line(b >> 1, 0) + 12) < nstart; it++)
            if (it > SPIN_LIMIT) __trap();
        for (const unsigned c = clock32(); clock32() - c < (warp - 5) * PGAP;) {}
        for (int it = 0;; it++) {
            const uint4 a0 = ldg_relaxed(pa), b0 = ldg_relaxed(pa + 1024);
            if (it > SPIN_LIMIT) __trap();
            bar_sync(B_WARP, 32);
            asm volatile("{.reg .pred p, q; .reg .b32 a; setp.ge.u32 p, %5, %10; setp.ge.and.u32 p, %9, %10, p; vote.sync.all.pred q, p, 0xffffffff; selp.b32 a, %0, %1, p;"
                         " st.shared.v4.b32 [a], {%2,%3,%4,%5}; st.shared.v4.b32 [a + 704], {%6,%7,%8,%9}; @q bar.arrive 15, 192; @q exit;}"
                         ::"r"(bw), "r"(bw - (RD_B - RD_QN)), "r"(a0.x), "r"(a0.y), "r"(a0.z), "r"(a0.w), "r"(b0.x), "r"(b0.y), "r"(b0.z), "r"(b0.w), "r"(n0) : "memory");
        }
    }
    const uint32_t br = opaque(sb + brow(8 * (g & 1) + 2 * (g & 2) + t));
    const bool hi = t >= 2;
    const int oi = (first_row() + (t & 1)) * C + 96 * (b & 1) + 24 * warp + g;
    const float qv0 = __bfloat162float(q[oi + 4 * (t & 2)]), qv1 = __bfloat162float(q[oi + 16]);
    const float ws0 = f(lds32(sb + RD_WS + (3 * warp + (t >> 1)) * 128 + lane * 4)), ws1 = f(lds32(sb + RD_WS + (3 * warp + 2) * 128 + lane * 4));
    __nv_bfloat16* op0 = out + oi + 4 * (t & 2), * op1 = out + oi + 16;
    asm volatile("" : "+l"(op0), "+l"(op1));
    const uint32_t ar = sb + RD_A + warp * 18 * 512 + lane * 16;
    project<true>(ar, br, hi, ws0, ws1, qv0, qv1, op0, op1, scr);
    slow_rows(f0, f1, q, wq, wk, sb);
    project<false>(ar, br + RD_B2, hi, ws0, ws1, qv0, qv1, op0, op1, scr);
}

__global__ void __launch_bounds__(NTHREADS, 1)
attn_main(const char* __restrict__ f0, const char* __restrict__ f1,
          const __nv_bfloat16* __restrict__ q, const __nv_bfloat16* __restrict__ wq, const __nv_bfloat16* __restrict__ wk, Scratch* scr,
          const __nv_bfloat16* __restrict__ wv, const __nv_bfloat16* __restrict__ wo, __nv_bfloat16* __restrict__ out,
          const __grid_constant__ CUtensorMap m0, const __grid_constant__ CUtensorMap m1)
{
    extern __shared__ char smem_raw[];
    const uint32_t sb = (s2u(smem_raw) + 1023u) & ~1023u;
    const int G = gridDim.x - NRD;
    const int b = blockIdx.x - NRD;
    if (threadIdx.x < 32 && b >= 0 && f0 != nullptr) {
        const int l = threadIdx.x;
        const uint32_t o1 = l < 16 ? 8192 : W0 * C * 2 - 4096;
#pragma unroll
        for (int n = 0; n < 2; n++) {
            const int pr = b + n * G;
            const char* x = f0 + (uint32_t)(pr * (4 * TP * C * 2) + (pr >> 4) * (W0 * C * 2)) + l * 256;
            prefetch_line(x); prefetch_line(x + o1); prefetch_line(x + W0 * C * 2 + 4096);
            if (l < 24) prefetch_line(f1 + pr * (2 * TP * C * 2) + l * 256);
        }
        if (l == 0) prefetch_l2((const char*)(b % (2 * WSL) < WSL ? wq : wk) + b % WSL * (C * C * 2 / WSL), C * C * 2 / WSL);
    }
    if (b < 0) { reducer(f0, f1, q, wq, wk, scr, wv, wo, out, sb, G); return; }
    const int warp = __shfl_sync(~0u, threadIdx.x >> 5, 0), lane = laneid();
    const int g = lane >> 2, t = lane & 3;

    if (warp >= 8) {
        if (warp < 10) {
            const int p = warp - 8;
            const unsigned c0 = clock32();
            const uint32_t sbp = opaque(sb), bar = sbp + SM_BAR + p * 8;
            uint64_t pol; asm volatile("createpolicy.fractional.L2::evict_first.b64 %0, 1.0;" : "=l"(pol));
            if (elect()) {
                if (p == 0) TS(0);
                asm volatile("prefetch.tensormap [%0];" ::"l"(p ? &m1 : &m0) : "memory");
#pragma unroll
                for (int n = 0; n < NI; n++) mbar_init(bar + n * 16, 2);
                asm volatile("fence.mbarrier_init.release.cluster;" ::: "memory");
#pragma unroll
                for (int n = 0; n < NI; n++) {
                    mbar_expect(bar + n * 16, STAGE);
                    issue_tile(&m0, &m1, sbp, p + 2 * n, 2 * b + p + 2 * n * G, pol);
                    TR(0, 2 * n + p);
                    sts32(sbp + SM_FLAG + (p + 2 * n) * 4, 0);
                    mbar_arrive(bar + n * 16);
                }
#pragma unroll
                for (int n = 0; n < NS / 2; n++) {
                    if (n >= NI) mbar_init(bar + n * 16, 2);
                    mbar_init(bar + NS * 8 + n * 16, 1);
                }
                if (p == 0) mbar_init(sbp + SM_REF, 1);
                asm volatile("fence.mbarrier_init.release.cluster;" ::: "memory");
            }
            __syncwarp();
            bar_arrive(B_QK, NTHREADS);
            if (elect()) {
                int tl = 2 * b + p + 2 * NI * G;
                int s = p + 2 * NI; uint32_t ph = 1;
                int sa = p, na = 0; uint32_t pa = 0;
                bool late = false;
                for (int n = NI;; n++) {
                    const int d = n < NRAMP ? D0 : (tl >= NT - (TA) ? 1 : D1);
                    mbar_wait(sbp + SM_BAR + (NS + s) * 8, ph);
                    mbar_expect(sbp + SM_BAR + s * 8, STAGE);
                    if (n < NPACE) while (clock32() - c0 < (n ? T1 + (2 * (n - 1) + p) * TG : T0)) {}
                    while (n - na >= d) {
                        mbar_wait(sbp + SM_BAR + sa * 8, pa);
                        if (na < NS / 2) TR(1, 2 * na + p);
                        na++; sa += 2;
                        if (sa >= NS) { sa -= NS; pa ^= 1; }
                    }
                    issue_tile(&m0, &m1, sbp, s, tl, pol);
                    TR(0, 2 * n + p);
                    int nxt = tl + 2 * G;
                    if (n >= NST - 1) nxt = grab_tile(g_ctr) + 2 * NST * G;
                    const bool last = nxt >= NT;
                    uint32_t flag = last;
                    if (!late && nxt >= NT - MAXT - 16 * b) { late = true; flag |= 2; }
                    if (last) mbar_wait(sbp + SM_REF, 0);
                    sts32(sbp + SM_FLAG + s * 4, flag);
                    mbar_arrive(sbp + SM_BAR + s * 8);
                    if (last) break;
                    s += 2;
                    if (s >= NS) { s -= NS; ph ^= 1; }
                    tl = nxt;
                }
                if (p) TSE(5);
            }
            return;
        }
        const int h = threadIdx.x - 320;
        uint4 v[6];
        for (int it = 0;; it++) {
            bool miss = false;
#pragma unroll
            for (int k = 0; k < 6; k++) v[k] = ldg_relaxed(g_qk + k * 64 + h);
#pragma unroll
            for (int k = 0; k < 6; k++) miss |= has(v[k], 0);
            if (!miss) break;
            if (it > SPIN_LIMIT) __trap();
            if (it == 0) __nanosleep(QSLEEP);
        }
#pragma unroll
        for (int k = 0; k < 6; k++) sts128(sb + SM_QK + (k * 64 + h) * 16, ~v[k].x, ~v[k].y, ~v[k].z, ~v[k].w);
        __syncwarp();
        bar_sync(B_QK, NTHREADS);
        if (warp == 11) return;
        uint32_t r = 1;
        for (int it = 0;; it++) {
            __nanosleep(500);
            if (lane < NQ) asm volatile("ld.acquire.gpu.global.u32 %0, [%1];" : "=r"(r) : "l"(g_mref + lane) : "memory");
            if (__all_sync(~0u, r != 0)) break;
            if (it > SPIN_LIMIT) __trap();
        }
        if (lane < NQ) sts32(sb + SM_M + lane * 4, ~r);
        __syncwarp();
        if (lane == 0) { mbar_arrive(sb + SM_REF); TSE(7); }
        return;
    }

    const int grp = warp >> 2, cw = warp & 3;
    const int xp = lane & 7, mi = lane >> 3;
    const uint32_t offS1 = opaque(12288 + xp * 128 + ((mi ^ xp) << 4)), offS1x = opaque(offS1 ^ 64);
    const uint32_t offS0 = opaque(offS1 - 12288 + cw * 3072), offS0x = opaque(offS0 ^ 64);
    const uint32_t offT = opaque(mi * 3072 + xp * 128 + (((cw + 4 * grp) ^ xp) << 4)), offTx = opaque(offT ^ 64);
    const uint32_t offU = opaque(12288 + (mi % 3) * 1024 + xp * 128 + (((cw + 4 * (grp ^ (mi / 3))) ^ xp) << 4));
    const uint32_t offV = opaque(12288 + (1 + (mi & 1)) * 1024 + xp * 128 + (((cw + 4 * (grp ^ 1)) ^ xp) << 4));
    const int shl = opaque(9 * t), shl4 = opaque(9 * t + 4);
    const uint32_t pw = opaque((cw >> 1) * 512 + lane * 16 + (cw & 1) * 8), muw = opaque(1024 + t * 16 + cw * 4);
    const uint32_t prd = opaque(lane * 16), mur = opaque(1024 + t * 16), mof = g * 4;
    uint32_t pb0 = sb + SM_P + grp * 2 * PBUF;
    const uint32_t pbx = pb0 ^ (pb0 + PBUF);
    const bool odd = g & 1;
    const int barid = B_GRP + grp;
    const bool elected = cw == 3 && lane == 0;

    uint32_t qa[48];
    float r_lo, r_hi;
    bar_sync(B_QK, NTHREADS);
    {
        float rr[2][4] = {{0.f, 0.f, 0.f, 0.f}, {0.f, 0.f, 0.f, 0.f}};
#pragma unroll
        for (int kk = 0; kk < 12; kk++) {
            const uint4 v = lds128(sb + SM_QK + kk * 512 + lane * 16);
            qa[4 * kk] = v.x; qa[4 * kk + 1] = v.y; qa[4 * kk + 2] = v.z; qa[4 * kk + 3] = v.w;
            mma(rr[kk & 1], v.x, v.y, v.z, v.w, ONES, ONES);
        }
        r_lo = rr[0][0] + rr[1][0]; r_hi = rr[0][2] + rr[1][2];
    }
    if (threadIdx.x == 0) TS(1);

    float acc[6][4];
#pragma unroll
    for (int i = 0; i < 6; i++) acc[i][0] = acc[i][1] = acc[i][2] = acc[i][3] = 0.f;
    float m_lo = -INFINITY, m_hi = -INFINITY, l_lo = 0.f, l_hi = 0.f;
    float cm[4] = {0.f, 0.f, 0.f, 0.f};
    uint32_t xt[6][4], yt[6]; uint4 pa, pb, mv;
    uint4* dst = reinterpret_cast<uint4*>(reinterpret_cast<char*>(g_acc) + acc_line(g >> 1, warp) + (lane & 7) * 16);
    asm volatile("" : "+l"(dst));
    const uint32_t xof = __shfl_sync(~0u, 512 - lane * 8, lane);
    uint32_t ref_lo = 0, ref_hi = 0;
    const uint32_t mad = __shfl_sync(~0u, sb + SM_M + mof, lane);
    uint32_t one[2];
#pragma unroll
    for (int i = 0; i < 2; i++) one[i] = __shfl_sync(~0u, ONES + ((lane + i) >> (G >> 16) >> 16), lane);
    uint32_t st = sb + SM_STAGES + grp * STAGE;
    int s = grp; uint32_t ph = 0;
    while (true) {
        mbar_wait(sb + SM_BAR + s * 8, ph);
        PH(0, 0);
        const uint32_t stop = lds32(sb + SM_FLAG + s * 4);
        float sc[2][4], gr[2][4];
#pragma unroll
        for (int e = 0; e < 4; e++) sc[0][e] = sc[1][e] = gr[0][e] = gr[1][e] = 0.f;
#pragma unroll
        for (int qq = 0; qq < 6; qq++) {
            uint32_t x[4], y[4];
            ldsm4(x, st + (qq & 1 ? offS0x : offS0) + (qq >> 1) * 1024);
            ldsm4(y, st + (qq & 1 ? offS1x : offS1) + (qq >> 1) * 1024);
            uint32_t z[4];
#pragma unroll
            for (int e = 0; e < 4; e++) asm("fma.rn.bf16x2 %0, %1, %2, %3;" : "=r"(z[e]) : "r"(x[e]), "r"(one[e & 1]), "r"(y[e]));
#pragma unroll
            for (int e = 0; e < 4; e++) x[e] = hadd2(x[e], y[e]);
            mma(gr[0], z[0], one[0], z[1], one[1], x[0], x[1]);
            mma(gr[1], z[2], one[0], z[3], one[1], x[2], x[3]);
            mma(sc[0], qa[8 * qq], qa[8 * qq + 1], qa[8 * qq + 2], qa[8 * qq + 3], x[0], x[1]);
            mma(sc[1], qa[8 * qq + 4], qa[8 * qq + 5], qa[8 * qq + 6], qa[8 * qq + 7], x[2], x[3]);
        }
        ldsm4t(yt, st + offU);
        ldsm2t(yt + 4, st + offV);
#pragma unroll
        for (int i = 0; i < 6; i++) ldsm4t(xt[i], st + (i < 3 ? offT : offTx) + (i % 3) * 1024);

        const float mu0 = (gr[0][2] + gr[1][2]) * (1.f / C), mu1 = (gr[0][3] + gr[1][3]) * (1.f / C);
        const float mu = odd ? mu1 : mu0, ss = odd ? gr[0][1] + gr[1][1] : gr[0][0] + gr[1][0];
        const float rs = rsq(fmaxf(fmaf(-mu, mu, fmaf(ss, 1.f / C, 1e-5f)), 1e-5f));
        const float rs0 = __shfl_sync(~0u, rs, shl), rs1 = __shfl_sync(~0u, rs, shl4);
        const float u0 = fmaf(-mu0, r_lo, sc[0][0] + sc[1][0]), u1 = fmaf(-mu1, r_lo, sc[0][1] + sc[1][1]);
        const float u2 = fmaf(-mu0, r_hi, sc[0][2] + sc[1][2]), u3 = fmaf(-mu1, r_hi, sc[0][3] + sc[1][3]);
        const float d0 = fmaf(u0, rs0, -m_lo), d1 = fmaf(u1, rs1, -m_lo), d2 = fmaf(u2, rs0, -m_hi), d3 = fmaf(u3, rs1, -m_hi);
        PH(1, u(d0 + d2));
        float p0 = ex2(d0), p1 = ex2(d1), p2 = ex2(d2), p3 = ex2(d3);
        sts64(pb0 + pw, pack2(p0 * rs0, p1 * rs1), pack2(p2 * rs0, p3 * rs1));
        if (lane < 4) sts32(pb0 + muw, pack2(mu0, mu1));
        asm volatile("{.reg .pred p; setp.ne.u32 p, %2, 0; @p ld.shared.b32 %0, [%3]; @p ld.shared.b32 %1, [%3+32];}" : "+r"(ref_lo), "+r"(ref_hi) : "r"(stop & 1), "r"(mad) : "memory");
        const bool over = bar_any(barid, 128, fmaxf(fmaxf(d0, d1), fmaxf(d2, d3)) > LAZY);
        PH(3, 0);
        pa = lds128(pb0 + prd); pb = lds128(pb0 + prd + 512); mv = lds128(pb0 + mur);
        if (stop & 1) { l_lo += p0 + p1; l_hi += p2 + p3; break; }
        if (elected) mbar_arrive(sb + SM_BAR + (NS + s) * 8);
        if (__builtin_expect(over, 0)) {
            const int ln = laneid(), g = ln >> 2, t = ln & 3;
            const float s0 = u0 * rs0, s1 = u1 * rs1, s2 = u2 * rs0, s3 = u3 * rs1;
            float xl = fmaxf(s0, s1), xh = fmaxf(s2, s3);
            xl = fmaxf(xl, __shfl_xor_sync(~0u, xl, 1)); xh = fmaxf(xh, __shfl_xor_sync(~0u, xh, 1));
            xl = fmaxf(xl, __shfl_xor_sync(~0u, xl, 2)); xh = fmaxf(xh, __shfl_xor_sync(~0u, xh, 2));
            if (t < 2) sts32(sb + SM_MX + grp * 256 + ((g + 8 * t) * 4 + cw) * 4, u(t ? xh : xl));
            bar_sync(B_MAX + grp, 128);
            const uint4 ml4 = lds128(sb + SM_MX + grp * 256 + g * 16), mh4 = lds128(sb + SM_MX + grp * 256 + g * 16 + 128);
            const float nl = fmaxf(fmaxf(fmaxf(f(ml4.x), f(ml4.y)), fmaxf(f(ml4.z), f(ml4.w))), m_lo);
            const float nh = fmaxf(fmaxf(fmaxf(f(mh4.x), f(mh4.y)), fmaxf(f(mh4.z), f(mh4.w))), m_hi);
            p0 = ex2(s0 - nl); p1 = ex2(s1 - nl); p2 = ex2(s2 - nh); p3 = ex2(s3 - nh);
            sts64(pb0 + pw, pack2(p0 * rs0, p1 * rs1), pack2(p2 * rs0, p3 * rs1));
            const float al = ex2(m_lo - nl), ah = ex2(m_hi - nh);
            m_lo = nl; m_hi = nh;
            l_lo *= al; l_hi *= ah; cm[0] *= al; cm[2] *= ah;
#pragma unroll
            for (int i = 0; i < 6; i++) { acc[i][0] *= al; acc[i][1] *= al; acc[i][2] *= ah; acc[i][3] *= ah; }
            bar_sync(B_MAX + grp, 128);
            pa = lds128(pb0 + prd); pb = lds128(pb0 + prd + 512);
        }
        l_lo += p0 + p1; l_hi += p2 + p3;
#pragma unroll
        for (int i = 0; i < 6; i++) mma(acc[i], pa.x, pa.y, pa.z, pa.w, hadd2v(xt[i][0], yt[i]), hadd2v(xt[i][1], yt[i]));
        mma(cm, pa.x, pa.y, pa.z, pa.w, mv.x, mv.y);
#pragma unroll
        for (int i = 0; i < 6; i++) mma(acc[i], pb.x, pb.y, pb.z, pb.w, hadd2v(xt[i][2], yt[i]), hadd2v(xt[i][3], yt[i]));
        mma(cm, pb.x, pb.y, pb.z, pb.w, mv.z, mv.w);
        PH(4, u(acc[5][0]));
        if (stop) {
            const int ln = laneid(), g = ln >> 2, t = ln & 3;
            float a = l_lo + __shfl_xor_sync(~0u, l_lo, 1), c = l_hi + __shfl_xor_sync(~0u, l_hi, 1);
            a += __shfl_xor_sync(~0u, a, 2); c += __shfl_xor_sync(~0u, c, 2);
            const uint32_t m = u((t ? m_hi : m_lo) + lg2(fmaxf(t ? c : a, 1.f)));
            if (t < 2) asm volatile("red.relaxed.gpu.global.max.u32 [%0], %1;" ::"l"(g_mmax + g + 8 * t), "r"(m >> 31 ? ~m : m | 0x80000000u) : "memory");
        }
        pb0 ^= pbx;
        s += 2;
        st += 2 * STAGE;
        if (s >= NS) { s -= NS; ph ^= 1; st -= NS * STAGE; }
        asm volatile("" : "+r"(st));
    }
    const float al = ex2(m_lo - f(ref_lo)), ah = ex2(m_hi - f(ref_hi));
    mma(cm, pa.x, pa.y, pa.z, pa.w, mv.x, mv.y);
#pragma unroll
    for (int i = 3; i < 6; i++) mma(acc[i], pa.x, pa.y, pa.z, pa.w, hadd2v(xt[i][0], yt[i]), hadd2v(xt[i][1], yt[i]));
    mma(cm, pb.x, pb.y, pb.z, pb.w, mv.z, mv.w);
#pragma unroll
    for (int i = 3; i < 6; i++) mma(acc[i], pb.x, pb.y, pb.z, pb.w, hadd2v(xt[i][2], yt[i]), hadd2v(xt[i][3], yt[i]));
#pragma unroll
    for (int i = 0; i < 3; i++) mma(acc[i], pa.x, pa.y, pa.z, pa.w, hadd2v(xt[i][0], yt[i]), hadd2v(xt[i][1], yt[i]));
#pragma unroll
    for (int i = 0; i < 3; i++) mma(acc[i], pb.x, pb.y, pb.z, pb.w, hadd2v(xt[i][2], yt[i]), hadd2v(xt[i][3], yt[i]));
    if (threadIdx.x == grp * 128) TSE(2 + grp);
    if (threadIdx.x == grp * 128 + 96) TSX(2 + grp, u(acc[5][0]));

    const uint32_t xw = sb + SM_STAGES + grp * STAGE + cw * 768 + prd, xr = sb + SM_STAGES + (grp ^ 1) * STAGE + cw * 768 + prd;
    const float cl = -cm[0] * al, ch = -cm[2] * ah;
    uint32_t hl[6], hh[6];
#pragma unroll
    for (int i = 3; i < 6; i++) { hl[i] = packh(fmaf(acc[i][0], al, cl), fmaf(acc[i][1], al, cl)); hh[i] = packh(fmaf(acc[i][2], ah, ch), fmaf(acc[i][3], ah, ch)); }
    sts128(xw, hl[3], hl[4], hl[5], hh[3]);
    sts64(xw + xof, hh[4], hh[5]);
#pragma unroll
    for (int i = 0; i < 3; i++) { hl[i] = packh(fmaf(acc[i][0], al, cl), fmaf(acc[i][1], al, cl)); hh[i] = packh(fmaf(acc[i][2], ah, ch), fmaf(acc[i][3], ah, ch)); }
    const uint32_t w_lo = packh(l_lo * al, 1.f), w_hi = packh(l_hi * ah, 1.f);
    bar_sync(B_MERGE, 256);
    if (threadIdx.x == 224) TSX(4, 0);
    const uint4 o = lds128(xr);
    const uint2 o2 = lds64(xr + xof);
    red8h(dst + ACC_HI / 16, haddh(hl[0], o.x), haddh(hl[1], o.y), haddh(hl[2], o.z), w_lo);
    for (const unsigned c = clock32(); clock32() - c < RDEL;) {}
    red8h(dst, haddh(hh[0], o.w), haddh(hh[1], o2.x), haddh(hh[2], o2.y), w_hi);
    if (threadIdx.x == 0) TSE(4);
    if (threadIdx.x == 224) TSX(9, 0);
}

typedef CUresult (*EncodeFn)(CUtensorMap*, CUtensorMapDataType, cuuint32_t, void*, const cuuint64_t*, const cuuint64_t*,
                             const cuuint32_t*, const cuuint32_t*, CUtensorMapInterleave, CUtensorMapSwizzle,
                             CUtensorMapL2promotion, CUtensorMapFloatOOBfill);

}

extern "C" void kernel_launch(void* const* d_in, const int* in_sizes, int n_in, void* d_out, int out_size) {
    const __nv_bfloat16* q = (const __nv_bfloat16*)d_in[0];
    char* f0 = (char*)d_in[1];
    char* f1 = (char*)d_in[2];
    const __nv_bfloat16* wq = (const __nv_bfloat16*)d_in[3];
    const __nv_bfloat16* wk = (const __nv_bfloat16*)d_in[4];
    const __nv_bfloat16* wv = (const __nv_bfloat16*)d_in[5];
    const __nv_bfloat16* wo = (const __nv_bfloat16*)d_in[6];

    static EncodeFn enc = nullptr;
    static int grid = 0;
    static Scratch* scr = nullptr;
    if (!enc) {
        void* fn = nullptr; cudaDriverEntryPointQueryResult qr;
        cudaGetDriverEntryPoint("cuTensorMapEncodeTiled", &fn, cudaEnableDefault, &qr);
        enc = (EncodeFn)fn;
        cudaGetSymbolAddress((void**)&scr, g_scratch);
        int dev = 0, sms = 0;
        cudaGetDevice(&dev);
        cudaDeviceGetAttribute(&sms, cudaDevAttrMultiProcessorCount, dev);
        grid = sms < MAXG ? sms : MAXG;
        cudaFuncSetAttribute(attn_main, cudaFuncAttributeMaxDynamicSharedMemorySize, SMEM_BYTES);
    }
    CUtensorMap m0, m1;
    {
        cuuint64_t dims[5] = {64, W1, 3, 2, W0};
        cuuint64_t str[4] = {2 * C * 2, 128, C * 2, (cuuint64_t)W0 * C * 2};
        cuuint32_t box[5] = {64, TP, 3, 2, 2}, es[5] = {1, 1, 1, 1, 1};
        enc(&m0, CU_TENSOR_MAP_DATA_TYPE_BFLOAT16, 5, f0, dims, str, box, es, CU_TENSOR_MAP_INTERLEAVE_NONE,
            CU_TENSOR_MAP_SWIZZLE_128B, CU_TENSOR_MAP_L2_PROMOTION_NONE, CU_TENSOR_MAP_FLOAT_OOB_FILL_NONE);
    }
    {
        cuuint64_t dims[4] = {64, W1, 3, W1};
        cuuint64_t str[3] = {C * 2, 128, (cuuint64_t)W1 * C * 2};
        cuuint32_t box[4] = {64, TP, 3, 1}, es[4] = {1, 1, 1, 1};
        enc(&m1, CU_TENSOR_MAP_DATA_TYPE_BFLOAT16, 4, f1, dims, str, box, es, CU_TENSOR_MAP_INTERLEAVE_NONE,
            CU_TENSOR_MAP_SWIZZLE_128B, CU_TENSOR_MAP_L2_PROMOTION_NONE, CU_TENSOR_MAP_FLOAT_OOB_FILL_NONE);
    }
    attn_main<<<grid, NTHREADS, SMEM_BYTES, cudaStreamPerThread>>>(f0, f1, q, wq, wk, scr, wv, wo, (__nv_bfloat16*)d_out, m0, m1);
}
```

```cpp
#include <cuda_runtime.h>
#include <cuda_bf16.h>
#include <cuda.h>
#include <stdint.h>
#include <stddef.h>

namespace {

constexpr int C = 192;
constexpr int NQ = 16;
constexpr int W0 = 512;
constexpr int W1 = 256;
constexpr int TP = 8;
constexpr int NT = W1 * W1 / TP;
constexpr int STAGE = TP * 5 * C * 2;
#define NS 14
#define D0 3
#define D1 2
#define NRAMP 5
#define TA (p ? NT : 100 + 6 * b)
#define QSLEEP 700
#define MAXT 3000
#define REFT 1800
#define POLLN 1
#define PGAP 120
#define NPW 4
#define LAZY 12.f
#define RDEL 20
#define NST 4
#define NI 1
#define NPACE 5
#define T0 0
#define T1 1600
#define TG 960
static_assert(NST > D0, "the first dynamic tile index must not delay the start");
constexpr int NTHREADS = 384;
constexpr int MAXG = 132;
constexpr int NRD = NQ;
constexpr int NSRC = 12;
constexpr int SPIN_LIMIT = 1 << 22;

constexpr int SM_STAGES = 0;
constexpr int SM_P = NS * STAGE;
constexpr int PBUF = 1088;
constexpr int SM_QK = SM_P + 4 * PBUF;
constexpr int SM_MX = SM_QK + 6144;
constexpr int SM_M = SM_MX + 512;
constexpr int SM_BAR = SM_M + 64;
constexpr int SM_REF = SM_BAR + 16 * NS;
constexpr int SM_FLAG = SM_REF + 8;
constexpr int SM_TOTAL = SM_FLAG + 4 * NS;
constexpr int SMEM_BYTES = SM_TOTAL + 1024;
static_assert(SMEM_BYTES <= 232448, "smem");
constexpr int WROW = 400;
constexpr int RD_W = 0;
constexpr int RD_QN = 2 * C * WROW;
constexpr int RD_KQ = RD_QN + 6144;
constexpr int RD_B = RD_KQ + 7168;
constexpr int RD_B2 = 17 * 80;
constexpr int RD_BAR = RD_B + 2 * RD_B2;
constexpr int RD_A = RD_BAR + 64;
constexpr int RD_WS = RD_A + 12 * 6 * 512;
static_assert(RD_WS + 12 * 128 <= SM_TOTAL, "smem");

struct Scratch {
    uint4 acc[2816];
    uint4 qk[NSRC * 32];
    unsigned ctr[32];
    unsigned mmax[32];
    unsigned mref[32];
    uint4 acc_hi[4096];
};
__device__ __align__(131072) Scratch g_scratch;
#define g_acc (scr->acc)
#define g_qk (scr->qk)
#define g_ctr (scr->ctr)
#define g_mmax (scr->mmax)
#define g_mref (scr->mref)
#define g_ts (scr->ts)
#define g_tr (scr->tr)
#define TR(k, i) do {} while (0)
#define TS(i) do {} while (0)
#define TSD(i, dep) do {} while (0)
#define TSX(i, dep) do {} while (0)
#define TSP(i, dep) do {} while (0)
#define TSE(i) TS(i)
#define CK_(i, dep) do {} while (0)
#define PH(i, dep) do {} while (0)

__device__ __forceinline__ uint32_t s2u(const void* p) { return (uint32_t)__cvta_generic_to_shared(p); }
__device__ __forceinline__ void mbar_init(uint32_t a, int c) { asm volatile("mbarrier.init.shared::cta.b64 [%0], %1;" ::"r"(a), "r"(c) : "memory"); }
__device__ __forceinline__ void mbar_expect(uint32_t a, uint32_t b) { asm volatile("mbarrier.arrive.expect_tx.shared::cta.b64 _, [%0], %1;" ::"r"(a), "r"(b) : "memory"); }
__device__ __forceinline__ void mbar_arrive(uint32_t a) { asm volatile("mbarrier.arrive.shared::cta.b64 _, [%0];" ::"r"(a) : "memory"); }
__device__ __forceinline__ void mbar_wait(uint32_t a, uint32_t ph) {
    uint32_t ok; int it = 0;
    do {
        asm volatile("{.reg .pred p; mbarrier.try_wait.parity.shared::cta.b64 p, [%1], %2; selp.u32 %0,1,0,p;}" : "=r"(ok) : "r"(a), "r"(ph) : "memory");
        if (++it > SPIN_LIMIT) __trap();
    } while (!ok);
}
__device__ __forceinline__ bool elect() {
    uint32_t r; asm volatile("{.reg .pred p; elect.sync _|p, 0xffffffff; selp.u32 %0, 1, 0, p;}" : "=r"(r)); return r;
}
__device__ __forceinline__ void bar_sync(int id, int n) { asm volatile("bar.sync %0, %1;" ::"r"(id), "r"(n) : "memory"); }
__device__ __forceinline__ bool bar_any(int id, int n, bool c) {
    uint32_t r;
    asm volatile("{.reg .pred p, q; setp.ne.u32 q, %3, 0; bar.red.or.pred p, %1, %2, q; selp.u32 %0, 1, 0, p;}" : "=r"(r) : "r"(id), "r"(n), "r"((uint32_t)c) : "memory");
    return r;
}
__device__ __forceinline__ void bar_arrive(int id, int n) { asm volatile("bar.arrive %0, %1;" ::"r"(id), "r"(n) : "memory"); }
__device__ __forceinline__ void ldsm4(uint32_t* r, uint32_t a) {
    asm volatile("ldmatrix.sync.aligned.m8n8.x4.shared.b16 {%0,%1,%2,%3}, [%4];" : "=r"(r[0]), "=r"(r[1]), "=r"(r[2]), "=r"(r[3]) : "r"(a) : "memory");
}
__device__ __forceinline__ void ldsm4t(uint32_t* r, uint32_t a) {
    asm volatile("ldmatrix.sync.aligned.m8n8.x4.trans.shared.b16 {%0,%1,%2,%3}, [%4];" : "=r"(r[0]), "=r"(r[1]), "=r"(r[2]), "=r"(r[3]) : "r"(a) : "memory");
}
__device__ __forceinline__ void ldsm2t(uint32_t* r, uint32_t a) {
    asm volatile("ldmatrix.sync.aligned.m8n8.x2.trans.shared.b16 {%0,%1}, [%2];" : "=r"(r[0]), "=r"(r[1]) : "r"(a) : "memory");
}
__device__ __forceinline__ void mma(float* d, uint32_t a0, uint32_t a1, uint32_t a2, uint32_t a3, uint32_t b0, uint32_t b1) {
    asm("mma.sync.aligned.m16n8k16.row.col.f32.bf16.bf16.f32 {%0,%1,%2,%3}, {%4,%5,%6,%7}, {%8,%9}, {%0,%1,%2,%3};"
        : "+f"(d[0]), "+f"(d[1]), "+f"(d[2]), "+f"(d[3]) : "r"(a0), "r"(a1), "r"(a2), "r"(a3), "r"(b0), "r"(b1));
}
__device__ __forceinline__ void mmah(float* d, uint32_t a0, uint32_t a1, uint32_t a2, uint32_t a3, uint32_t b0, uint32_t b1) {
    asm("mma.sync.aligned.m16n8k16.row.col.f32.f16.f16.f32 {%0,%1,%2,%3}, {%4,%5,%6,%7}, {%8,%9}, {%0,%1,%2,%3};"
        : "+f"(d[0]), "+f"(d[1]), "+f"(d[2]), "+f"(d[3]) : "r"(a0), "r"(a1), "r"(a2), "r"(a3), "r"(b0), "r"(b1));
}
__device__ __forceinline__ void mma8(float* d, uint32_t a0, uint32_t a1, uint32_t b0) {
    asm("mma.sync.aligned.m16n8k8.row.col.f32.bf16.bf16.f32 {%0,%1,%2,%3}, {%4,%5}, {%6}, {%0,%1,%2,%3};"
        : "+f"(d[0]), "+f"(d[1]), "+f"(d[2]), "+f"(d[3]) : "r"(a0), "r"(a1), "r"(b0));
}
__device__ __forceinline__ uint32_t hadd2(uint32_t a, uint32_t b) {
    uint32_t r; asm("add.rn.bf16x2 %0, %1, %2;" : "=r"(r) : "r"(a), "r"(b)); return r;
}
__device__ __forceinline__ uint32_t pack2(float lo, float hi) {
    uint32_t r; asm("cvt.rn.bf16x2.f32 %0, %1, %2;" : "=r"(r) : "f"(hi), "f"(lo)); return r;
}
__device__ __forceinline__ uint32_t packh(float lo, float hi) {
    uint32_t r; asm("cvt.rn.f16x2.f32 %0, %1, %2;" : "=r"(r) : "f"(hi), "f"(lo)); return r;
}
__device__ __forceinline__ float bflo(uint32_t v) { return __uint_as_float(v << 16); }
__device__ __forceinline__ float bfhi(uint32_t v) { return __uint_as_float(v & 0xffff0000u); }
__device__ __forceinline__ float ex2(float x) { float r; asm("ex2.approx.ftz.f32 %0, %1;" : "=f"(r) : "f"(x)); return r; }
__device__ __forceinline__ void sts128(uint32_t a, uint32_t x, uint32_t y, uint32_t z, uint32_t w) {
    asm volatile("st.shared.v4.b32 [%0], {%1,%2,%3,%4};" ::"r"(a), "r"(x), "r"(y), "r"(z), "r"(w) : "memory");
}
__device__ __forceinline__ void sts64(uint32_t a, uint32_t x, uint32_t y) {
    asm volatile("st.shared.v2.b32 [%0], {%1,%2};" ::"r"(a), "r"(x), "r"(y) : "memory");
}
__device__ __forceinline__ void sts32(uint32_t a, uint32_t x) { asm volatile("st.shared.b32 [%0], %1;" ::"r"(a), "r"(x) : "memory"); }
__device__ __forceinline__ uint4 lds128(uint32_t a) {
    uint4 v; asm volatile("ld.shared.v4.b32 {%0,%1,%2,%3}, [%4];" : "=r"(v.x), "=r"(v.y), "=r"(v.z), "=r"(v.w) : "r"(a) : "memory"); return v;
}
__device__ __forceinline__ uint2 lds64(uint32_t a) {
    uint2 v; asm volatile("ld.shared.v2.b32 {%0,%1}, [%2];" : "=r"(v.x), "=r"(v.y) : "r"(a) : "memory"); return v;
}
__device__ __forceinline__ uint32_t haddh(uint32_t a, uint32_t b) {
    uint32_t r; asm("add.rn.f16x2 %0, %1, %2;" : "=r"(r) : "r"(a), "r"(b)); return r;
}
__device__ __forceinline__ uint32_t lds32(uint32_t a) { uint32_t v; asm volatile("ld.shared.b32 %0, [%1];" : "=r"(v) : "r"(a) : "memory"); return v; }
__device__ __forceinline__ int grab_tile(unsigned* ctr) {
    int v; asm volatile("atom.relaxed.gpu.global.inc.u32 %0, [%1], 0x7fffffff;" : "=r"(v) : "l"(ctr) : "memory"); return v;
}
__device__ __forceinline__ uint32_t opaque(uint32_t v) { uint32_t r; asm volatile("mov.b32 %0, %1;" : "=r"(r) : "r"(v)); return r; }
__device__ __forceinline__ uint32_t select_lt(uint32_t x, uint32_t lim, uint32_t lo, uint32_t hi) {
    uint32_t r; asm("{.reg .pred p; setp.lt.u32 p, %1, %2; selp.b32 %0, %3, %4, p;}" : "=r"(r) : "r"(x), "r"(lim), "r"(lo), "r"(hi)); return r;
}
__device__ __forceinline__ int laneid() { int r; asm volatile("mov.u32 %0, %%laneid;" : "=r"(r)); return r; }
__device__ __forceinline__ unsigned clock32() { unsigned c; asm volatile("mov.u32 %0, %%clock;" : "=r"(c)); return c; }
__device__ __forceinline__ float rsq(float x) { float r; asm("rsqrt.approx.ftz.f32 %0, %1;" : "=f"(r) : "f"(x)); return r; }
__device__ __forceinline__ float rcp(float x) { float r; asm("rcp.approx.ftz.f32 %0, %1;" : "=f"(r) : "f"(x)); return r; }
__device__ __forceinline__ float lg2(float x) { float r; asm("lg2.approx.ftz.f32 %0, %1;" : "=f"(r) : "f"(x)); return r; }
__device__ __forceinline__ float f(uint32_t v) { return __uint_as_float(v); }
__device__ __forceinline__ uint32_t u(float v) { return __float_as_uint(v); }

constexpr uint32_t ONES = 0x3F803F80u;
constexpr float QSCALE = 0.07216878364870322f * 1.4426950408889634f;

__device__ __forceinline__ void issue_tile(const CUtensorMap* m0, const CUtensorMap* m1, uint32_t sb, int s, int tl, uint64_t pol) {
    const uint32_t full = sb + SM_BAR + s * 8, dst = sb + SM_STAGES + s * STAGE;
    const int par = tl * TP, y = par >> 8, x = par & 255;
    asm volatile("cp.async.bulk.tensor.5d.shared::cluster.global.mbarrier::complete_tx::bytes.L2::cache_hint [%0], [%1, {%3,%4,%3,%3,%5}], [%2], %6;"
                 ::"r"(dst), "l"(m0), "r"(full), "r"(0), "r"(x), "r"(2 * y), "l"(pol) : "memory");
    asm volatile("cp.async.bulk.tensor.4d.shared::cluster.global.mbarrier::complete_tx::bytes.L2::cache_hint [%0], [%1, {%3,%4,%3,%5}], [%2], %6;"
                 ::"r"(dst + TP * 4 * C * 2), "l"(m1), "r"(full), "r"(0), "r"(x), "r"(y), "l"(pol) : "memory");
}

__device__ __forceinline__ uint4 ldg_relaxed(const uint4* p) {
    uint4 v; asm volatile("ld.relaxed.gpu.global.v4.u32 {%0,%1,%2,%3}, [%4];" : "=r"(v.x), "=r"(v.y), "=r"(v.z), "=r"(v.w) : "l"(p) : "memory"); return v;
}
__device__ __forceinline__ uint32_t ldg_relaxed32(const void* p) {
    uint32_t v; asm volatile("ld.relaxed.gpu.global.u32 %0, [%1];" : "=r"(v) : "l"(p) : "memory"); return v;
}
__device__ __forceinline__ void stg_relaxed(uint4* p, uint32_t x, uint32_t y, uint32_t z, uint32_t w) {
    asm volatile("st.relaxed.gpu.global.v4.u32 [%0], {%1,%2,%3,%4};" ::"l"(p), "r"(x), "r"(y), "r"(z), "r"(w) : "memory");
}
__device__ __forceinline__ void stg_relaxed32(void* p, uint32_t x) { asm volatile("st.relaxed.gpu.global.u32 [%0], %1;" ::"l"(p), "r"(x) : "memory"); }
__device__ __forceinline__ bool has(const uint4& v, uint32_t m) { return v.x == m || v.y == m || v.z == m || v.w == m; }
__device__ __forceinline__ uint32_t hadd2v(uint32_t a, uint32_t b) {
    uint32_t r; asm volatile("add.rn.bf16x2 %0, %1, %2;" : "=r"(r) : "r"(a), "r"(b)); return r;
}

__device__ __forceinline__ void red8h(uint4* p, uint32_t x, uint32_t y, uint32_t z, uint32_t w) {
    asm volatile("red.relaxed.gpu.global.add.noftz.v4.f16x2 [%0], {%1,%2,%3,%4};" ::"l"(p), "r"(x), "r"(y), "r"(z), "r"(w) : "memory");
}
__device__ __forceinline__ uint4 lds128v(uint32_t a) {
    uint4 v; asm volatile("ld.volatile.shared.v4.b32 {%0,%1,%2,%3}, [%4];" : "=r"(v.x), "=r"(v.y), "=r"(v.z), "=r"(v.w) : "r"(a) : "memory"); return v;
}
__device__ __forceinline__ uint32_t brow(int r) { return RD_B + r * 80 + (r >> 3) * 64; }

constexpr int ACC_HI = 65536;
static_assert(offsetof(Scratch, acc_hi) <= ACC_HI && offsetof(Scratch, acc_hi) + sizeof(Scratch::acc_hi) >= ACC_HI + 32768, "scratch");
__device__ __forceinline__ uint32_t acc_line(int s, int k) {
    return (k >> 2) * 16384 + (k & 2) * 6144 + (k & 1) * 1024 + (s & 1) * 256 + (s & 2) * 1024 + (s >> 2) * ACC_HI;
}

__device__ __forceinline__ int first_row() { return (blockIdx.x & 14) ^ 8; }

enum { B_QK = 1, B_QN = 2, B_GRP = 3  , B_Q = 5, B_MERGE = 6, B_ALL = 7, B_MAX = 8  , B_WARP = 10, B_SLOW = 12, B_PARK = 13, B_CLEAN = 14, B_RDY = 15 };

__device__ __noinline__ void slow_rows(const char* __restrict__ f0, const char* __restrict__ f1, const __nv_bfloat16* __restrict__ q,
                                       const __nv_bfloat16* __restrict__ wq, const __nv_bfloat16* __restrict__ wk, const uint32_t sb)
{
    const int warp = threadIdx.x >> 5, lane = threadIdx.x & 31;
    float* const sm = reinterpret_cast<float*>(__cvta_shared_to_generic(sb + RD_W));
    for (int i = threadIdx.x; i < 2 * C; i += 128) sm[i] = __bfloat162float(q[first_row() * C + i]);
    bar_sync(B_SLOW, 128);
#pragma unroll 1
    for (int j = threadIdx.x; j < 2 * C; j += 128) {
        const float* const x = sm + j / C * C;
        float mu = 0.f, var = 0.f, s = 0.f;
#pragma unroll 1
        for (int i = 0; i < C; i++) mu += x[i];
        mu *= 1.f / C;
#pragma unroll 4
        for (int i = 0; i < C; i++) { var = fmaf(x[i] - mu, x[i] - mu, var); s = fmaf(x[i] - mu, __bfloat162float(wq[i * C + j % C]), s); }
        sm[4 * C + j] = s * rsq(var * (1.f / C) + 1e-5f);
    }
    bar_sync(B_SLOW, 128);
#pragma unroll 1
    for (int j = threadIdx.x; j < 2 * C; j += 128) {
        float s = 0.f;
#pragma unroll 4
        for (int i = 0; i < C; i++) s = fmaf(sm[4 * C + j / C * C + i], __bfloat162float(wk[j % C * C + i]), s);
        sm[j] = s * QSCALE;
    }
    bar_sync(B_SLOW, 128);
    float k[2][6], a[2][6], m[2], l[2];
#pragma unroll
    for (int r = 0; r < 2; r++) {
        m[r] = -INFINITY; l[r] = 0.f;
#pragma unroll
        for (int i = 0; i < 6; i++) { k[r][i] = sm[r * C + 64 * (i >> 1) + 2 * lane + (i & 1)]; a[r][i] = 0.f; }
    }
#pragma unroll 1
    for (int par = warp; par < W1 * W1; par += 4) {
        const uint32_t* p0 = reinterpret_cast<const uint32_t*>(f0 + (size_t)((par >> 8) * 2 * W0 + (par & 255) * 2) * (C * 2)) + lane;
        const uint32_t* p1 = reinterpret_cast<const uint32_t*>(f1 + (size_t)par * (C * 2)) + lane;
        uint32_t v[4][3];
#pragma unroll
        for (int i = 0; i < 3; i++)
#pragma unroll
            for (int j = 0; j < 4; j++) v[j][i] = hadd2(__ldg(p0 + ((j >> 1) * W0 + (j & 1)) * (C / 2) + 32 * i), __ldg(p1 + 32 * i));
#pragma unroll
        for (int j = 0; j < 4; j++) {
            float x[6], s1 = 0.f, s2 = 0.f, d[2] = {0.f, 0.f};
#pragma unroll
            for (int i = 0; i < 3; i++) { x[2 * i] = bflo(v[j][i]); x[2 * i + 1] = bfhi(v[j][i]); s1 += x[2 * i] + x[2 * i + 1]; }
#pragma unroll
            for (int o = 1; o < 32; o <<= 1) s1 += __shfl_xor_sync(~0u, s1, o);
#pragma unroll
            for (int i = 0; i < 6; i++) {
                x[i] -= s1 * (1.f / C); s2 = fmaf(x[i], x[i], s2);
#pragma unroll
                for (int r = 0; r < 2; r++) d[r] = fmaf(x[i], k[r][i], d[r]);
            }
#pragma unroll
            for (int o = 1; o < 32; o <<= 1) {
                s2 += __shfl_xor_sync(~0u, s2, o);
#pragma unroll
                for (int r = 0; r < 2; r++) d[r] += __shfl_xor_sync(~0u, d[r], o);
            }
            const float rs = rsq(s2 * (1.f / C) + 1e-5f);
#pragma unroll
            for (int r = 0; r < 2; r++) {
                const float nm = fmaxf(m[r], d[r] * rs), al = ex2(m[r] - nm), p = ex2(d[r] * rs - nm);
                m[r] = nm; l[r] = fmaf(l[r], al, p);
#pragma unroll
                for (int i = 0; i < 6; i++) a[r][i] = fmaf(a[r][i], al, x[i] * (p * rs));
            }
        }
    }
    bar_sync(B_SLOW, 128);
#pragma unroll
    for (int r = 0; r < 2; r++) {
        float* const o = sm + ((r * 4 + warp) * 32 + lane) * 8;
#pragma unroll
        for (int i = 0; i < 6; i++) o[i] = a[r][i];
        o[6] = l[r]; o[7] = m[r];
    }
    bar_sync(B_SLOW, 128);
    if (warp < 2) {
        const int r = warp;
        const float* const o = sm + (r * 128 + lane) * 8;
        float M = o[7], x[7] = {0.f, 0.f, 0.f, 0.f, 0.f, 0.f, 0.f};
#pragma unroll
        for (int w = 1; w < 4; w++) M = fmaxf(M, o[256 * w + 7]);
#pragma unroll
        for (int w = 0; w < 4; w++) {
            const float e = ex2(o[256 * w + 7] - M);
#pragma unroll
            for (int i = 0; i < 7; i++) x[i] = fmaf(o[256 * w + i], e, x[i]);
        }
        const float rl = 1.f / x[6];
        sts128(sb + RD_B2 + brow(8 * (lane >> 4) + 4 * r + (lane & 3)) + ((lane >> 2) & 3) * 16, packh(x[0] * rl, x[1] * rl), packh(x[2] * rl, x[3] * rl), packh(x[4] * rl, x[5] * rl), lane ? 0u : 0x3C00u);
    }
}

template <bool FIRST>
__device__ __forceinline__ void project(const uint32_t ar, const uint32_t br, const bool hi, const float ws0, const float ws1, const float qv0, const float qv1,
                                        __nv_bfloat16* op0, __nv_bfloat16* op1, Scratch* scr)
{
    uint4 wa[3][6], x[4];
#pragma unroll
    for (int i = 0; i < 18; i++) wa[i / 6][i % 6] = lds128v(ar + i * 512);
    if (FIRST) { bar_arrive(B_CLEAN, NTHREADS); bar_sync(B_RDY, 192); }
    else bar_sync(B_SLOW, 128);
    if (FIRST && threadIdx.x == 0) TSX(8, 0);
#pragma unroll
    for (int j = 0; j < 4; j++) x[j] = lds128v(br + 16 * j);
    float o[7][4];
#pragma unroll
    for (int j = 0; j < 7; j++) o[j][0] = o[j][1] = o[j][2] = o[j][3] = 0.f;
#pragma unroll
    for (int i = 0; i < 2; i++) {
        mmah(o[6], 0x3C00u, 0x3C00u, 0x3C00u, 0x3C00u, x[2 * i].w, x[2 * i + 1].w);
#pragma unroll
        for (int n = 0; n < 3; n++) mmah(o[2 * n + i], wa[n][2 * i].x, wa[n][2 * i].y, wa[n][2 * i].z, wa[n][2 * i].w, x[2 * i].x, x[2 * i].y);
#pragma unroll
        for (int n = 0; n < 3; n++) mmah(o[2 * n + 1 - i], wa[n][2 * i + 1].x, wa[n][2 * i + 1].y, wa[n][2 * i + 1].z, wa[n][2 * i + 1].w, x[2 * i + 1].x, x[2 * i + 1].y);
#pragma unroll
        for (int n = 0; n < 3; n++) mmah(o[2 * n + i], wa[n][4 + i].x, wa[n][4 + i].y, wa[n][4 + i].z, wa[n][4 + i].w, x[2 * i].z, x[2 * i + 1].z);
    }
    const float L = o[6][0] + o[6][1], r = rcp(L);
    const float y0 = hi ? (o[2][0] + o[2][3]) + (o[3][0] + o[3][3]) : (o[0][0] + o[0][3]) + (o[1][0] + o[1][3]), y1 = (o[4][0] + o[4][3]) + (o[5][0] + o[5][3]);
    const uint32_t y = pack2(fmaf(y0, r * ws0, qv0), fmaf(y1, r * ws1, qv1));
    asm volatile("{.reg .b16 l, h; mov.b32 {l, h}, %2; st.global.b16 [%0], l; st.global.b16 [%1], h;}" ::"l"(op0), "l"(op1), "r"(y) : "memory");
    if (FIRST && threadIdx.x == 0) TSD(11, y);
    if (FIRST)
        asm volatile("{.reg .pred p; .reg .f32 a; abs.f32 a, %1; setp.ge.f32 p, %0, 0f3B000000; setp.le.and.f32 p, %0, 0f45000000, p; setp.lt.and.f32 p, a, 0f7F800000, p;"
                     " vote.sync.all.pred p, p, 0xffffffff; @p exit;}" ::"f"(L), "f"(y0) : "memory");
}

__device__ __forceinline__ void reducer(const char* __restrict__ f0, const char* __restrict__ f1, const __nv_bfloat16* __restrict__ q, const __nv_bfloat16* __restrict__ wq, const __nv_bfloat16* __restrict__ wk,
                                        Scratch* scr, const __nv_bfloat16* __restrict__ wv, const __nv_bfloat16* __restrict__ wo,
                                        __nv_bfloat16* __restrict__ out, const uint32_t sb, const int GS)
{
    const int warp = threadIdx.x >> 5, lane = threadIdx.x & 31, b = blockIdx.x;
    const int g = lane >> 2, t = lane & 3;
    char* const ap = reinterpret_cast<char*>(g_acc);
    if (threadIdx.x == 256) TS(0);
    if (b < NSRC && warp < 8) {
        const uint32_t wqs = sb + RD_W, wbar = sb + RD_BAR;
        const int hr = lane >> 4, qt = (lane >> 2) & 3, sub = lane & 3;
        const uint32_t* qp = reinterpret_cast<const uint32_t*>(q + (warp + 8 * hr) * C + 48 * qt + 6 * sub);
        uint32_t qw[6];
#pragma unroll
        for (int j = 0; j < 3; j++) { qw[j] = __ldg(qp + j); qw[3 + j] = __ldg(qp + 12 + j); }
        if (lane == 0) { mbar_init(wbar + warp * 8, 1); asm volatile("fence.mbarrier_init.release.cluster;" ::: "memory"); mbar_expect(wbar + warp * 8, 9216);
            asm volatile("cp.async.bulk.shared::cluster.global.mbarrier::complete_tx::bytes [%0], [%1], 9216, [%2];"
                         ::"r"(wqs + warp * 9232), "l"(wq + 24 * warp * C), "r"(wbar + warp * 8) : "memory");
        }
        __syncwarp();
        if (threadIdx.x == 0) TSP(2, 0);
        float e[12];
#pragma unroll
        for (int j = 0; j < 6; j++) { e[2 * j] = bflo(qw[j]); e[2 * j + 1] = bfhi(qw[j]); }
        float sm = ((e[0] + e[1]) + (e[2] + e[3])) + ((e[4] + e[5]) + (e[6] + e[7])) + ((e[8] + e[9]) + (e[10] + e[11]));
#pragma unroll
        for (int o = 1; o < 16; o <<= 1) sm += __shfl_xor_sync(~0u, sm, o);
        if (threadIdx.x == 0) TSP(5, u(sm));
        float v0 = 0.f, v1 = 0.f;
#pragma unroll
        for (int j = 0; j < 12; j++) e[j] -= sm * (1.f / C);
#pragma unroll
        for (int j = 0; j < 6; j++) { v0 = fmaf(e[j], e[j], v0); v1 = fmaf(e[6 + j], e[6 + j], v1); }
        v0 += v1;
#pragma unroll
        for (int o = 1; o < 16; o <<= 1) v0 += __shfl_xor_sync(~0u, v0, o);
        const float rq = rsq(v0 * (1.f / C) + 1e-5f);
#pragma unroll
        for (int j = 0; j < 6; j++)
            sts32(sb + RD_QN + (3 * sub + (j >> 1)) * 512 + (4 * warp + qt) * 16 + (2 * (j & 1) + hr) * 4, pack2(e[j] * rq, e[6 + j] * rq));
        if (threadIdx.x == 0) TSP(8, 0);
        uint32_t wkf[2][3];
#pragma unroll
        for (int i = 0; i < 2; i++)
#pragma unroll
            for (int j = 0; j < 3; j++) wkf[i][j] = __ldg(reinterpret_cast<const uint32_t*>(wk + (16 * b + 8 * i + g) * C + 24 * warp + 8 * j + 2 * t));
        bar_sync(B_QN, 256);
        float acc[2][3][4];
#pragma unroll
        for (int i = 0; i < 3; i++)
#pragma unroll
            for (int e = 0; e < 4; e++) acc[0][i][e] = acc[1][i][e] = 0.f;
        const uint32_t ba = wqs + (lane & 7) * 9232 + (lane >> 3) * 384 + 48 * warp;
        uint4 a[12];
#pragma unroll
        for (int kk = 0; kk < 12; kk++) a[kk] = lds128(sb + RD_QN + kk * 512 + lane * 16);
        mbar_wait(wbar + (lane & 7) * 8, 0);
        __syncwarp();
        if (threadIdx.x == 0) TSP(4, 0);
#pragma unroll
        for (int kp = 0; kp < 6; kp++)
#pragma unroll
            for (int i = 0; i < 3; i++) {
                uint32_t bb[4];
                ldsm4t(bb, ba + kp * 1536 + i * 16);
                mma(acc[0][i], a[2 * kp].x, a[2 * kp].y, a[2 * kp].z, a[2 * kp].w, bb[0], bb[1]);
                mma(acc[1][i], a[2 * kp + 1].x, a[2 * kp + 1].y, a[2 * kp + 1].z, a[2 * kp + 1].w, bb[2], bb[3]);
            }
        if (threadIdx.x == 0) TSP(7, u(acc[1][2][3]));
        float kq[2][4] = {{0.f, 0.f, 0.f, 0.f}, {0.f, 0.f, 0.f, 0.f}};
#pragma unroll
        for (int j = 0; j < 3; j++) {
            const uint32_t a0 = pack2(acc[0][j][0] + acc[1][j][0], acc[0][j][1] + acc[1][j][1]), a1 = pack2(acc[0][j][2] + acc[1][j][2], acc[0][j][3] + acc[1][j][3]);
            mma8(kq[0], a0, a1, wkf[0][j]);
            mma8(kq[1], a0, a1, wkf[1][j]);
        }
        if (warp < 7) {
            sts128(sb + RD_KQ + warp * 1024 + lane * 16, u(kq[0][0]), u(kq[0][1]), u(kq[0][2]), u(kq[0][3]));
            sts128(sb + RD_KQ + warp * 1024 + 512 + lane * 16, u(kq[1][0]), u(kq[1][1]), u(kq[1][2]), u(kq[1][3]));
            bar_arrive(B_Q, 256);
        } else {
            bar_sync(B_Q, 256);
#pragma unroll
            for (int w = 0; w < 7; w++)
#pragma unroll
                for (int i = 0; i < 2; i++) {
                    const uint4 o = lds128(sb + RD_KQ + w * 1024 + i * 512 + lane * 16);
                    kq[i][0] += f(o.x); kq[i][1] += f(o.y); kq[i][2] += f(o.z); kq[i][3] += f(o.w);
                }
            stg_relaxed(g_qk + b * 32 + lane, ~pack2(kq[0][0] * QSCALE, kq[0][1] * QSCALE), ~pack2(kq[0][2] * QSCALE, kq[0][3] * QSCALE),
                        ~pack2(kq[1][0] * QSCALE, kq[1][1] * QSCALE), ~pack2(kq[1][2] * QSCALE, kq[1][3] * QSCALE));
            if (lane == 0) TS(10);
        }
    } else if (warp == 8 && !(b & 1)) {
#pragma unroll
        for (int i = 0; i < 2; i++) stg_relaxed(reinterpret_cast<uint4*>(ap + acc_line(b >> 1, 4 * i + (lane >> 3))) + (lane & 7), 0, 0, 0, 0);
        __threadfence();
    } else if (b >= NSRC) {
        if (b == NSRC && warp == 0) stg_relaxed32(g_mmax + lane, 0);
        const unsigned c0 = clock32();
        for (int it = 0; it < 8; it++) {
            __nanosleep(500);
            if (clock32() - c0 > 4400) break;
        }
    }
    bar_sync(B_ALL, NTHREADS);

#pragma unroll 1
    for (int r = 0; r < 3; r++) {
        uint4 v[8];
#pragma unroll
        for (int k = 0; k < 8; k++) {
            const int idx = (8 * r + k) * 384 + threadIdx.x;
            v[k] = __ldg(reinterpret_cast<const uint4*>(idx < 4608 ? wv : wo - C * C) + idx);
        }
#pragma unroll
        for (int k = 0; k < 8; k++) {
            const int idx = (8 * r + k) * 384 + threadIdx.x, row = idx / 24;
            sts128(sb + RD_W + row * WROW + (idx - 24 * row) * 16, v[k].x, v[k].y, v[k].z, v[k].w);
        }
    }
    bar_sync(B_ALL, NTHREADS);
    if (warp < 6) {
        const int col = 96 * (b & 1) + 16 * warp;
        float d[24][4];
#pragma unroll
        for (int i = 0; i < 24; i++) d[i][0] = d[i][1] = d[i][2] = d[i][3] = 0.f;
        const int mi = lane >> 3, r = lane & 7;
        const uint32_t aa = sb + RD_W + (C + (mi >> 1) * 8 + r) * WROW + (col + (mi & 1) * 8) * 2;
        const uint32_t ba = sb + RD_W + ((mi >> 1) * 8 + r) * WROW + (mi & 1) * 16;
#pragma unroll 1
        for (int kk = 0; kk < 12; kk++) {
            uint32_t a[4];
            ldsm4t(a, aa + kk * 16 * WROW);
#pragma unroll
            for (int i = 0; i < 12; i++) {
                uint32_t bb[4];
                ldsm4(bb, ba + i * 16 * WROW + kk * 32);
                mma(d[2 * i], a[0], a[1], a[2], a[3], bb[0], bb[1]);
                mma(d[2 * i + 1], a[0], a[1], a[2], a[3], bb[2], bb[3]);
            }
        }
        float c0 = 0.f, c1 = 0.f, m0 = 0.f, m1 = 0.f;
#pragma unroll
        for (int i = 0; i < 24; i++) { c0 += d[i][0] + d[i][1]; c1 += d[i][2] + d[i][3]; }
        c0 += __shfl_xor_sync(~0u, c0, 1); c1 += __shfl_xor_sync(~0u, c1, 1);
        c0 += __shfl_xor_sync(~0u, c0, 2); c1 += __shfl_xor_sync(~0u, c1, 2);
        c0 *= 1.f / C; c1 *= 1.f / C;
#pragma unroll
        for (int i = 0; i < 24; i++) {
            d[i][0] -= c0; d[i][1] -= c0; d[i][2] -= c1; d[i][3] -= c1;
            m0 = fmaxf(m0, fmaxf(fabsf(d[i][0]), fabsf(d[i][1]))); m1 = fmaxf(m1, fmaxf(fabsf(d[i][2]), fabsf(d[i][3])));
        }
        m0 = fmaxf(m0, __shfl_xor_sync(~0u, m0, 1)); m1 = fmaxf(m1, __shfl_xor_sync(~0u, m1, 1));
        m0 = fmaxf(m0, __shfl_xor_sync(~0u, m0, 2)); m1 = fmaxf(m1, __shfl_xor_sync(~0u, m1, 2));
        const uint32_t e0 = min(max(u(m0) >> 23, 12u), 254u), e1 = min(max(u(m1) >> 23, 12u), 254u);
        const float s0 = f((265u - e0) << 23), s1 = f((265u - e1) << 23);
        const bool k0 = fabsf(c0) < INFINITY, k1 = fabsf(c1) < INFINITY;
#pragma unroll
        for (int j = 0; j < 6; j++) {
            const int n[4] = {j < 4 ? j : 8 + 2 * j, j < 4 ? 4 + j : 12 + 2 * j, j < 4 ? 8 + j : 9 + 2 * j, j < 4 ? 12 + j : 13 + 2 * j};
            uint32_t a[2][4];
#pragma unroll
            for (int e = 0; e < 4; e++) {
                a[0][e] = k0 ? packh(d[n[e]][0] * s0, d[n[e]][1] * s0) : 0u;
                a[1][e] = k1 ? packh(d[n[e]][2] * s1, d[n[e]][3] * s1) : 0u;
            }
#pragma unroll
            for (int e = 0; e < 2; e++) sts128(sb + RD_A + ((2 * warp + e) * 6 + j) * 512 + lane * 16, a[e][0], a[e][1], a[e][2], a[e][3]);
        }
        sts32(sb + RD_WS + 2 * warp * 128 + lane * 4, k0 ? (e0 - 11u) << 23 : u(c0));
        sts32(sb + RD_WS + (2 * warp + 1) * 128 + lane * 4, k1 ? (e1 - 11u) << 23 : u(c1));
        if (warp < 4) bar_sync(B_PARK, 192); else bar_arrive(B_PARK, 192);
        if (threadIdx.x == 0) TSE(6);
    }
    if (warp >= 4) {
        if (threadIdx.x == 128) {
            uint32_t m;
            for (int it = 0;; it++) {
                const int left = NT - 2 * NST * GS - (int)ldg_relaxed32(g_ctr);
                m = ldg_relaxed32(g_mmax + b);
                if (left <= REFT && m) break;
                if (left <= 0) { m = 0x80000000u; break; }
                if (it > SPIN_LIMIT) __trap();
                __nanosleep(300);
            }
            if (b & 1) for (int it = 0;; it++) {
                uint32_t r;
                asm volatile("ld.acquire.gpu.global.u32 %0, [%1];" : "=r"(r) : "l"(g_mref + b - 1) : "memory");
                if (r) break;
                if (it > SPIN_LIMIT) __trap();
            }
            asm volatile("st.release.gpu.global.u32 [%0], %1;" ::"l"(g_mref + b), "r"(~u(f(m >> 31 ? m ^ 0x80000000u : ~m) + 8.f)) : "memory");
            TSE(7);
        }
        __syncwarp();
        if (warp == 4) {
            uint4* p0 = g_qk + min(b, NSRC - 1) * 32 + lane;
            unsigned* p1 = lane == 1 && b == NSRC ? g_ctr : g_mref + b;
            asm volatile("" : "+l"(p0), "+l"(p1));
            bar_arrive(B_CLEAN, NTHREADS);
            bar_sync(B_RDY, 192);
            *p0 = make_uint4(0, 0, 0, 0);
            *p1 = 0;
            return;
        }
        bar_sync(B_CLEAN, NTHREADS);
        if (warp >= 5 + NPW) return;
        const uint4* const pa = reinterpret_cast<const uint4*>(ap + acc_line(b >> 1, lane >> 3)) + (lane & 7);
        const uint32_t bw = opaque(sb + brow(lane & 7) + (lane >> 3) * 16);
        const uint32_t n0 = packh(0.f, (float)GS), nstart = packh(0.f, (float)POLLN);
        for (int it = 0; ldg_relaxed32(ap + acc_line(b >> 1, 0) + 12) < nstart; it++)
            if (it > SPIN_LIMIT) __trap();
        for (const unsigned c = clock32(); clock32() - c < (warp - 5) * PGAP;) {}
        for (int it = 0;; it++) {
            const uint4 a0 = ldg_relaxed(pa), b0 = ldg_relaxed(pa + 1024);
            if (it > SPIN_LIMIT) __trap();
            bar_sync(B_WARP, 32);
            asm volatile("{.reg .pred p, q; .reg .b32 a; setp.ge.u32 p, %5, %10; setp.ge.and.u32 p, %9, %10, p; vote.sync.all.pred q, p, 0xffffffff; selp.b32 a, %0, %1, p;"
                         " st.shared.v4.b32 [a], {%2,%3,%4,%5}; st.shared.v4.b32 [a + 704], {%6,%7,%8,%9}; @q bar.arrive 15, 192; @q exit;}"
                         ::"r"(bw), "r"(bw - (RD_B - RD_QN)), "r"(a0.x), "r"(a0.y), "r"(a0.z), "r"(a0.w), "r"(b0.x), "r"(b0.y), "r"(b0.z), "r"(b0.w), "r"(n0) : "memory");
        }
    }
    const uint32_t br = opaque(sb + brow(8 * (g & 1) + 2 * (g & 2) + t));
    const bool hi = t >= 2;
    const int oi = (first_row() + (t & 1)) * C + 96 * (b & 1) + 24 * warp + g;
    const float qv0 = __bfloat162float(q[oi + 4 * (t & 2)]), qv1 = __bfloat162float(q[oi + 16]);
    const float ws0 = f(lds32(sb + RD_WS + (3 * warp + (t >> 1)) * 128 + lane * 4)), ws1 = f(lds32(sb + RD_WS + (3 * warp + 2) * 128 + lane * 4));
    __nv_bfloat16* op0 = out + oi + 4 * (t & 2), * op1 = out + oi + 16;
    asm volatile("" : "+l"(op0), "+l"(op1));
    const uint32_t ar = sb + RD_A + warp * 18 * 512 + lane * 16;
    project<true>(ar, br, hi, ws0, ws1, qv0, qv1, op0, op1, scr);
    slow_rows(f0, f1, q, wq, wk, sb);
    project<false>(ar, br + RD_B2, hi, ws0, ws1, qv0, qv1, op0, op1, scr);
}

struct Head { const char* p[5]; };

__global__ void __launch_bounds__(NTHREADS, 1)
attn_main(const __grid_constant__ Head H, Scratch* scr, const __nv_bfloat16* __restrict__ wv, const __nv_bfloat16* __restrict__ wo,
          __nv_bfloat16* __restrict__ out, const __nv_bfloat16* __restrict__ q,
          const __grid_constant__ CUtensorMap m0, const __grid_constant__ CUtensorMap m1)
{
    extern __shared__ char smem_raw[];
    const uint32_t sb = (s2u(smem_raw) + 1023u) & ~1023u;
    const int b = blockIdx.x - NRD;
    const int warp = __shfl_sync(~0u, threadIdx.x >> 5, 0);
    const uint32_t w = warp, ub = b & 255;
    const uint32_t off = select_lt(w, 4, ub * 2 + ((ub >> 4) + (w >> 1)) * (W0 / (2 * TP)) + (w & 1), select_lt(w, 5, ub, min(ub & 15, 11u))) * (2 * TP * C * 2);
    const uint32_t z = off >> 28 & 8;
    const char* const head = reinterpret_cast<const char*>(H.p);
    const char* const first = *reinterpret_cast<const char* const*>(head + (select_lt(w, 5, w * 2 & 8, 24 + (b >> 1 & 8)) + z)) + off;
    asm volatile("{.reg .pred p; setp.ge.s32 p, %1, 0; setp.lt.and.u32 p, %2, 6, p; @p cp.async.bulk.prefetch.L2.global [%0], %3;}"
                 ::"l"(first), "r"(b), "r"(w), "n"(2 * TP * C * 2) : "memory");
    static_assert(C * C * 2 == 12 * (2 * TP * C * 2), "12 slices per weight matrix");
    const int G = *reinterpret_cast<const int*>(head + 16 + (w >> 4) * 8) - NRD;
    const char* const f0 = H.p[0], * const f1 = H.p[1];
    const __nv_bfloat16* const wq = reinterpret_cast<const __nv_bfloat16*>(H.p[3]), * const wk = reinterpret_cast<const __nv_bfloat16*>(H.p[4]);
    if (b < 0) { reducer(f0, f1, q, wq, wk, scr, wv, wo, out, sb, G); return; }
    const int lane = laneid();
    const int g = lane >> 2, t = lane & 3;

    if (warp >= 8) {
        if (warp < 10) {
            const int p = warp - 8;
            const unsigned c0 = clock32();
            const uint32_t sbp = opaque(sb), bar = sbp + SM_BAR + p * 8;
            uint64_t pol; asm volatile("createpolicy.fractional.L2::evict_first.b64 %0, 1.0;" : "=l"(pol));
            if (elect()) {
                if (p == 0) TS(0);
                asm volatile("prefetch.tensormap [%0];" ::"l"(p ? &m1 : &m0) : "memory");
#pragma unroll
                for (int n = 0; n < NI; n++) mbar_init(bar + n * 16, 2);
                asm volatile("fence.mbarrier_init.release.cluster;" ::: "memory");
#pragma unroll
                for (int n = 0; n < NI; n++) {
                    mbar_expect(bar + n * 16, STAGE);
                    issue_tile(&m0, &m1, sbp, p + 2 * n, 2 * b + p + 2 * n * G, pol);
                    TR(0, 2 * n + p);
                    sts32(sbp + SM_FLAG + (p + 2 * n) * 4, 0);
                    mbar_arrive(bar + n * 16);
                }
#pragma unroll
                for (int n = 0; n < NS / 2; n++) {
                    if (n >= NI) mbar_init(bar + n * 16, 2);
                    mbar_init(bar + NS * 8 + n * 16, 1);
                }
                if (p == 0) mbar_init(sbp + SM_REF, 1);
                asm volatile("fence.mbarrier_init.release.cluster;" ::: "memory");
            }
            __syncwarp();
            bar_arrive(B_QK, NTHREADS);
            if (elect()) {
                int tl = 2 * b + p + 2 * NI * G;
                int s = p + 2 * NI; uint32_t ph = 1;
                int sa = p, na = 0; uint32_t pa = 0;
                bool late = false;
                for (int n = NI;; n++) {
                    const int d = n < NRAMP ? D0 : (tl >= NT - (TA) ? 1 : D1);
                    mbar_wait(sbp + SM_BAR + (NS + s) * 8, ph);
                    mbar_expect(sbp + SM_BAR + s * 8, STAGE);
                    if (n < NPACE) while (clock32() - c0 < (n ? T1 + (2 * (n - 1) + p) * TG : T0)) {}
                    while (n - na >= d) {
                        mbar_wait(sbp + SM_BAR + sa * 8, pa);
                        if (na < NS / 2) TR(1, 2 * na + p);
                        na++; sa += 2;
                        if (sa >= NS) { sa -= NS; pa ^= 1; }
                    }
                    issue_tile(&m0, &m1, sbp, s, tl, pol);
                    TR(0, 2 * n + p);
                    int nxt = tl + 2 * G;
                    if (n >= NST - 1) nxt = grab_tile(g_ctr) + 2 * NST * G;
                    const bool last = nxt >= NT;
                    uint32_t flag = last;
                    if (!late && nxt >= NT - MAXT - 16 * b) { late = true; flag |= 2; }
                    if (last) mbar_wait(sbp + SM_REF, 0);
                    sts32(sbp + SM_FLAG + s * 4, flag);
                    mbar_arrive(sbp + SM_BAR + s * 8);
                    if (last) break;
                    s += 2;
                    if (s >= NS) { s -= NS; ph ^= 1; }
                    tl = nxt;
                }
                if (p) TSE(5);
            }
            return;
        }
        const int h = threadIdx.x - 320;
        uint4 v[6];
        for (int it = 0;; it++) {
            bool miss = false;
#pragma unroll
            for (int k = 0; k < 6; k++) v[k] = ldg_relaxed(g_qk + k * 64 + h);
#pragma unroll
            for (int k = 0; k < 6; k++) miss |= has(v[k], 0);
            if (!miss) break;
            if (it > SPIN_LIMIT) __trap();
            if (it == 0) __nanosleep(QSLEEP);
        }
#pragma unroll
        for (int k = 0; k < 6; k++) sts128(sb + SM_QK + (k * 64 + h) * 16, ~v[k].x, ~v[k].y, ~v[k].z, ~v[k].w);
        __syncwarp();
        bar_sync(B_QK, NTHREADS);
        if (warp == 11) return;
        uint32_t r = 1;
        for (int it = 0;; it++) {
            __nanosleep(500);
            if (lane < NQ) asm volatile("ld.acquire.gpu.global.u32 %0, [%1];" : "=r"(r) : "l"(g_mref + lane) : "memory");
            if (__all_sync(~0u, r != 0)) break;
            if (it > SPIN_LIMIT) __trap();
        }
        if (lane < NQ) sts32(sb + SM_M + lane * 4, ~r);
        __syncwarp();
        if (lane == 0) { mbar_arrive(sb + SM_REF); TSE(7); }
        return;
    }

    const int grp = warp >> 2, cw = warp & 3;
    const int xp = lane & 7, mi = lane >> 3;
    const uint32_t offS1 = opaque(12288 + xp * 128 + ((mi ^ xp) << 4)), offS1x = opaque(offS1 ^ 64);
    const uint32_t offS0 = opaque(offS1 - 12288 + cw * 3072), offS0x = opaque(offS0 ^ 64);
    const uint32_t offT = opaque(mi * 3072 + xp * 128 + (((cw + 4 * grp) ^ xp) << 4)), offTx = opaque(offT ^ 64);
    const uint32_t offU = opaque(12288 + (mi % 3) * 1024 + xp * 128 + (((cw + 4 * (grp ^ (mi / 3))) ^ xp) << 4));
    const uint32_t offV = opaque(12288 + (1 + (mi & 1)) * 1024 + xp * 128 + (((cw + 4 * (grp ^ 1)) ^ xp) << 4));
    const int shl = opaque(9 * t), shl4 = opaque(9 * t + 4);
    const uint32_t pw = opaque((cw >> 1) * 512 + lane * 16 + (cw & 1) * 8), muw = opaque(1024 + t * 16 + cw * 4);
    const uint32_t prd = opaque(lane * 16), mur = opaque(1024 + t * 16), mof = g * 4;
    uint32_t pb0 = sb + SM_P + grp * 2 * PBUF;
    const uint32_t pbx = pb0 ^ (pb0 + PBUF);
    const bool odd = g & 1;
    const int barid = B_GRP + grp;
    const bool elected = cw == 3 && lane == 0;

    uint32_t qa[48];
    float r_lo, r_hi;
    bar_sync(B_QK, NTHREADS);
    {
        float rr[2][4] = {{0.f, 0.f, 0.f, 0.f}, {0.f, 0.f, 0.f, 0.f}};
#pragma unroll
        for (int kk = 0; kk < 12; kk++) {
            const uint4 v = lds128(sb + SM_QK + kk * 512 + lane * 16);
            qa[4 * kk] = v.x; qa[4 * kk + 1] = v.y; qa[4 * kk + 2] = v.z; qa[4 * kk + 3] = v.w;
            mma(rr[kk & 1], v.x, v.y, v.z, v.w, ONES, ONES);
        }
        r_lo = rr[0][0] + rr[1][0]; r_hi = rr[0][2] + rr[1][2];
    }
    if (threadIdx.x == 0) TS(1);

    float acc[6][4];
#pragma unroll
    for (int i = 0; i < 6; i++) acc[i][0] = acc[i][1] = acc[i][2] = acc[i][3] = 0.f;
    float m_lo = -INFINITY, m_hi = -INFINITY, l_lo = 0.f, l_hi = 0.f;
    float cm[4] = {0.f, 0.f, 0.f, 0.f};
    uint32_t xt[6][4], yt[6]; uint4 pa, pb, mv;
    uint4* dst = reinterpret_cast<uint4*>(reinterpret_cast<char*>(g_acc) + acc_line(g >> 1, warp) + (lane & 7) * 16);
    asm volatile("" : "+l"(dst));
    const uint32_t xof = __shfl_sync(~0u, 512 - lane * 8, lane);
    uint32_t ref_lo = 0, ref_hi = 0;
    const uint32_t mad = __shfl_sync(~0u, sb + SM_M + mof, lane);
    uint32_t one[2];
#pragma unroll
    for (int i = 0; i < 2; i++) one[i] = __shfl_sync(~0u, ONES + ((lane + i) >> (G >> 16) >> 16), lane);
    uint32_t st = sb + SM_STAGES + grp * STAGE;
    int s = grp; uint32_t ph = 0;
    while (true) {
        mbar_wait(sb + SM_BAR + s * 8, ph);
        PH(0, 0);
        const uint32_t stop = lds32(sb + SM_FLAG + s * 4);
        float sc[2][4], gr[2][4];
#pragma unroll
        for (int e = 0; e < 4; e++) sc[0][e] = sc[1][e] = gr[0][e] = gr[1][e] = 0.f;
#pragma unroll
        for (int qq = 0; qq < 6; qq++) {
            uint32_t x[4], y[4];
            ldsm4(x, st + (qq & 1 ? offS0x : offS0) + (qq >> 1) * 1024);
            ldsm4(y, st + (qq & 1 ? offS1x : offS1) + (qq >> 1) * 1024);
            uint32_t z[4];
#pragma unroll
            for (int e = 0; e < 4; e++) asm("fma.rn.bf16x2 %0, %1, %2, %3;" : "=r"(z[e]) : "r"(x[e]), "r"(one[e & 1]), "r"(y[e]));
#pragma unroll
            for (int e = 0; e < 4; e++) x[e] = hadd2(x[e], y[e]);
            mma(gr[0], z[0], one[0], z[1], one[1], x[0], x[1]);
            mma(gr[1], z[2], one[0], z[3], one[1], x[2], x[3]);
            mma(sc[0], qa[8 * qq], qa[8 * qq + 1], qa[8 * qq + 2], qa[8 * qq + 3], x[0], x[1]);
            mma(sc[1], qa[8 * qq + 4], qa[8 * qq + 5], qa[8 * qq + 6], qa[8 * qq + 7], x[2], x[3]);
        }
        ldsm4t(yt, st + offU);
        ldsm2t(yt + 4, st + offV);
#pragma unroll
        for (int i = 0; i < 6; i++) ldsm4t(xt[i], st + (i < 3 ? offT : offTx) + (i % 3) * 1024);

        const float mu0 = (gr[0][2] + gr[1][2]) * (1.f / C), mu1 = (gr[0][3] + gr[1][3]) * (1.f / C);
        const float mu = odd ? mu1 : mu0, ss = odd ? gr[0][1] + gr[1][1] : gr[0][0] + gr[1][0];
        const float rs = rsq(fmaxf(fmaf(-mu, mu, fmaf(ss, 1.f / C, 1e-5f)), 1e-5f));
        const float rs0 = __shfl_sync(~0u, rs, shl), rs1 = __shfl_sync(~0u, rs, shl4);
        const float u0 = fmaf(-mu0, r_lo, sc[0][0] + sc[1][0]), u1 = fmaf(-mu1, r_lo, sc[0][1] + sc[1][1]);
        const float u2 = fmaf(-mu0, r_hi, sc[0][2] + sc[1][2]), u3 = fmaf(-mu1, r_hi, sc[0][3] + sc[1][3]);
        const float d0 = fmaf(u0, rs0, -m_lo), d1 = fmaf(u1, rs1, -m_lo), d2 = fmaf(u2, rs0, -m_hi), d3 = fmaf(u3, rs1, -m_hi);
        PH(1, u(d0 + d2));
        float p0 = ex2(d0), p1 = ex2(d1), p2 = ex2(d2), p3 = ex2(d3);
        sts64(pb0 + pw, pack2(p0 * rs0, p1 * rs1), pack2(p2 * rs0, p3 * rs1));
        if (lane < 4) sts32(pb0 + muw, pack2(mu0, mu1));
        asm volatile("{.reg .pred p; setp.ne.u32 p, %2, 0; @p ld.shared.b32 %0, [%3]; @p ld.shared.b32 %1, [%3+32];}" : "+r"(ref_lo), "+r"(ref_hi) : "r"(stop & 1), "r"(mad) : "memory");
        const bool over = bar_any(barid, 128, fmaxf(fmaxf(d0, d1), fmaxf(d2, d3)) > LAZY);
        PH(3, 0);
        pa = lds128(pb0 + prd); pb = lds128(pb0 + prd + 512); mv = lds128(pb0 + mur);
        if (stop & 1) { l_lo += p0 + p1; l_hi += p2 + p3; break; }
        if (elected) mbar_arrive(sb + SM_BAR + (NS + s) * 8);
        if (__builtin_expect(over, 0)) {
            const int ln = laneid(), g = ln >> 2, t = ln & 3;
            const float s0 = u0 * rs0, s1 = u1 * rs1, s2 = u2 * rs0, s3 = u3 * rs1;
            float xl = fmaxf(s0, s1), xh = fmaxf(s2, s3);
            xl = fmaxf(xl, __shfl_xor_sync(~0u, xl, 1)); xh = fmaxf(xh, __shfl_xor_sync(~0u, xh, 1));
            xl = fmaxf(xl, __shfl_xor_sync(~0u, xl, 2)); xh = fmaxf(xh, __shfl_xor_sync(~0u, xh, 2));
            if (t < 2) sts32(sb + SM_MX + grp * 256 + ((g + 8 * t) * 4 + cw) * 4, u(t ? xh : xl));
            bar_sync(B_MAX + grp, 128);
            const uint4 ml4 = lds128(sb + SM_MX + grp * 256 + g * 16), mh4 = lds128(sb + SM_MX + grp * 256 + g * 16 + 128);
            const float nl = fmaxf(fmaxf(fmaxf(f(ml4.x), f(ml4.y)), fmaxf(f(ml4.z), f(ml4.w))), m_lo);
            const float nh = fmaxf(fmaxf(fmaxf(f(mh4.x), f(mh4.y)), fmaxf(f(mh4.z), f(mh4.w))), m_hi);
            p0 = ex2(s0 - nl); p1 = ex2(s1 - nl); p2 = ex2(s2 - nh); p3 = ex2(s3 - nh);
            sts64(pb0 + pw, pack2(p0 * rs0, p1 * rs1), pack2(p2 * rs0, p3 * rs1));
            const float al = ex2(m_lo - nl), ah = ex2(m_hi - nh);
            m_lo = nl; m_hi = nh;
            l_lo *= al; l_hi *= ah; cm[0] *= al; cm[2] *= ah;
#pragma unroll
            for (int i = 0; i < 6; i++) { acc[i][0] *= al; acc[i][1] *= al; acc[i][2] *= ah; acc[i][3] *= ah; }
            bar_sync(B_MAX + grp, 128);
            pa = lds128(pb0 + prd); pb = lds128(pb0 + prd + 512);
        }
        l_lo += p0 + p1; l_hi += p2 + p3;
#pragma unroll
        for (int i = 0; i < 6; i++) mma(acc[i], pa.x, pa.y, pa.z, pa.w, hadd2v(xt[i][0], yt[i]), hadd2v(xt[i][1], yt[i]));
        mma(cm, pa.x, pa.y, pa.z, pa.w, mv.x, mv.y);
#pragma unroll
        for (int i = 0; i < 6; i++) mma(acc[i], pb.x, pb.y, pb.z, pb.w, hadd2v(xt[i][2], yt[i]), hadd2v(xt[i][3], yt[i]));
        mma(cm, pb.x, pb.y, pb.z, pb.w, mv.z, mv.w);
        PH(4, u(acc[5][0]));
        if (stop) {
            const int ln = laneid(), g = ln >> 2, t = ln & 3;
            float a = l_lo + __shfl_xor_sync(~0u, l_lo, 1), c = l_hi + __shfl_xor_sync(~0u, l_hi, 1);
            a += __shfl_xor_sync(~0u, a, 2); c += __shfl_xor_sync(~0u, c, 2);
            const uint32_t m = u((t ? m_hi : m_lo) + lg2(fmaxf(t ? c : a, 1.f)));
            if (t < 2) asm volatile("red.relaxed.gpu.global.max.u32 [%0], %1;" ::"l"(g_mmax + g + 8 * t), "r"(m >> 31 ? ~m : m | 0x80000000u) : "memory");
        }
        pb0 ^= pbx;
        s += 2;
        st += 2 * STAGE;
        if (s >= NS) { s -= NS; ph ^= 1; st -= NS * STAGE; }
        asm volatile("" : "+r"(st));
    }
    const float al = ex2(m_lo - f(ref_lo)), ah = ex2(m_hi - f(ref_hi));
    mma(cm, pa.x, pa.y, pa.z, pa.w, mv.x, mv.y);
#pragma unroll
    for (int i = 3; i < 6; i++) mma(acc[i], pa.x, pa.y, pa.z, pa.w, hadd2v(xt[i][0], yt[i]), hadd2v(xt[i][1], yt[i]));
    mma(cm, pb.x, pb.y, pb.z, pb.w, mv.z, mv.w);
#pragma unroll
    for (int i = 3; i < 6; i++) mma(acc[i], pb.x, pb.y, pb.z, pb.w, hadd2v(xt[i][2], yt[i]), hadd2v(xt[i][3], yt[i]));
#pragma unroll
    for (int i = 0; i < 3; i++) mma(acc[i], pa.x, pa.y, pa.z, pa.w, hadd2v(xt[i][0], yt[i]), hadd2v(xt[i][1], yt[i]));
#pragma unroll
    for (int i = 0; i < 3; i++) mma(acc[i], pb.x, pb.y, pb.z, pb.w, hadd2v(xt[i][2], yt[i]), hadd2v(xt[i][3], yt[i]));
    if (threadIdx.x == grp * 128) TSE(2 + grp);
    if (threadIdx.x == grp * 128 + 96) TSX(2 + grp, u(acc[5][0]));

    const uint32_t xw = sb + SM_STAGES + grp * STAGE + cw * 768 + prd, xr = sb + SM_STAGES + (grp ^ 1) * STAGE + cw * 768 + prd;
    const float cl = -cm[0] * al, ch = -cm[2] * ah;
    uint32_t hl[6], hh[6];
#pragma unroll
    for (int i = 3; i < 6; i++) { hl[i] = packh(fmaf(acc[i][0], al, cl), fmaf(acc[i][1], al, cl)); hh[i] = packh(fmaf(acc[i][2], ah, ch), fmaf(acc[i][3], ah, ch)); }
    sts128(xw, hl[3], hl[4], hl[5], hh[3]);
    sts64(xw + xof, hh[4], hh[5]);
#pragma unroll
    for (int i = 0; i < 3; i++) { hl[i] = packh(fmaf(acc[i][0], al, cl), fmaf(acc[i][1], al, cl)); hh[i] = packh(fmaf(acc[i][2], ah, ch), fmaf(acc[i][3], ah, ch)); }
    const uint32_t w_lo = packh(l_lo * al, 1.f), w_hi = packh(l_hi * ah, 1.f);
    bar_sync(B_MERGE, 256);
    if (threadIdx.x == 224) TSX(4, 0);
    const uint4 o = lds128(xr);
    const uint2 o2 = lds64(xr + xof);
    red8h(dst + ACC_HI / 16, haddh(hl[0], o.x), haddh(hl[1], o.y), haddh(hl[2], o.z), w_lo);
    for (const unsigned c = clock32(); clock32() - c < RDEL;) {}
    red8h(dst, haddh(hh[0], o.w), haddh(hh[1], o2.x), haddh(hh[2], o2.y), w_hi);
    if (threadIdx.x == 0) TSE(4);
    if (threadIdx.x == 224) TSX(9, 0);
}

typedef CUresult (*EncodeFn)(CUtensorMap*, CUtensorMapDataType, cuuint32_t, void*, const cuuint64_t*, const cuuint64_t*,
                             const cuuint32_t*, const cuuint32_t*, CUtensorMapInterleave, CUtensorMapSwizzle,
                             CUtensorMapL2promotion, CUtensorMapFloatOOBfill);

}

extern "C" void kernel_launch(void* const* d_in, const int* in_sizes, int n_in, void* d_out, int out_size) {
    const __nv_bfloat16* q = (const __nv_bfloat16*)d_in[0];
    char* f0 = (char*)d_in[1];
    char* f1 = (char*)d_in[2];
    const __nv_bfloat16* wq = (const __nv_bfloat16*)d_in[3];
    const __nv_bfloat16* wk = (const __nv_bfloat16*)d_in[4];
    const __nv_bfloat16* wv = (const __nv_bfloat16*)d_in[5];
    const __nv_bfloat16* wo = (const __nv_bfloat16*)d_in[6];

    static EncodeFn enc = nullptr;
    static int grid = 0;
    static Scratch* scr = nullptr;
    if (!enc) {
        void* fn = nullptr; cudaDriverEntryPointQueryResult qr;
        cudaGetDriverEntryPoint("cuTensorMapEncodeTiled", &fn, cudaEnableDefault, &qr);
        enc = (EncodeFn)fn;
        cudaGetSymbolAddress((void**)&scr, g_scratch);
        int dev = 0, sms = 0;
        cudaGetDevice(&dev);
        cudaDeviceGetAttribute(&sms, cudaDevAttrMultiProcessorCount, dev);
        grid = sms < MAXG ? sms : MAXG;
        cudaFuncSetAttribute(attn_main, cudaFuncAttributeMaxDynamicSharedMemorySize, SMEM_BYTES);
    }
    CUtensorMap m0, m1;
    {
        cuuint64_t dims[5] = {64, W1, 3, 2, W0};
        cuuint64_t str[4] = {2 * C * 2, 128, C * 2, (cuuint64_t)W0 * C * 2};
        cuuint32_t box[5] = {64, TP, 3, 2, 2}, es[5] = {1, 1, 1, 1, 1};
        enc(&m0, CU_TENSOR_MAP_DATA_TYPE_BFLOAT16, 5, f0, dims, str, box, es, CU_TENSOR_MAP_INTERLEAVE_NONE,
            CU_TENSOR_MAP_SWIZZLE_128B, CU_TENSOR_MAP_L2_PROMOTION_NONE, CU_TENSOR_MAP_FLOAT_OOB_FILL_NONE);
    }
    {
        cuuint64_t dims[4] = {64, W1, 3, W1};
        cuuint64_t str[3] = {C * 2, 128, (cuuint64_t)W1 * C * 2};
        cuuint32_t box[4] = {64, TP, 3, 1}, es[4] = {1, 1, 1, 1};
        enc(&m1, CU_TENSOR_MAP_DATA_TYPE_BFLOAT16, 4, f1, dims, str, box, es, CU_TENSOR_MAP_INTERLEAVE_NONE,
            CU_TENSOR_MAP_SWIZZLE_128B, CU_TENSOR_MAP_L2_PROMOTION_NONE, CU_TENSOR_MAP_FLOAT_OOB_FILL_NONE);
    }
    const Head H = {{(const char*)f0, (const char*)f1, (const char*)(uintptr_t)grid, (const char*)wq, (const char*)wk}};
    attn_main<<<grid, NTHREADS, SMEM_BYTES, cudaStreamPerThread>>>(H, scr, wv, wo, (__nv_bfloat16*)d_out, q, m0, m1);
}
```
